```python
import torch

def _softmax(x, axis=-1):
    return torch.softmax(x, dim=axis)
def _gelu(x):
    return torch.nn.functional.gelu(x, approximate="tanh")
def _silu(x):
    return torch.nn.functional.silu(x)
def _sigmoid(x):
    return torch.sigmoid(x)
def _layernorm(x, axis=-1, eps=1e-5):
    m = x.mean(dim=axis, keepdim=True)
    v = x.var(dim=axis, keepdim=True, unbiased=False)
    return (x - m) / torch.sqrt(v + eps)
def _scatter_add(tgt, idx, src, axis=0):
    return tgt.clone().index_add_(axis, idx, src)
def _segment_sum(src, seg, n):
    out = torch.zeros((n,) + src.shape[1:], dtype=src.dtype)
    return out.index_add_(0, seg, src)
def _pad(x, pw):
    flat = tuple(v for pair in reversed(pw) for v in pair)
    return torch.nn.functional.pad(x, flat)

kernel_name = 'recurrent_scan__linear_attn_block__dense_activation_gelu__prompt'

def setup_inputs():

    _w = (lambda a: (lambda t: t.to(torch.bfloat16) if t.is_floating_point() else t)(torch.as_tensor(a)))
    def _A_setup():
        B, S, D = 1, 2048, 576
        return {
            "x": _w((lambda *s: torch.randn(*s, dtype=torch.bfloat16) * 0.05)(B, S, D)),
            "wqkv": _w((lambda *s: torch.randn(*s, dtype=torch.bfloat16) * 0.2)(D, 3 * D)),
            "wo": _w((lambda *s: torch.randn(*s, dtype=torch.bfloat16) * 0.2)(D, D)),
        }
    _A_in = _A_setup()

    def _B_setup():
        B, S, D, F = 1, 2048, 576, 4608
        return {
            "x": _w((lambda *s: torch.randn(*s, dtype=torch.bfloat16) * 0.05)(B, S, D)),
            "w1": _w((lambda *s: torch.randn(*s, dtype=torch.bfloat16) * 0.4)(D, F) * (D ** -0.5)),
            "b1": _w((lambda *s: torch.randn(*s, dtype=torch.bfloat16) * 12.8)(F) * 0.01),
            "w2": _w((lambda *s: torch.randn(*s, dtype=torch.bfloat16) * 0.2)(F, D) * (F ** -0.5)),
            "b2": _w((lambda *s: torch.randn(*s, dtype=torch.bfloat16) * 1.6)(D) * 0.01),
        }
    _B_in = _B_setup()

    return {
        "A_x": _A_in["x"],
        "A_wqkv": _A_in["wqkv"],
        "A_wo": _A_in["wo"],
        "B_x": _B_in["x"],
        "B_w1": _B_in["w1"],
        "B_b1": _B_in["b1"],
        "B_w2": _B_in["w2"],
        "B_b2": _B_in["b2"],
    }

def reference(A_x, A_wqkv, A_wo, B_x, B_w1, B_b1, B_w2, B_b2):
    def _A_ref(x, wqkv, wo):
        B, S, D = x.shape
        H = 32; Dh = D // H
        qkv = (lambda x, *d: x.permute(*d))((x @ wqkv).reshape(B, S, 3, H, Dh), 2, 0, 3, 1, 4)
        q, k, v = qkv[0], qkv[1], qkv[2]
        phi = lambda t: torch.where(t > 0, t + 1, torch.exp(t)) + 1e-6
        pq, pk = phi(q), phi(k)
        kv = torch.einsum("bhsd,bhse->bhde", pk, v)
        z = torch.einsum("bhsd->bhd", pk)
        num = torch.einsum("bhqd,bhde->bhqe", pq, kv)
        den = torch.einsum("bhqd,bhd->bhq", pq, z)[..., None] + 1e-6
        o = num / den
        return (lambda x, *d: x.permute(*d))(o, 0, 2, 1, 3).reshape(B, S, D) @ wo

    def _B_ref(x, w1, b1, w2, b2):
        h = torch.einsum("bsd,df->bsf", x, w1) + b1
        h = _gelu(h)
        return torch.einsum("bsf,fd->bsd", h, w2) + b2

    x = A_x
    xn = _layernorm(x, axis=-1)
    s = _A_ref(xn, A_wqkv, A_wo)
    g = _silu(_B_ref(xn, B_w1, B_b1, B_w2, B_b2))
    return x + s * g
```

```cpp
#include <cuda_runtime.h>
#include <cuda.h>
#include <cuda_bf16.h>
#include <stdint.h>

#define YF32 0

namespace {
constexpr int WAIT_ITERS = 3000000;

constexpr int SEQ = 2048, DM = 576, FF = 4608;
constexpr int NMAIN = 128, NAUX = 4;

constexpr uint32_t SB    = 0x400;
constexpr uint32_t HA    = SB;
constexpr uint32_t XB    = SB + 131072;
constexpr uint32_t RING  = SB + 147456;
constexpr uint32_t SLOT  = 24576;
constexpr uint32_t MISC  = SB + 221184;
constexpr uint32_t BARS  = MISC;
constexpr uint32_t ONES  = MISC + 256;
constexpr uint32_t B1S   = MISC + 512;
constexpr uint32_t B2S   = MISC + 2816;
constexpr uint32_t EPO   = MISC + 3072;
constexpr uint32_t SMEM_BYTES = 221184 + 3200;
constexpr uint32_t PKT   = HA + 32768;
constexpr uint32_t VT    = HA + 51200;
constexpr uint32_t PQT   = HA + 98304;
constexpr uint32_t KVB   = HA + 116736;
constexpr uint32_t QNG   = 144 * 16 + 16;

enum { B_FULL = 0, B_FULLQ = 3, B_EMPTY = 6, B_XFULL = 9, B_OFULL = 12, B_HFREE = 15, B_KVB = 16, B_YRDY = 17, B_EV = 18  , B_COUNT = 22 };
__device__ __forceinline__ constexpr uint32_t bar(int i) { return BARS + 8u * i; }

constexpr int YT_BYTES = YF32 ? 32768 : 16384;
__device__ __align__(1024) __nv_bfloat16 g_o[SEQ * DM];
__device__ __align__(1024) unsigned char g_yacc[2 * 16 * 9 * YT_BYTES];
__device__ __align__(128) float g_kv[2 * 8 * 72 * 20];
__device__ __align__(128) unsigned int g_cnt[(8 + 16 + 16 * 9) * 8];
__device__ unsigned int g_epoch[NMAIN + NAUX];
__device__ __forceinline__ unsigned int* cnt_kv(int j) { return g_cnt + j * 8; }
__device__ __forceinline__ unsigned int* cnt_o(int m) { return g_cnt + (8 + m) * 8; }
__device__ __forceinline__ unsigned int* cnt_y(int m, int c) { return g_cnt + (24 + m * 9 + c) * 8; }

__device__ __forceinline__ void mbar_init(uint32_t b, uint32_t cnt) { asm volatile("mbarrier.init.shared::cta.b64 [%0], %1;" :: "r"(b), "r"(cnt)); }
__device__ __forceinline__ void mbar_expect_tx(uint32_t b, uint32_t bytes) { asm volatile("mbarrier.arrive.expect_tx.shared::cta.b64 _, [%0], %1;" :: "r"(b), "r"(bytes) : "memory"); }
__device__ __forceinline__ void mbar_arrive(uint32_t b) { asm volatile("mbarrier.arrive.shared::cta.b64 _, [%0];" :: "r"(b) : "memory"); }
__device__ __forceinline__ void mbar_wait(uint32_t b, uint32_t parity) {
    asm volatile("{\n.reg .pred p;\n.reg .u32 c;\nmov.u32 c, 0;\n"
                 "WAIT_LOOP:\nmbarrier.try_wait.parity.shared::cta.b64 p, [%0], %1;\n@p bra WAIT_DONE;\n"
                 "add.u32 c, c, 1;\nsetp.lt.u32 p, c, 4000000;\n@p bra WAIT_LOOP;\ntrap;\nWAIT_DONE:\n}"
                 :: "r"(b), "r"(parity) : "memory");
}
__device__ __forceinline__ void tma_2d(uint32_t dst, const CUtensorMap* tm, uint32_t b, int c0, int c1) {
    asm volatile("cp.async.bulk.tensor.2d.shared::cluster.global.mbarrier::complete_tx::bytes [%0], [%1, {%3, %4}], [%2];"
                 :: "r"(dst), "l"(tm), "r"(b), "r"(c0), "r"(c1) : "memory");
}
__device__ __forceinline__ void fence_async_smem() { asm volatile("fence.proxy.async.shared::cta;" ::: "memory"); }
__device__ __forceinline__ void fence_async_all() { asm volatile("fence.proxy.async;" ::: "memory"); }
__device__ __forceinline__ void named_bar(int id, int n) { asm volatile("bar.sync %0, %1;" :: "r"(id), "r"(n) : "memory"); }
__device__ __forceinline__ void wg_fence() { asm volatile("wgmma.fence.sync.aligned;" ::: "memory"); }
__device__ __forceinline__ void wg_commit() { asm volatile("wgmma.commit_group.sync.aligned;" ::: "memory"); }
template<int N> __device__ __forceinline__ void wg_wait() { asm volatile("wgmma.wait_group.sync.aligned %0;" :: "n"(N) : "memory"); }
template<int N> __device__ __forceinline__ void reg_fence(float* d) {
    #pragma unroll
    for (int i = 0; i < N; i++) asm volatile("" : "+f"(d[i]) :: "memory");
}
__device__ __forceinline__ uint32_t pack_bf16(float lo, float hi) { uint32_t r; asm("cvt.rn.bf16x2.f32 %0, %1, %2;" : "=r"(r) : "f"(hi), "f"(lo)); return r; }
__device__ __forceinline__ float bf_lo(uint32_t v) { return __uint_as_float(v << 16); }
__device__ __forceinline__ float bf_hi(uint32_t v) { return __uint_as_float(v & 0xffff0000u); }
__device__ __forceinline__ uint32_t sub_bf16x2(uint32_t a, uint32_t b) { uint32_t r; asm("sub.rn.bf16x2 %0, %1, %2;" : "=r"(r) : "r"(a), "r"(b)); return r; }
__device__ __forceinline__ float ex2(float x) { float r; asm("ex2.approx.ftz.f32 %0, %1;" : "=f"(r) : "f"(x)); return r; }
__device__ __forceinline__ float rcp(float x) { float r; asm("rcp.approx.ftz.f32 %0, %1;" : "=f"(r) : "f"(x)); return r; }
__device__ __forceinline__ float tanh_ap(float x) { float r; asm("tanh.approx.f32 %0, %1;" : "=f"(r) : "f"(x)); return r; }
__device__ __forceinline__ void sts32(uint32_t a, uint32_t v) { asm volatile("st.shared.b32 [%0], %1;" :: "r"(a), "r"(v) : "memory"); }
__device__ __forceinline__ void sts128(uint32_t a, uint32_t x, uint32_t y, uint32_t z, uint32_t w) { asm volatile("st.shared.v4.b32 [%0], {%1,%2,%3,%4};" :: "r"(a), "r"(x), "r"(y), "r"(z), "r"(w) : "memory"); }
__device__ __forceinline__ void lds128(uint32_t a, uint32_t* v) { asm volatile("ld.shared.v4.b32 {%0,%1,%2,%3}, [%4];" : "=r"(v[0]), "=r"(v[1]), "=r"(v[2]), "=r"(v[3]) : "r"(a) : "memory"); }
__device__ __forceinline__ float2 lds64f(uint32_t a) { float2 v; asm volatile("ld.shared.v2.f32 {%0,%1}, [%2];" : "=f"(v.x), "=f"(v.y) : "r"(a) : "memory"); return v; }
__device__ __forceinline__ void ldsm4(uint32_t a, uint32_t* v) {
    asm volatile("ldmatrix.sync.aligned.m8n8.x4.shared.b16 {%0,%1,%2,%3}, [%4];" : "=r"(v[0]), "=r"(v[1]), "=r"(v[2]), "=r"(v[3]) : "r"(a) : "memory");
}
__device__ __forceinline__ void mma_ones(float* c, const uint32_t* a) {
    const uint32_t one2 = 0x3F803F80u;
    asm volatile("mma.sync.aligned.m16n8k16.row.col.f32.bf16.bf16.f32 {%0,%1,%2,%3}, {%4,%5,%6,%7}, {%8,%8}, {%0,%1,%2,%3};"
                 : "+f"(c[0]), "+f"(c[1]), "+f"(c[2]), "+f"(c[3]) : "r"(a[0]), "r"(a[1]), "r"(a[2]), "r"(a[3]), "r"(one2));
}
__device__ __forceinline__ unsigned int ld_acquire(const unsigned int* p) { unsigned int v; asm volatile("ld.acquire.gpu.global.u32 %0, [%1];" : "=r"(v) : "l"(p) : "memory"); return v; }
__device__ __forceinline__ void wait_cnt(const unsigned int* p, unsigned int target) {
    for (int i = 0; i < WAIT_ITERS; i++) {
        if ((int)(ld_acquire(p) - target) >= 0) return;
        __nanosleep(40);
    }
    __trap();
}
__device__ __forceinline__ uint32_t v_tid() { uint32_t r; asm volatile("mov.u32 %0, %%tid.x;" : "=r"(r)); return r; }
__device__ __forceinline__ uint32_t v_bid() { uint32_t r; asm volatile("mov.u32 %0, %%ctaid.x;" : "=r"(r)); return r; }
__device__ __forceinline__ uint32_t v_epoch() { uint32_t r; asm volatile("ld.shared.u32 %0, [%1];" : "=r"(r) : "r"(EPO)); return r; }
__device__ __forceinline__ void prefetch_l2(const void* p) { asm volatile("prefetch.global.L2 [%0];" :: "l"(p)); }

__host__ __device__ constexpr uint64_t mkdesc(uint32_t addr, uint32_t lbo, uint32_t sbo, uint32_t swz) {
    return (uint64_t)((addr & 0x3FFFF) >> 4) | ((uint64_t)((lbo >> 4) & 0x3FFF) << 16) | ((uint64_t)((sbo >> 4) & 0x3FFF) << 32) | ((uint64_t)swz << 62);
}

template<int SD> __device__ __forceinline__ void wg_rs64(float* d, const uint32_t* a, uint64_t bd) {
    asm volatile("{\n.reg .pred p;\nsetp.ne.b32 p, %37, 0;\n"
    "wgmma.mma_async.sync.aligned.m64n64k16.f32.bf16.bf16 {%0,%1,%2,%3,%4,%5,%6,%7,%8,%9,%10,%11,%12,%13,%14,%15,%16,%17,%18,%19,%20,%21,%22,%23,%24,%25,%26,%27,%28,%29,%30,%31}, {%32,%33,%34,%35}, %36, p, 1, 1, 1;\n}"
    : "+f"(d[0]),"+f"(d[1]),"+f"(d[2]),"+f"(d[3]),"+f"(d[4]),"+f"(d[5]),"+f"(d[6]),"+f"(d[7]),"+f"(d[8]),"+f"(d[9]),"+f"(d[10]),"+f"(d[11]),"+f"(d[12]),"+f"(d[13]),"+f"(d[14]),"+f"(d[15]),"+f"(d[16]),"+f"(d[17]),"+f"(d[18]),"+f"(d[19]),"+f"(d[20]),"+f"(d[21]),"+f"(d[22]),"+f"(d[23]),"+f"(d[24]),"+f"(d[25]),"+f"(d[26]),"+f"(d[27]),"+f"(d[28]),"+f"(d[29]),"+f"(d[30]),"+f"(d[31])
    : "r"(a[0]),"r"(a[1]),"r"(a[2]),"r"(a[3]), "l"(bd), "n"(SD));
}
template<int SD> __device__ __forceinline__ void wg_ss64(float* d, uint64_t ad, uint64_t bd) {
    asm volatile("{\n.reg .pred p;\nsetp.ne.b32 p, %34, 0;\n"
    "wgmma.mma_async.sync.aligned.m64n64k16.f32.bf16.bf16 {%0,%1,%2,%3,%4,%5,%6,%7,%8,%9,%10,%11,%12,%13,%14,%15,%16,%17,%18,%19,%20,%21,%22,%23,%24,%25,%26,%27,%28,%29,%30,%31}, %32, %33, p, 1, 1, 0, 1;\n}"
    : "+f"(d[0]),"+f"(d[1]),"+f"(d[2]),"+f"(d[3]),"+f"(d[4]),"+f"(d[5]),"+f"(d[6]),"+f"(d[7]),"+f"(d[8]),"+f"(d[9]),"+f"(d[10]),"+f"(d[11]),"+f"(d[12]),"+f"(d[13]),"+f"(d[14]),"+f"(d[15]),"+f"(d[16]),"+f"(d[17]),"+f"(d[18]),"+f"(d[19]),"+f"(d[20]),"+f"(d[21]),"+f"(d[22]),"+f"(d[23]),"+f"(d[24]),"+f"(d[25]),"+f"(d[26]),"+f"(d[27]),"+f"(d[28]),"+f"(d[29]),"+f"(d[30]),"+f"(d[31])
    : "l"(ad), "l"(bd), "n"(SD));
}
template<int SD> __device__ __forceinline__ void wg_rs72(float* d, const uint32_t* a, uint64_t bd) {
    asm volatile("{\n.reg .pred p;\nsetp.ne.b32 p, %41, 0;\n"
    "wgmma.mma_async.sync.aligned.m64n72k16.f32.bf16.bf16 {%0,%1,%2,%3,%4,%5,%6,%7,%8,%9,%10,%11,%12,%13,%14,%15,%16,%17,%18,%19,%20,%21,%22,%23,%24,%25,%26,%27,%28,%29,%30,%31,%32,%33,%34,%35}, {%36,%37,%38,%39}, %40, p, 1, 1, 1;\n}"
    : "+f"(d[0]),"+f"(d[1]),"+f"(d[2]),"+f"(d[3]),"+f"(d[4]),"+f"(d[5]),"+f"(d[6]),"+f"(d[7]),"+f"(d[8]),"+f"(d[9]),"+f"(d[10]),"+f"(d[11]),"+f"(d[12]),"+f"(d[13]),"+f"(d[14]),"+f"(d[15]),"+f"(d[16]),"+f"(d[17]),"+f"(d[18]),"+f"(d[19]),"+f"(d[20]),"+f"(d[21]),"+f"(d[22]),"+f"(d[23]),"+f"(d[24]),"+f"(d[25]),"+f"(d[26]),"+f"(d[27]),"+f"(d[28]),"+f"(d[29]),"+f"(d[30]),"+f"(d[31]),"+f"(d[32]),"+f"(d[33]),"+f"(d[34]),"+f"(d[35])
    : "r"(a[0]),"r"(a[1]),"r"(a[2]),"r"(a[3]), "l"(bd), "n"(SD));
}
template<int SD> __device__ __forceinline__ void wg_ss72(float* d, uint64_t ad, uint64_t bd) {
    asm volatile("{\n.reg .pred p;\nsetp.ne.b32 p, %38, 0;\n"
    "wgmma.mma_async.sync.aligned.m64n72k16.f32.bf16.bf16 {%0,%1,%2,%3,%4,%5,%6,%7,%8,%9,%10,%11,%12,%13,%14,%15,%16,%17,%18,%19,%20,%21,%22,%23,%24,%25,%26,%27,%28,%29,%30,%31,%32,%33,%34,%35}, %36, %37, p, 1, 1, 0, 1;\n}"
    : "+f"(d[0]),"+f"(d[1]),"+f"(d[2]),"+f"(d[3]),"+f"(d[4]),"+f"(d[5]),"+f"(d[6]),"+f"(d[7]),"+f"(d[8]),"+f"(d[9]),"+f"(d[10]),"+f"(d[11]),"+f"(d[12]),"+f"(d[13]),"+f"(d[14]),"+f"(d[15]),"+f"(d[16]),"+f"(d[17]),"+f"(d[18]),"+f"(d[19]),"+f"(d[20]),"+f"(d[21]),"+f"(d[22]),"+f"(d[23]),"+f"(d[24]),"+f"(d[25]),"+f"(d[26]),"+f"(d[27]),"+f"(d[28]),"+f"(d[29]),"+f"(d[30]),"+f"(d[31]),"+f"(d[32]),"+f"(d[33]),"+f"(d[34]),"+f"(d[35])
    : "l"(ad), "l"(bd), "n"(SD));
}
template<int SD> __device__ __forceinline__ void wg_ss80(float* d, uint64_t ad, uint64_t bd) {
    asm volatile("{\n.reg .pred p;\nsetp.ne.b32 p, %42, 0;\n"
    "wgmma.mma_async.sync.aligned.m64n80k16.f32.bf16.bf16 {%0,%1,%2,%3,%4,%5,%6,%7,%8,%9,%10,%11,%12,%13,%14,%15,%16,%17,%18,%19,%20,%21,%22,%23,%24,%25,%26,%27,%28,%29,%30,%31,%32,%33,%34,%35,%36,%37,%38,%39}, %40, %41, p, 1, 1, 0, 1;\n}"
    : "+f"(d[0]),"+f"(d[1]),"+f"(d[2]),"+f"(d[3]),"+f"(d[4]),"+f"(d[5]),"+f"(d[6]),"+f"(d[7]),"+f"(d[8]),"+f"(d[9]),"+f"(d[10]),"+f"(d[11]),"+f"(d[12]),"+f"(d[13]),"+f"(d[14]),"+f"(d[15]),"+f"(d[16]),"+f"(d[17]),"+f"(d[18]),"+f"(d[19]),"+f"(d[20]),"+f"(d[21]),"+f"(d[22]),"+f"(d[23]),"+f"(d[24]),"+f"(d[25]),"+f"(d[26]),"+f"(d[27]),"+f"(d[28]),"+f"(d[29]),"+f"(d[30]),"+f"(d[31]),"+f"(d[32]),"+f"(d[33]),"+f"(d[34]),"+f"(d[35]),"+f"(d[36]),"+f"(d[37]),"+f"(d[38]),"+f"(d[39])
    : "l"(ad), "l"(bd), "n"(SD));
}
template<int SD> __device__ __forceinline__ void wg_tt40(float* d, uint64_t ad, uint64_t bd) {
    asm volatile("{\n.reg .pred p;\nsetp.ne.b32 p, %22, 0;\n"
    "wgmma.mma_async.sync.aligned.m64n40k16.f32.bf16.bf16 {%0,%1,%2,%3,%4,%5,%6,%7,%8,%9,%10,%11,%12,%13,%14,%15,%16,%17,%18,%19}, %20, %21, p, 1, 1, 1, 1;\n}"
    : "+f"(d[0]),"+f"(d[1]),"+f"(d[2]),"+f"(d[3]),"+f"(d[4]),"+f"(d[5]),"+f"(d[6]),"+f"(d[7]),"+f"(d[8]),"+f"(d[9]),"+f"(d[10]),"+f"(d[11]),"+f"(d[12]),"+f"(d[13]),"+f"(d[14]),"+f"(d[15]),"+f"(d[16]),"+f"(d[17]),"+f"(d[18]),"+f"(d[19])
    : "l"(ad), "l"(bd), "n"(SD));
}
template<int SD> __device__ __forceinline__ void wg_tt8(float* d, uint64_t ad, uint64_t bd) {
    asm volatile("{\n.reg .pred p;\nsetp.ne.b32 p, %6, 0;\n"
    "wgmma.mma_async.sync.aligned.m64n8k16.f32.bf16.bf16 {%0,%1,%2,%3}, %4, %5, p, 1, 1, 1, 1;\n}"
    : "+f"(d[0]),"+f"(d[1]),"+f"(d[2]),"+f"(d[3])
    : "l"(ad), "l"(bd), "n"(SD));
}

template<int V> struct IC { static constexpr int v = V; };
template<int I, int N, class F> __device__ __forceinline__ void sfor(F&& f) {
    if constexpr (I < N) { f(IC<I>{}); sfor<I + 1, N>(f); }
}

enum { K_QKV = 0, K_H = 1, K_Y = 2 };

struct Ctx {
    uint32_t wgoff;
    uint32_t tph;
    bool lane0;
};

__device__ __forceinline__ void release_slot(const Ctx& c, int slot) { if (c.lane0) mbar_arrive(bar(B_EMPTY + slot)); }

template<int KIND, int QSTEP, bool REL0, class PART>
__device__ __forceinline__ void run_step(Ctx& c, float* acc, const uint32_t* a, PART&& part) {
    constexpr int NST = (KIND == K_QKV) ? 4 : 3;
    constexpr int KPS = 36 / NST;
    sfor<0, NST>([&](auto ST) {
        constexpr int st = decltype(ST)::v;
        constexpr int u = QSTEP * 4 + st;
        constexpr int slot = (KIND == K_QKV) ? (u % 3) : st;
        if constexpr (KIND == K_QKV) mbar_wait(bar(B_FULLQ + slot), (u / 3) & 1);
        else mbar_wait(bar(B_FULL + slot), c.tph);
        wg_fence();
        sfor<0, KPS>([&](auto KK) {
            constexpr int kk = decltype(KK)::v;
            constexpr int ks = st * KPS + kk;
            constexpr int SD = ks ? 1 : 0;
            if constexpr (KIND == K_QKV) {
                constexpr uint64_t bd = mkdesc(RING + slot * SLOT + kk * 256, 128, QNG, 0);
                if constexpr (ks < 32) wg_rs72<SD>(acc, a + ks * 4, bd);
                else wg_ss72<SD>(acc, mkdesc(XB + (ks - 32) * 32, 16, 1024, 1) + c.wgoff, bd);
            } else {
                constexpr uint64_t bd = mkdesc(RING + slot * SLOT + kk * 2048, 16, 1024, 1);
                if constexpr (KIND == K_Y || (KIND == K_H && ks < 32)) wg_rs64<SD>(acc, a + ks * 4, bd);
                else wg_ss64<SD>(acc, mkdesc(XB + (ks - 32) * 32, 16, 1024, 1) + c.wgoff, bd);
            }
        });
        wg_commit();
        wg_wait<1>();
        if constexpr (st > 0) release_slot(c, (slot + 2) % 3);
        else if constexpr (REL0) release_slot(c, (slot + 2) % 3);
        part(ST);
    });
    if constexpr (KIND != K_QKV) c.tph ^= 1;
}
__device__ __forceinline__ void drain(Ctx& c) { wg_wait<0>(); release_slot(c, 2); }

__device__ __forceinline__ float phi(float t) {
    float e = ex2(t * 1.4426950408889634f);
    return (t > 0.f ? t + 1.0f : e) + 1e-6f;
}
__device__ __forceinline__ float gelu(float x) {
    float u = x * fmaf(x * x, 0.0356774081f, 0.7978845608f);
    float hx = 0.5f * x;
    return fmaf(hx, tanh_ap(u), hx);
}

struct Params {
    const __nv_bfloat16* x;
    const __nv_bfloat16* wqkv;
    const __nv_bfloat16* wo;
    const __nv_bfloat16* w1;
    const __nv_bfloat16* b1;
    const __nv_bfloat16* w2;
    const __nv_bfloat16* b2;
    __nv_bfloat16* out;
};

__global__ void __launch_bounds__(384, 1)
fused_kernel(const __grid_constant__ CUtensorMap tm_x, const __grid_constant__ CUtensorMap tm_w1,
             const __grid_constant__ CUtensorMap tm_w2, const __grid_constant__ CUtensorMap tm_wo,
             const __grid_constant__ CUtensorMap tm_o, const Params p) {
    extern __shared__ __align__(1024) unsigned char smem_raw[];
    const int tid = threadIdx.x;
    const int bid = blockIdx.x;
    const bool is_main = bid < NMAIN;
    const int j = bid & 7;
    const int m = bid >> 3;

    if (tid == 0) {
        if ((uint32_t)__cvta_generic_to_shared(smem_raw) != SB) __trap();
        for (int i = 0; i < 3; i++) {
            mbar_init(bar(B_FULL + i), 1); mbar_init(bar(B_FULLQ + i), 3); mbar_init(bar(B_EMPTY + i), 8);
            mbar_init(bar(B_XFULL + i), 1); mbar_init(bar(B_OFULL + i), 1);
        }
        mbar_init(bar(B_HFREE), 8); mbar_init(bar(B_KVB), 1); mbar_init(bar(B_YRDY), 1);
        for (int i = 0; i < 4; i++) mbar_init(bar(B_EV + i), 4);
        asm volatile("fence.mbarrier_init.release.cluster;" ::: "memory");
        if (is_main) {
            for (int g = 0; g < 3; g++) {
                mbar_expect_tx(bar(B_XFULL + g), 49152);
                for (int kb = 3 * g; kb < 3 * g + 3; kb++) tma_2d(HA + kb * 16384, &tm_x, bar(B_XFULL + g), kb * 64, m * 128);
            }
        }
    }
    if (tid == 32) sts32(EPO, g_epoch[bid]);
    if (tid >= 64 && tid < 64 + 288 && is_main) {
        int i = tid - 64;
        uint32_t v = *reinterpret_cast<const uint32_t*>(p.b1 + j * 576 + 2 * i);
        sts32(B1S + 8 * i, v << 16); sts32(B1S + 8 * i + 4, v & 0xffff0000u);
    }
    if (tid >= 352) {
        int i = tid - 352;
        uint32_t v = *reinterpret_cast<const uint32_t*>(p.b2 + (is_main ? j : 8) * 64 + 2 * i);
        sts32(B2S + 8 * i, v << 16); sts32(B2S + 8 * i + 4, v & 0xffff0000u);
    }
    if (tid < 64) sts32(ONES + tid * 4, (tid & 3) == 0 ? 0x00003F80u : 0u);
    fence_async_smem();
    __syncthreads();
    uint32_t epoch;
    asm volatile("ld.shared.u32 %0, [%1];" : "=r"(epoch) : "r"(EPO));
    const uint32_t par = epoch & 1;

    if (tid >= 256) {
        asm volatile("setmaxnreg.dec.sync.aligned.u32 24;");
        const int hw = (tid >> 5) - 8, lane = tid & 31;
        if (hw == 0) {
            if (lane == 0) {
                uint32_t n = is_main ? 4 : 0;
                if (is_main) {
                    for (int u = 3; u < 12; u++) mbar_wait(bar(B_EMPTY + u % 3), ((u / 3) & 1) ^ 1);
                }
                const int nsteps = is_main ? 19 : 4;
                for (int s = 0; s < nsteps; s++, n++) {
                    const CUtensorMap* tm; int col, row;
                    if (!is_main) { tm = &tm_wo; col = 512; row = 0; }
                    else if (s < 9) { tm = &tm_w1; col = j * 576 + s * 64; row = 0; }
                    else if (s < 18) { tm = &tm_w2; col = (s == 9) ? 512 : (((j + s - 9) & 7) * 64); row = j * 576; }
                    else { tm = &tm_wo; col = j * 64; row = 0; }
                    for (int st = 0; st < 3; st++) {
                        mbar_wait(bar(B_EMPTY + st), (n & 1) ^ 1);
                        mbar_expect_tx(bar(B_FULL + st), SLOT);
                        tma_2d(RING + st * SLOT, tm, bar(B_FULL + st), col, row + st * 192);
                    }
                }
            }
        } else {
            if (is_main) {
                const char* wsrc = reinterpret_cast<const char*>(p.wqkv) + j * 144 + (size_t)((hw - 1) * 48) * 3456;
                for (int u = 0; u < 12; u++) {
                    const int slot = u % 3, step = u >> 2;
                    const int type = (step == 2) ? 0 : step + 1;
                    mbar_wait(bar(B_EMPTY + slot), ((u / 3) & 1) ^ 1);
                    const char* src = wsrc + type * 1152 + (size_t)((u & 3) * 144) * 3456;
                    const uint32_t dst = RING + slot * SLOT + (hw - 1) * 48 * 16;
                    #pragma unroll 2
                    for (int idx = lane; idx < 432; idx += 32) {
                        int r = idx / 9, ch = idx - r * 9;
                        asm volatile("cp.async.cg.shared.global [%0], [%1], 16;" :: "r"(dst + ch * QNG + r * 16), "l"(src + r * 3456 + ch * 16) : "memory");
                    }
                    asm volatile("cp.async.commit_group;" ::: "memory");
                    if (u == 2) {
                        const int t = tid - 288;
                        for (int i = t; i < 36 * 4; i += 96) {
                            int r = i >> 2, q = i & 3;
                            prefetch_l2(reinterpret_cast<const char*>(p.wqkv) + (size_t)(36 * m + r) * 3456 + ((q & 2) ? 0 : 2304) + j * 144 + (q & 1) * 128);
                        }
                        for (int i = t; i < 36 * 9; i += 96) {
                            int r = i / 9, q = i - r * 9;
                            prefetch_l2(reinterpret_cast<const char*>(p.w1) + (size_t)(36 * m + r) * 9216 + j * 1152 + q * 128);
                        }
                    }
                    if (u > 0) {
                        asm volatile("cp.async.wait_group 1;" ::: "memory");
                        fence_async_smem();
                        __syncwarp();
                        if (lane == 0) mbar_arrive(bar(B_FULLQ + (u + 2) % 3));
                    }
                }
                asm volatile("cp.async.wait_group 0;" ::: "memory");
                fence_async_smem();
                __syncwarp();
                if (lane == 0) mbar_arrive(bar(B_FULLQ + 2));
                {
                    const int t = tid - 288;
                    for (int i = t; i < 36 * 9; i += 96)
                        prefetch_l2(reinterpret_cast<const char*>(p.w2) + (size_t)(576 * j + 36 * m) * 1152 + i * 128);
                    for (int i = t; i < 41; i += 96)
                        if ((bid * 41 + i) < 5184) prefetch_l2(reinterpret_cast<const char*>(p.wo) + (size_t)(bid * 41 + i) * 128);
                }
            }
            if (hw == 1) {
                if (lane == 0) {
                    const int nit = is_main ? 1 : 4;
                    for (int it = 0; it < nit; it++) {
                        const int mt = is_main ? m : ((bid - NMAIN) * 4 + it);
                        if (is_main) mbar_wait(bar(B_HFREE), 0);
                        else if (it > 0) mbar_wait(bar(B_HFREE), (it - 1) & 1);
                        wait_cnt(cnt_o(mt), (epoch + 1) * 8);
                        fence_async_all();
                        for (int g = 0; g < 3; g++) {
                            mbar_expect_tx(bar(B_OFULL + g), 49152);
                            for (int kb = 3 * g; kb < 3 * g + 3; kb++) tma_2d(HA + kb * 16384, &tm_o, bar(B_OFULL + g), kb * 64, mt * 128);
                        }
                        if (is_main) wait_cnt(cnt_y(m, j), (epoch + 1) * 7);
                        else wait_cnt(cnt_y(mt, 8), (epoch + 1) * 8);
                        mbar_arrive(bar(B_YRDY));
                    }
                }
            } else if (hw == 2) {
                if (lane == 0 && is_main) {
                    for (int e = 0; e < 10; e++) {
                        mbar_wait(bar(B_EV + (e & 1)), (e >> 1) & 1);
                        mbar_wait(bar(B_EV + 2 + (e & 1)), (e >> 1) & 1);
                        unsigned int* cp = (e == 0) ? cnt_kv(j) : (e == 1) ? cnt_o(m) : cnt_y(m, e == 2 ? 8 : ((j + e - 2) & 7));
                        fence_async_all();
                        __threadfence();
                        asm volatile("red.relaxed.gpu.global.add.u32 [%0], 1;" :: "l"(cp) : "memory");
                    }
                }
            } else {
                {
                    const int t0 = is_main ? (m * 9 + j) : ((bid - NMAIN) * 4 * 9 + 8);
                    const int nt = is_main ? 1 : 4;
                    for (int t = 0; t < nt; t++) {
                        uint4* z = reinterpret_cast<uint4*>(g_yacc + (size_t)((par ^ 1) * 144 + t0 + t * 9) * YT_BYTES);
                        for (int i = lane; i < YT_BYTES / 16; i += 32) z[i] = make_uint4(0, 0, 0, 0);
                    }
                    if (is_main && m == 0) {
                        float* z = g_kv + ((par ^ 1) * 8 + j) * 1440;
                        for (int i = lane; i < 1440; i += 32) z[i] = 0.f;
                    }
                }
                if (is_main) {
                    if (lane == 0) wait_cnt(cnt_kv(j), (epoch + 1) * 16);
                    __syncwarp();
                    for (int i = lane; i < 800; i += 32) sts128(KVB + i * 16, 0, 0, 0, 0);
                    __syncwarp();
                    const float* kv = g_kv + (par * 8 + j) * 1440;
                    #pragma unroll 4
                    for (int i = lane; i < 1440; i += 32) {
                        int d = i / 20, e = i - d * 20;
                        float v = __ldcg(kv + i);
                        int h = d / 18;
                        int n = (e < 18) ? (h * 18 + e) : (72 + h);
                        if (e < 19) {
                            uint32_t pk = pack_bf16(v, 0.f);
                            asm volatile("st.shared.u16 [%0], %1;" :: "r"(KVB + (n >> 3) * 1280 + (d >> 3) * 128 + (d & 7) * 16 + (n & 7) * 2), "h"((unsigned short)pk) : "memory");
                        }
                    }
                    fence_async_smem();
                    __syncwarp();
                    if (lane == 0) mbar_arrive(bar(B_KVB));
                }
            }
        }
    } else {
        asm volatile("setmaxnreg.inc.sync.aligned.u32 240;");
        Ctx c; c.wgoff = (tid >> 7) * 512; c.tph = 0; c.lane0 = ((tid & 31) == 0);
        float accx[40], accy[36];
        float* const ha = accy; float* const hb = accx;
        uint32_t ev = 0;
        auto event = [&]() { __syncwarp(); if (c.lane0) mbar_arrive(bar(B_EV) + (c.wgoff >> 5) + (ev & 1) * 8); ev++; };

        if (is_main) {
            uint32_t a[144];
            float rs0, rs1;
            uint32_t m00, m11; float d0, d1, q0 = 0.f, q1 = 0.f;
            const uint32_t lrow = HA + (tid >> 7) * 8192 + (((tid >> 5) & 3) * 16 + (tid & 15)) * 128 + ((((tid >> 4) & 1) ^ (tid & 7)) << 4);
            {
                float cs[2][4] = {{0.f, 0.f, 0.f, 0.f}, {0.f, 0.f, 0.f, 0.f}};
                sfor<0, 36>([&](auto KS) {
                    constexpr int ks = decltype(KS)::v;
                    if constexpr (ks % 12 == 0) mbar_wait(bar(B_XFULL + ks / 12), 0);
                    ldsm4((lrow ^ ((ks % 4) << 5)) + (ks / 4) * 16384, a + ks * 4);
                    mma_ones(cs[ks & 1], a + ks * 4);
                });
                float mean0 = (cs[0][0] + cs[1][0]) * (1.0f / 576.0f), mean1 = (cs[0][2] + cs[1][2]) * (1.0f / 576.0f);
                m00 = pack_bf16(mean0, mean0); m11 = pack_bf16(mean1, mean1);
                d0 = mean0 - bf_lo(m00); d1 = mean1 - bf_lo(m11);
                #pragma unroll
                for (int i = 0; i < 144; i++) a[i] = sub_bf16x2(a[i], (i & 1) ? m11 : m00);
                #pragma unroll
                for (int i = 128; i < 144; i++) {
                    float lo = bf_lo(a[i]), hi = bf_hi(a[i]);
                    if (i & 1) q1 = fmaf(lo, lo, fmaf(hi, hi, q1)); else q0 = fmaf(lo, lo, fmaf(hi, hi, q0));
                }
                const uint32_t g = (tid >> 2) & 7;
                const uint32_t tb = XB + ((tid >> 5) * 16 + g) * 128 + (g << 4) + (tid & 3) * 4;
                #pragma unroll
                for (int i = 128; i < 144; i++) {
                    const int ch = (i / 4 - 32) * 2 + ((i >> 1) & 1);
                    sts32((tb ^ (ch << 4)) + (i & 1) * 1024, a[i]);
                }
                fence_async_smem();
                named_bar(2 + (tid >> 7), 128);
            }
            float* const qa = accx; float* const qb = accy;
            auto cm_off = [&]() { uint32_t t_ = v_tid(); return (t_ >> 5) * 256 + (t_ & 31) * 4; };
            run_step<K_QKV, 0, false>(c, qa, a, [&](auto ST) {
                constexpr int st = decltype(ST)::v;
                sfor<0, 8>([&](auto I) {
                    constexpr int ks = st * 8 + decltype(I)::v;
                    uint32_t v[4];
                    ldsm4((lrow ^ ((ks % 4) << 5)) + (ks / 4) * 16384, v);
                    #pragma unroll
                    for (int r = 0; r < 4; r++) {
                        uint32_t w = sub_bf16x2(v[r], (r & 1) ? m11 : m00);
                        float lo = bf_lo(w), hi = bf_hi(w);
                        if (r & 1) q1 = fmaf(lo, lo, fmaf(hi, hi, q1)); else q0 = fmaf(lo, lo, fmaf(hi, hi, q0));
                    }
                });
                if constexpr (st == 3) {
                    q0 += __shfl_xor_sync(0xffffffffu, q0, 1); q1 += __shfl_xor_sync(0xffffffffu, q1, 1);
                    q0 += __shfl_xor_sync(0xffffffffu, q0, 2); q1 += __shfl_xor_sync(0xffffffffu, q1, 2);
                    rs0 = rsqrtf(fmaxf(fmaf(q0, 1.0f / 576.0f, -d0 * d0), 0.f) + 1e-5f);
                    rs1 = rsqrtf(fmaxf(fmaf(q1, 1.0f / 576.0f, -d1 * d1), 0.f) + 1e-5f);
                    named_bar(1, 256);
                }
            });
            run_step<K_QKV, 1, true>(c, qb, a, [&](auto ST) {
                constexpr int st = decltype(ST)::v;
                if constexpr (st == 0) reg_fence<36>(qa);
                const uint32_t cm = cm_off();
                sfor<0, 9>([&](auto B) {
                    constexpr int b = decltype(B)::v;
                    if constexpr ((b * 4) / 9 == st) {
                        sts32(PKT + b * 2048 + cm, pack_bf16(phi(qa[4 * b] * rs0), phi(qa[4 * b + 1] * rs0)));
                        sts32(PKT + b * 2048 + cm + 128, pack_bf16(phi(qa[4 * b + 2] * rs1), phi(qa[4 * b + 3] * rs1)));
                    }
                });
            });
            run_step<K_QKV, 2, true>(c, qa, a, [&](auto ST) {
                constexpr int st = decltype(ST)::v;
                if constexpr (st == 0) reg_fence<36>(qb);
                const uint32_t cm = cm_off();
                sfor<0, 9>([&](auto B) {
                    constexpr int b = decltype(B)::v;
                    if constexpr ((b * 4) / 9 == st) {
                        sts32(VT + b * 2048 + cm, pack_bf16(qb[4 * b] * rs0, qb[4 * b + 1] * rs0));
                        sts32(VT + b * 2048 + cm + 128, pack_bf16(qb[4 * b + 2] * rs1, qb[4 * b + 3] * rs1));
                    }
                });
            });
            {
                float* const kv = accx; float* const zz = accx + 20;
                run_step<K_H, 0, true>(c, ha, a, [&](auto ST) {
                    constexpr int st = decltype(ST)::v;
                    if constexpr (st == 0) {
                        reg_fence<36>(qa);
                        const uint32_t pq = PQT + cm_off() + c.wgoff * 16;
                        sfor<0, 9>([&](auto B) {
                            constexpr int b = decltype(B)::v;
                            sts32(pq + b * 1024, pack_bf16(phi(qa[4 * b] * rs0), phi(qa[4 * b + 1] * rs0)));
                            sts32(pq + b * 1024 + 128, pack_bf16(phi(qa[4 * b + 2] * rs1), phi(qa[4 * b + 3] * rs1)));
                        });
                        fence_async_smem();
                    } else if constexpr (st == 1) {
                        named_bar(1, 256);
                        wg_fence();
                        sfor<0, 8>([&](auto KS) {
                            constexpr int ks = decltype(KS)::v;
                            const uint64_t ad = mkdesc(PKT + ks * 256, 128, 2048, 0) + c.wgoff;
                            wg_tt40<(ks ? 1 : 0)>(kv, ad, mkdesc(VT + ks * 256, 128, 2048, 0) + c.wgoff);
                            wg_tt8<(ks ? 1 : 0)>(zz, ad, mkdesc(ONES, 128, 128, 0));
                        });
                        wg_commit();
                    } else {
                        reg_fence<20>(kv); reg_fence<4>(zz);
                        const int t_ = v_tid(), wg = t_ >> 7, t = t_ & 3;
                        float* dst = g_kv + ((v_epoch() & 1) * 8 + (v_bid() & 7)) * 1440;
                        #pragma unroll
                        for (int hf = 0; hf < 2; hf++) {
                            const int d = wg * 32 + ((t_ >> 5) & 3) * 16 + ((t_ >> 2) & 7) + hf * 8;
                            const bool dv = wg ? (d >= 36 && d < 72) : (d < 36);
                            const int e0 = (d / 18) * 18;
                            #pragma unroll
                            for (int i = 0; i < 5; i++) {
                                const int e = wg * 32 + i * 8 + 2 * t - e0;
                                if (dv && e >= 0 && e < 18) {
                                    atomicAdd(dst + d * 20 + e, kv[4 * i + 2 * hf]);
                                    atomicAdd(dst + d * 20 + e + 1, kv[4 * i + 2 * hf + 1]);
                                }
                            }
                            if (dv && t == 0) atomicAdd(dst + d * 20 + 18, zz[2 * hf]);
                        }
                        event();
                    }
                });
            }
            drain(c);
            auto gelu4 = [&](const float* acc, int q, uint32_t bofs, uint32_t* w) {
                #pragma unroll
                for (int bb = 0; bb < 2; bb++) {
                    const int b = 2 * q + bb;
                    float2 bv = lds64f(bofs + b * 32);
                    w[2 * bb]     = pack_bf16(gelu(fmaf(acc[4 * b], rs0, bv.x)), gelu(fmaf(acc[4 * b + 1], rs0, bv.y)));
                    w[2 * bb + 1] = pack_bf16(gelu(fmaf(acc[4 * b + 2], rs1, bv.x)), gelu(fmaf(acc[4 * b + 3], rs1, bv.y)));
                }
            };
            auto spill_off = [&]() { uint32_t t_ = v_tid(); return HA + (t_ >> 7) * 8192 + (t_ & 127) * 16; };
            auto hepi = [&](float* acc, int hidx, auto ST) {
                constexpr int st = decltype(ST)::v;
                if constexpr (st == 0) reg_fence<32>(acc);
                const uint32_t bofs = B1S + hidx * 256 + (v_tid() & 3) * 8;
                const uint32_t spill = spill_off() + hidx * 16384;
                sfor<0, 4>([&](auto Q) {
                    constexpr int q = decltype(Q)::v;
                    if constexpr ((q < 2 && st == 0) || (q == 2 && st == 1) || (q == 3 && st == 2)) {
                        uint32_t w[4];
                        gelu4(acc, q, bofs, w);
                        sts128(spill + q * 2048, w[0], w[1], w[2], w[3]);
                    }
                });
            };
            #pragma unroll 1
            for (int it = 0; it < 3; it++) {
                run_step<K_H, 0, false>(c, hb, a, [&](auto ST) { hepi(ha, 2 * it, ST); });
                run_step<K_H, 0, true>(c, ha, a, [&](auto ST) { hepi(hb, 2 * it + 1, ST); });
                drain(c);
                if (it == 1) {
                    float* const oa = accx;
                    mbar_wait(bar(B_KVB), 0);
                    wg_fence();
                    const uint32_t pqo = c.wgoff + (c.wgoff >> 3);
                    sfor<0, 5>([&](auto KS) {
                        constexpr int ks = decltype(KS)::v;
                        wg_ss80<(ks ? 1 : 0)>(oa, mkdesc(PQT + ks * 2048, ks == 4 ? 0 : 1024, 128, 0) + pqo, mkdesc(KVB + ks * 256, 128, 1280, 0));
                    });
                    wg_commit();
                    wg_wait<0>();
                    reg_fence<40>(oa);
                    const int t_ = v_tid(), b_ = v_bid(), t = t_ & 3, l4 = t_ & 28;
                    __nv_bfloat16* op = g_o + (size_t)((b_ >> 3) * 128 + (t_ >> 5) * 16 + ((t_ >> 2) & 7)) * DM + (b_ & 7) * 72 + 2 * t;
                    #pragma unroll
                    for (int hf = 0; hf < 2; hf++) {
                        float r[4];
                        r[0] = rcp(__shfl_sync(0xffffffffu, oa[36 + 2 * hf], l4) + 1e-6f);
                        r[1] = rcp(__shfl_sync(0xffffffffu, oa[37 + 2 * hf], l4) + 1e-6f);
                        r[2] = rcp(__shfl_sync(0xffffffffu, oa[36 + 2 * hf], l4 + 1) + 1e-6f);
                        r[3] = rcp(__shfl_sync(0xffffffffu, oa[37 + 2 * hf], l4 + 1) + 1e-6f);
                        #pragma unroll
                        for (int i = 0; i < 9; i++) {
                            float rr = (i < 2) ? r[0] : (i == 2) ? (t < 1 ? r[0] : r[1]) : (i == 3) ? r[1] : (i == 4) ? (t < 2 ? r[1] : r[2])
                                     : (i == 5) ? r[2] : (i == 6) ? (t < 3 ? r[2] : r[3]) : r[3];
                            *reinterpret_cast<uint32_t*>(op + hf * 8 * DM + i * 8) = pack_bf16(oa[4 * i + 2 * hf] * rr, oa[4 * i + 2 * hf + 1] * rr);
                        }
                    }
                    fence_async_all();
                    event();
                }
            }
            auto reload = [&](auto S0, auto S1) {
                const uint32_t spill = spill_off();
                sfor<decltype(S0)::v * 4, decltype(S1)::v * 4>([&](auto Q) {
                    constexpr int q = decltype(Q)::v;
                    lds128(spill + (q / 4) * 16384 + (q % 4) * 2048, a + q * 4);
                });
            };
            run_step<K_H, 0, false>(c, hb, a, [&](auto ST) { hepi(ha, 6, ST); });
            run_step<K_H, 0, true>(c, ha, a, [&](auto ST) {
                constexpr int st = decltype(ST)::v;
                if constexpr (st == 0) { hepi(hb, 7, IC<0>{}); hepi(hb, 7, IC<1>{}); hepi(hb, 7, IC<2>{}); }
                else if constexpr (st == 1) reload(IC<0>{}, IC<3>{});
                else reload(IC<3>{}, IC<6>{});
            });
            run_step<K_Y, 0, true>(c, hb, a, [&](auto ST) {
                constexpr int st = decltype(ST)::v;
                const uint32_t bofs = B1S + 8 * 256 + (v_tid() & 3) * 8;
                if constexpr (st == 0) {
                    reg_fence<32>(ha);
                    reload(IC<6>{}, IC<8>{});
                    __syncwarp();
                    if (c.lane0) mbar_arrive(bar(B_HFREE));
                    gelu4(ha, 0, bofs, a + 128);
                    gelu4(ha, 1, bofs, a + 132);
                } else if constexpr (st == 1) {
                    gelu4(ha, 2, bofs, a + 136);
                    gelu4(ha, 3, bofs, a + 140);
                }
            });
            drain(c);
            auto yepi = [&](float* acc, int rel, auto ST) {
                constexpr int st = decltype(ST)::v;
                if constexpr (st == 0) reg_fence<32>(acc);
                const uint32_t b_ = v_bid();
                const uint32_t chunk = rel ? ((b_ + rel) & 7) : 8;
                unsigned char* yp = g_yacc + ((v_epoch() & 1) * 144 + (b_ >> 3) * 9 + chunk) * YT_BYTES + v_tid() * 16;
                sfor<0, 4>([&](auto Q) {
                    constexpr int q = decltype(Q)::v;
                    if constexpr ((q < 2 && st == 0) || (q == 2 && st == 1) || (q == 3 && st == 2)) {
                        asm volatile("red.global.add.noftz.v4.bf16x2 [%0], {%1,%2,%3,%4};" :: "l"(yp + q * 4096),
                                     "r"(pack_bf16(acc[8 * q], acc[8 * q + 1])), "r"(pack_bf16(acc[8 * q + 2], acc[8 * q + 3])),
                                     "r"(pack_bf16(acc[8 * q + 4], acc[8 * q + 5])), "r"(pack_bf16(acc[8 * q + 6], acc[8 * q + 7])) : "memory");
                    }
                });
                if constexpr (st == 2) event();
            };
            #pragma unroll 1
            for (int it = 0; it < 3; it++) {
                run_step<K_Y, 0, false>(c, ha, a, [&](auto ST) { yepi(hb, 2 * it, ST); });
                run_step<K_Y, 0, true>(c, hb, a, [&](auto ST) { yepi(ha, 2 * it + 1, ST); });
                drain(c);
            }
            run_step<K_Y, 0, false>(c, ha, a, [&](auto ST) { yepi(hb, 6, ST); });
            run_step<K_Y, 0, true>(c, hb, a, [&](auto ST) { yepi(ha, 7, ST); });
            drain(c);
            reg_fence<32>(hb);
        }
        const int b2_ = v_bid(), t2_ = v_tid();
        const bool mainf = b2_ < NMAIN;
        const int nfin = mainf ? 1 : 4;
        const uint32_t oph0 = c.tph;
        #pragma unroll 1
        for (int it = 0; it < nfin; it++) {
            const int mt = mainf ? (b2_ >> 3) : ((b2_ - NMAIN) * 4 + it);
            const int ch = mainf ? (b2_ & 7) : 8;
            if (!mainf) {
                #pragma unroll
                for (int i = 0; i < 32; i++) hb[i] = 0.f;
            }
            const size_t eoff = (size_t)(mt * 128 + (t2_ >> 5) * 16 + ((t2_ >> 2) & 7)) * DM + ch * 64 + 2 * (t2_ & 3);
            uint32_t xr[16];
            const uint32_t opar = c.tph ^ oph0;
            sfor<0, 3>([&](auto ST) {
                constexpr int st = decltype(ST)::v;
                mbar_wait(bar(B_FULL + st), c.tph);
                mbar_wait(bar(B_OFULL + st), opar);
                wg_fence();
                sfor<0, 12>([&](auto KK) {
                    constexpr int kk = decltype(KK)::v;
                    constexpr int ks = st * 12 + kk;
                    wg_ss64<(ks ? 1 : 0)>(ha, mkdesc(HA + (ks / 4) * 16384 + (ks % 4) * 32, 16, 1024, 1) + c.wgoff,
                                          mkdesc(RING + st * SLOT + kk * 2048, 16, 1024, 1));
                });
                wg_commit();
                if constexpr (st == 0) {
                    #pragma unroll
                    for (int i = 0; i < 8; i++) {
                        xr[2 * i] = __ldg(reinterpret_cast<const uint32_t*>(p.x + eoff + i * 8));
                        xr[2 * i + 1] = __ldg(reinterpret_cast<const uint32_t*>(p.x + eoff + 8 * DM + i * 8));
                    }
                } else {
                    wg_wait<1>();
                    release_slot(c, st - 1);
                }
            });
            c.tph ^= 1;
            mbar_wait(bar(B_YRDY), opar);
            {
                const unsigned char* yp = g_yacc + ((v_epoch() & 1) * 144 + mt * 9 + ch) * YT_BYTES + t2_ * 16;
                #pragma unroll
                for (int q = 0; q < 4; q++) {
                    uint4 u = __ldcg(reinterpret_cast<const uint4*>(yp + q * 4096));
                    hb[8 * q] += bf_lo(u.x); hb[8 * q + 1] += bf_hi(u.x); hb[8 * q + 2] += bf_lo(u.y); hb[8 * q + 3] += bf_hi(u.y);
                    hb[8 * q + 4] += bf_lo(u.z); hb[8 * q + 5] += bf_hi(u.z); hb[8 * q + 6] += bf_lo(u.w); hb[8 * q + 7] += bf_hi(u.w);
                }
                #pragma unroll
                for (int b = 0; b < 8; b++) {
                    float2 bv = lds64f(B2S + b * 32 + (t2_ & 3) * 8);
                    #pragma unroll
                    for (int r = 0; r < 4; r++) {
                        float y = hb[4 * b + r] + ((r & 1) ? bv.y : bv.x);
                        hb[4 * b + r] = y * rcp(1.0f + ex2(y * -1.4426950408889634f));
                    }
                }
            }
            wg_wait<0>();
            reg_fence<32>(ha);
            release_slot(c, 2);
            if (!mainf) { __syncwarp(); if (c.lane0) mbar_arrive(bar(B_HFREE)); }
            #pragma unroll
            for (int b = 0; b < 8; b++) {
                *reinterpret_cast<uint32_t*>(p.out + eoff + b * 8) =
                    pack_bf16(fmaf(ha[4 * b], hb[4 * b], bf_lo(xr[2 * b])), fmaf(ha[4 * b + 1], hb[4 * b + 1], bf_hi(xr[2 * b])));
                *reinterpret_cast<uint32_t*>(p.out + eoff + 8 * DM + b * 8) =
                    pack_bf16(fmaf(ha[4 * b + 2], hb[4 * b + 2], bf_lo(xr[2 * b + 1])), fmaf(ha[4 * b + 3], hb[4 * b + 3], bf_hi(xr[2 * b + 1])));
            }
        }
        if (t2_ == 0) g_epoch[b2_] = v_epoch() + 1;
    }
}

typedef CUresult (*EncodeFn)(CUtensorMap*, CUtensorMapDataType, cuuint32_t, void*, const cuuint64_t*, const cuuint64_t*,
                             const cuuint32_t*, const cuuint32_t*, CUtensorMapInterleave, CUtensorMapSwizzle,
                             CUtensorMapL2promotion, CUtensorMapFloatOOBfill);

void make_map(EncodeFn enc, CUtensorMap* tm, const void* base, int rows, int cols, int box_rows) {
    cuuint64_t gdim[2] = {(cuuint64_t)cols, (cuuint64_t)rows};
    cuuint64_t gstr[1] = {(cuuint64_t)cols * 2};
    cuuint32_t box[2] = {64, (cuuint32_t)box_rows};
    cuuint32_t estr[2] = {1, 1};
    enc(tm, CU_TENSOR_MAP_DATA_TYPE_BFLOAT16, 2, const_cast<void*>(base), gdim, gstr, box, estr, CU_TENSOR_MAP_INTERLEAVE_NONE,
        CU_TENSOR_MAP_SWIZZLE_128B, CU_TENSOR_MAP_L2_PROMOTION_L2_128B, CU_TENSOR_MAP_FLOAT_OOB_FILL_NONE);
}

}

extern "C" void kernel_launch(void* const* d_in, const int* in_sizes, int n_in, void* d_out, int out_size) {
    static EncodeFn enc = nullptr;
    static void* o_ptr = nullptr;
    if (!enc) {
        void* fn = nullptr;
        cudaDriverEntryPointQueryResult qr;
        cudaGetDriverEntryPoint("cuTensorMapEncodeTiled", &fn, cudaEnableDefault, &qr);
        enc = (EncodeFn)fn;
        cudaGetSymbolAddress(&o_ptr, g_o);
        cudaFuncSetAttribute(fused_kernel, cudaFuncAttributeMaxDynamicSharedMemorySize, SMEM_BYTES);
    }
    Params p;
    p.x = (const __nv_bfloat16*)d_in[0];
    p.wqkv = (const __nv_bfloat16*)d_in[1];
    p.wo = (const __nv_bfloat16*)d_in[2];
    p.w1 = (const __nv_bfloat16*)d_in[4];
    p.b1 = (const __nv_bfloat16*)d_in[5];
    p.w2 = (const __nv_bfloat16*)d_in[6];
    p.b2 = (const __nv_bfloat16*)d_in[7];
    p.out = (__nv_bfloat16*)d_out;
    CUtensorMap tm_x, tm_w1, tm_w2, tm_wo, tm_o;
    make_map(enc, &tm_x, p.x, SEQ, DM, 128);
    make_map(enc, &tm_w1, p.w1, DM, FF, 192);
    make_map(enc, &tm_w2, p.w2, FF, DM, 192);
    make_map(enc, &tm_wo, p.wo, DM, DM, 192);
    make_map(enc, &tm_o, o_ptr, SEQ, DM, 128);
    fused_kernel<<<NMAIN + NAUX, 384, SMEM_BYTES>>>(tm_x, tm_w1, tm_w2, tm_wo, tm_o, p);
}
```

```cpp
#include <cuda_runtime.h>
#include <cuda.h>
#include <cuda_bf16.h>
#include <stdint.h>

#define OSTEP_AT 4
#define KNOB_A 1
#define KNOB_B 0
#define PF1_NS 2000
#define PF2_NS 3000
#define PFIDX 3
#define YF32 0

namespace {
constexpr int WAIT_ITERS = 3000000;

constexpr int SEQ = 2048, DM = 576, FF = 4608;
constexpr int NMAIN = 128, NAUX = 4;

constexpr uint32_t SB    = 0x400;
constexpr uint32_t HA    = SB;
constexpr uint32_t XB    = SB + 131072;
constexpr uint32_t RING  = SB + 147456;
constexpr uint32_t SLOT  = 24576;
constexpr uint32_t MISC  = SB + 221184;
constexpr uint32_t BARS  = MISC;
constexpr uint32_t B1S   = MISC + 512;
constexpr uint32_t B2S   = MISC + 2816;
constexpr uint32_t EPO   = MISC + 3072;
constexpr uint32_t EVC   = MISC + 3104;
constexpr uint32_t SMEM_BYTES = 221184 + 3200 + 512;
constexpr uint32_t PKT   = HA + 32768;
constexpr uint32_t VT    = HA + 51200;
constexpr uint32_t PQT   = HA + 98304;
constexpr uint32_t KVB   = HA + 116736;

enum { B_FULL = 0, B_EMPTY = 3, B_XFULL = 6, B_OFULL = 9, B_OFREE = 12  , B_KVB = 16, B_YRDY = 17, B_COUNT = 18 };
__device__ __forceinline__ constexpr uint32_t bar(int i) { return BARS + 8u * i; }

constexpr int YT_BYTES = YF32 ? 32768 : 16384;
__device__ __align__(1024) __nv_bfloat16 g_o[SEQ * DM];
__device__ __align__(1024) unsigned char g_yacc[2 * 16 * 9 * YT_BYTES];
__device__ __align__(128) float g_kv[2 * 8 * 72 * 20];
__device__ __align__(128) unsigned int g_cnt[(8 + 16 + 16 * 9) * 8];
__device__ unsigned int g_epoch[NMAIN + NAUX];
__device__ __forceinline__ unsigned int* cnt_kv(int j) { return g_cnt + j * 8; }
__device__ __forceinline__ unsigned int* cnt_o(int m) { return g_cnt + (8 + m) * 8; }
__device__ __forceinline__ unsigned int* cnt_y(int m, int c) { return g_cnt + (24 + m * 9 + c) * 8; }

__device__ __forceinline__ void mbar_init(uint32_t b, uint32_t cnt) { asm volatile("mbarrier.init.shared::cta.b64 [%0], %1;" :: "r"(b), "r"(cnt)); }
__device__ __forceinline__ void mbar_expect_tx(uint32_t b, uint32_t bytes) { asm volatile("mbarrier.arrive.expect_tx.shared::cta.b64 _, [%0], %1;" :: "r"(b), "r"(bytes) : "memory"); }
__device__ __forceinline__ void mbar_arrive(uint32_t b) { asm volatile("mbarrier.arrive.shared::cta.b64 _, [%0];" :: "r"(b) : "memory"); }
__device__ __forceinline__ void prof(int) {}
__device__ __forceinline__ void mbar_wait(uint32_t b, uint32_t parity) {
    asm volatile("{\n.reg .pred p;\n.reg .u32 c;\nmov.u32 c, 0;\n"
                 "WAIT_LOOP:\nmbarrier.try_wait.parity.shared::cta.b64 p, [%0], %1;\n@p bra WAIT_DONE;\n"
                 "add.u32 c, c, 1;\nsetp.lt.u32 p, c, 4000000;\n@p bra WAIT_LOOP;\ntrap;\nWAIT_DONE:\n}"
                 :: "r"(b), "r"(parity) : "memory");
}
__device__ __forceinline__ void tma_2d(uint32_t dst, const CUtensorMap* tm, uint32_t b, int c0, int c1) {
    asm volatile("cp.async.bulk.tensor.2d.shared::cluster.global.mbarrier::complete_tx::bytes [%0], [%1, {%3, %4}], [%2];"
                 :: "r"(dst), "l"(tm), "r"(b), "r"(c0), "r"(c1) : "memory");
}
__device__ __forceinline__ void fence_async_smem() { asm volatile("fence.proxy.async.shared::cta;" ::: "memory"); }
__device__ __forceinline__ void fence_async_all() { asm volatile("fence.proxy.async;" ::: "memory"); }
__device__ __forceinline__ void named_bar(int id, int n) { asm volatile("bar.sync %0, %1;" :: "r"(id), "r"(n) : "memory"); }
__device__ __forceinline__ void wg_fence() { asm volatile("wgmma.fence.sync.aligned;" ::: "memory"); }
__device__ __forceinline__ void wg_commit() { asm volatile("wgmma.commit_group.sync.aligned;" ::: "memory"); }
template<int N> __device__ __forceinline__ void wg_wait() { asm volatile("wgmma.wait_group.sync.aligned %0;" :: "n"(N) : "memory"); }
template<int N> __device__ __forceinline__ void reg_fence(float* d) {
    #pragma unroll
    for (int i = 0; i < N; i++) asm volatile("" : "+f"(d[i]) :: "memory");
}
template<int N> __device__ __forceinline__ void reg_copy(float* d, const float* s) {
    #pragma unroll
    for (int i = 0; i < N; i++) asm volatile("mov.b32 %0, %1;" : "=f"(d[i]) : "f"(s[i]));
}
__device__ __forceinline__ uint32_t pack_bf16(float lo, float hi) { uint32_t r; asm("cvt.rn.bf16x2.f32 %0, %1, %2;" : "=r"(r) : "f"(hi), "f"(lo)); return r; }
__device__ __forceinline__ float bf_lo(uint32_t v) { return __uint_as_float(v << 16); }
__device__ __forceinline__ float bf_hi(uint32_t v) { return __uint_as_float(v & 0xffff0000u); }
__device__ __forceinline__ uint32_t sub_bf16x2(uint32_t a, uint32_t b) { uint32_t r; asm("sub.rn.bf16x2 %0, %1, %2;" : "=r"(r) : "r"(a), "r"(b)); return r; }
__device__ __forceinline__ float ex2(float x) { float r; asm("ex2.approx.ftz.f32 %0, %1;" : "=f"(r) : "f"(x)); return r; }
__device__ __forceinline__ float rcp(float x) { float r; asm("rcp.approx.ftz.f32 %0, %1;" : "=f"(r) : "f"(x)); return r; }
__device__ __forceinline__ float tanh_ap(float x) { float r; asm("tanh.approx.f32 %0, %1;" : "=f"(r) : "f"(x)); return r; }
__device__ __forceinline__ void sts32(uint32_t a, uint32_t v) { asm volatile("st.shared.b32 [%0], %1;" :: "r"(a), "r"(v)); }
__device__ __forceinline__ void sts128(uint32_t a, uint32_t x, uint32_t y, uint32_t z, uint32_t w) { asm volatile("st.shared.v4.b32 [%0], {%1,%2,%3,%4};" :: "r"(a), "r"(x), "r"(y), "r"(z), "r"(w)); }
__device__ __forceinline__ void sts64(uint32_t a, uint32_t x, uint32_t y) { asm volatile("st.shared.v2.b32 [%0], {%1,%2};" :: "r"(a), "r"(x), "r"(y)); }
__device__ __forceinline__ void lds64(uint32_t a, uint32_t* v) { asm volatile("ld.shared.v2.b32 {%0,%1}, [%2];" : "=r"(v[0]), "=r"(v[1]) : "r"(a)); }
__device__ __forceinline__ void lds128(uint32_t a, uint32_t* v) { asm volatile("ld.shared.v4.b32 {%0,%1,%2,%3}, [%4];" : "=r"(v[0]), "=r"(v[1]), "=r"(v[2]), "=r"(v[3]) : "r"(a) : "memory"); }
__device__ __forceinline__ float2 lds64f(uint32_t a) { float2 v; asm("ld.shared.v2.f32 {%0,%1}, [%2];" : "=f"(v.x), "=f"(v.y) : "r"(a)); return v; }
__device__ __forceinline__ void ldsm4(uint32_t a, uint32_t* v) {
    asm volatile("ldmatrix.sync.aligned.m8n8.x4.shared.b16 {%0,%1,%2,%3}, [%4];" : "=r"(v[0]), "=r"(v[1]), "=r"(v[2]), "=r"(v[3]) : "r"(a));
}
__device__ __forceinline__ void mma_ones(float* c, const uint32_t* a) {
    const uint32_t one2 = 0x3F803F80u;
    asm volatile("mma.sync.aligned.m16n8k16.row.col.f32.bf16.bf16.f32 {%0,%1,%2,%3}, {%4,%5,%6,%7}, {%8,%8}, {%0,%1,%2,%3};"
                 : "+f"(c[0]), "+f"(c[1]), "+f"(c[2]), "+f"(c[3]) : "r"(a[0]), "r"(a[1]), "r"(a[2]), "r"(a[3]), "r"(one2));
}
__device__ __forceinline__ unsigned int ld_acquire(const unsigned int* p) { unsigned int v; asm volatile("ld.acquire.gpu.global.u32 %0, [%1];" : "=r"(v) : "l"(p) : "memory"); return v; }
__device__ __forceinline__ void wait_cnt(const unsigned int* p, unsigned int target) {
    for (int i = 0; i < WAIT_ITERS; i++) {
        if ((int)(ld_acquire(p) - target) >= 0) return;
        __nanosleep(40);
    }
    __trap();
}
__device__ __forceinline__ uint32_t v_tid() { uint32_t r; asm volatile("mov.u32 %0, %%tid.x;" : "=r"(r)); return r; }
__device__ __forceinline__ uint32_t v_bid() { uint32_t r; asm volatile("mov.u32 %0, %%ctaid.x;" : "=r"(r)); return r; }
__device__ __forceinline__ uint32_t v_epoch() { uint32_t r; asm volatile("ld.shared.u32 %0, [%1];" : "=r"(r) : "r"(EPO)); return r; }
__device__ __forceinline__ void prefetch_l2(const void* p) { asm volatile("prefetch.global.L2 [%0];" :: "l"(p)); }

__host__ __device__ constexpr uint64_t mkdesc(uint32_t addr, uint32_t lbo, uint32_t sbo, uint32_t swz) {
    return (uint64_t)((addr & 0x3FFFF) >> 4) | ((uint64_t)((lbo >> 4) & 0x3FFF) << 16) | ((uint64_t)((sbo >> 4) & 0x3FFF) << 32) | ((uint64_t)swz << 62);
}

template<int SD> __device__ __forceinline__ void wg_rs64(float* d, const uint32_t* a, uint64_t bd) {
  if constexpr (SD) {
    asm volatile("{\n.reg .pred p;\nsetp.eq.b32 p, 0, 0;\n"
    "wgmma.mma_async.sync.aligned.m64n64k16.f32.bf16.bf16 {%0,%1,%2,%3,%4,%5,%6,%7,%8,%9,%10,%11,%12,%13,%14,%15,%16,%17,%18,%19,%20,%21,%22,%23,%24,%25,%26,%27,%28,%29,%30,%31}, {%32,%33,%34,%35}, %36, p, 1, 1, 1;\n}"
    : "+f"(d[0]),"+f"(d[1]),"+f"(d[2]),"+f"(d[3]),"+f"(d[4]),"+f"(d[5]),"+f"(d[6]),"+f"(d[7]),"+f"(d[8]),"+f"(d[9]),"+f"(d[10]),"+f"(d[11]),"+f"(d[12]),"+f"(d[13]),"+f"(d[14]),"+f"(d[15]),"+f"(d[16]),"+f"(d[17]),"+f"(d[18]),"+f"(d[19]),"+f"(d[20]),"+f"(d[21]),"+f"(d[22]),"+f"(d[23]),"+f"(d[24]),"+f"(d[25]),"+f"(d[26]),"+f"(d[27]),"+f"(d[28]),"+f"(d[29]),"+f"(d[30]),"+f"(d[31])
    : "r"(a[0]),"r"(a[1]),"r"(a[2]),"r"(a[3]), "l"(bd));
  } else {
    asm volatile("{\n.reg .pred p;\nsetp.ne.b32 p, 0, 0;\n"
    "wgmma.mma_async.sync.aligned.m64n64k16.f32.bf16.bf16 {%0,%1,%2,%3,%4,%5,%6,%7,%8,%9,%10,%11,%12,%13,%14,%15,%16,%17,%18,%19,%20,%21,%22,%23,%24,%25,%26,%27,%28,%29,%30,%31}, {%32,%33,%34,%35}, %36, p, 1, 1, 1;\n}"
    : "+f"(d[0]),"+f"(d[1]),"+f"(d[2]),"+f"(d[3]),"+f"(d[4]),"+f"(d[5]),"+f"(d[6]),"+f"(d[7]),"+f"(d[8]),"+f"(d[9]),"+f"(d[10]),"+f"(d[11]),"+f"(d[12]),"+f"(d[13]),"+f"(d[14]),"+f"(d[15]),"+f"(d[16]),"+f"(d[17]),"+f"(d[18]),"+f"(d[19]),"+f"(d[20]),"+f"(d[21]),"+f"(d[22]),"+f"(d[23]),"+f"(d[24]),"+f"(d[25]),"+f"(d[26]),"+f"(d[27]),"+f"(d[28]),"+f"(d[29]),"+f"(d[30]),"+f"(d[31])
    : "r"(a[0]),"r"(a[1]),"r"(a[2]),"r"(a[3]), "l"(bd));
  }
}
template<int SD> __device__ __forceinline__ void wg_ss64(float* d, uint64_t ad, uint64_t bd) {
  if constexpr (SD) {
    asm volatile("{\n.reg .pred p;\nsetp.eq.b32 p, 0, 0;\n"
    "wgmma.mma_async.sync.aligned.m64n64k16.f32.bf16.bf16 {%0,%1,%2,%3,%4,%5,%6,%7,%8,%9,%10,%11,%12,%13,%14,%15,%16,%17,%18,%19,%20,%21,%22,%23,%24,%25,%26,%27,%28,%29,%30,%31}, %32, %33, p, 1, 1, 0, 1;\n}"
    : "+f"(d[0]),"+f"(d[1]),"+f"(d[2]),"+f"(d[3]),"+f"(d[4]),"+f"(d[5]),"+f"(d[6]),"+f"(d[7]),"+f"(d[8]),"+f"(d[9]),"+f"(d[10]),"+f"(d[11]),"+f"(d[12]),"+f"(d[13]),"+f"(d[14]),"+f"(d[15]),"+f"(d[16]),"+f"(d[17]),"+f"(d[18]),"+f"(d[19]),"+f"(d[20]),"+f"(d[21]),"+f"(d[22]),"+f"(d[23]),"+f"(d[24]),"+f"(d[25]),"+f"(d[26]),"+f"(d[27]),"+f"(d[28]),"+f"(d[29]),"+f"(d[30]),"+f"(d[31])
    : "l"(ad), "l"(bd));
  } else {
    asm volatile("{\n.reg .pred p;\nsetp.ne.b32 p, 0, 0;\n"
    "wgmma.mma_async.sync.aligned.m64n64k16.f32.bf16.bf16 {%0,%1,%2,%3,%4,%5,%6,%7,%8,%9,%10,%11,%12,%13,%14,%15,%16,%17,%18,%19,%20,%21,%22,%23,%24,%25,%26,%27,%28,%29,%30,%31}, %32, %33, p, 1, 1, 0, 1;\n}"
    : "+f"(d[0]),"+f"(d[1]),"+f"(d[2]),"+f"(d[3]),"+f"(d[4]),"+f"(d[5]),"+f"(d[6]),"+f"(d[7]),"+f"(d[8]),"+f"(d[9]),"+f"(d[10]),"+f"(d[11]),"+f"(d[12]),"+f"(d[13]),"+f"(d[14]),"+f"(d[15]),"+f"(d[16]),"+f"(d[17]),"+f"(d[18]),"+f"(d[19]),"+f"(d[20]),"+f"(d[21]),"+f"(d[22]),"+f"(d[23]),"+f"(d[24]),"+f"(d[25]),"+f"(d[26]),"+f"(d[27]),"+f"(d[28]),"+f"(d[29]),"+f"(d[30]),"+f"(d[31])
    : "l"(ad), "l"(bd));
  }
}
template<int SD> __device__ __forceinline__ void wg_rs72(float* d, const uint32_t* a, uint64_t bd) {
  if constexpr (SD) {
    asm volatile("{\n.reg .pred p;\nsetp.eq.b32 p, 0, 0;\n"
    "wgmma.mma_async.sync.aligned.m64n72k16.f32.bf16.bf16 {%0,%1,%2,%3,%4,%5,%6,%7,%8,%9,%10,%11,%12,%13,%14,%15,%16,%17,%18,%19,%20,%21,%22,%23,%24,%25,%26,%27,%28,%29,%30,%31,%32,%33,%34,%35}, {%36,%37,%38,%39}, %40, p, 1, 1, 1;\n}"
    : "+f"(d[0]),"+f"(d[1]),"+f"(d[2]),"+f"(d[3]),"+f"(d[4]),"+f"(d[5]),"+f"(d[6]),"+f"(d[7]),"+f"(d[8]),"+f"(d[9]),"+f"(d[10]),"+f"(d[11]),"+f"(d[12]),"+f"(d[13]),"+f"(d[14]),"+f"(d[15]),"+f"(d[16]),"+f"(d[17]),"+f"(d[18]),"+f"(d[19]),"+f"(d[20]),"+f"(d[21]),"+f"(d[22]),"+f"(d[23]),"+f"(d[24]),"+f"(d[25]),"+f"(d[26]),"+f"(d[27]),"+f"(d[28]),"+f"(d[29]),"+f"(d[30]),"+f"(d[31]),"+f"(d[32]),"+f"(d[33]),"+f"(d[34]),"+f"(d[35])
    : "r"(a[0]),"r"(a[1]),"r"(a[2]),"r"(a[3]), "l"(bd));
  } else {
    asm volatile("{\n.reg .pred p;\nsetp.ne.b32 p, 0, 0;\n"
    "wgmma.mma_async.sync.aligned.m64n72k16.f32.bf16.bf16 {%0,%1,%2,%3,%4,%5,%6,%7,%8,%9,%10,%11,%12,%13,%14,%15,%16,%17,%18,%19,%20,%21,%22,%23,%24,%25,%26,%27,%28,%29,%30,%31,%32,%33,%34,%35}, {%36,%37,%38,%39}, %40, p, 1, 1, 1;\n}"
    : "+f"(d[0]),"+f"(d[1]),"+f"(d[2]),"+f"(d[3]),"+f"(d[4]),"+f"(d[5]),"+f"(d[6]),"+f"(d[7]),"+f"(d[8]),"+f"(d[9]),"+f"(d[10]),"+f"(d[11]),"+f"(d[12]),"+f"(d[13]),"+f"(d[14]),"+f"(d[15]),"+f"(d[16]),"+f"(d[17]),"+f"(d[18]),"+f"(d[19]),"+f"(d[20]),"+f"(d[21]),"+f"(d[22]),"+f"(d[23]),"+f"(d[24]),"+f"(d[25]),"+f"(d[26]),"+f"(d[27]),"+f"(d[28]),"+f"(d[29]),"+f"(d[30]),"+f"(d[31]),"+f"(d[32]),"+f"(d[33]),"+f"(d[34]),"+f"(d[35])
    : "r"(a[0]),"r"(a[1]),"r"(a[2]),"r"(a[3]), "l"(bd));
  }
}
template<int SD> __device__ __forceinline__ void wg_ss72(float* d, uint64_t ad, uint64_t bd) {
  if constexpr (SD) {
    asm volatile("{\n.reg .pred p;\nsetp.eq.b32 p, 0, 0;\n"
    "wgmma.mma_async.sync.aligned.m64n72k16.f32.bf16.bf16 {%0,%1,%2,%3,%4,%5,%6,%7,%8,%9,%10,%11,%12,%13,%14,%15,%16,%17,%18,%19,%20,%21,%22,%23,%24,%25,%26,%27,%28,%29,%30,%31,%32,%33,%34,%35}, %36, %37, p, 1, 1, 0, 1;\n}"
    : "+f"(d[0]),"+f"(d[1]),"+f"(d[2]),"+f"(d[3]),"+f"(d[4]),"+f"(d[5]),"+f"(d[6]),"+f"(d[7]),"+f"(d[8]),"+f"(d[9]),"+f"(d[10]),"+f"(d[11]),"+f"(d[12]),"+f"(d[13]),"+f"(d[14]),"+f"(d[15]),"+f"(d[16]),"+f"(d[17]),"+f"(d[18]),"+f"(d[19]),"+f"(d[20]),"+f"(d[21]),"+f"(d[22]),"+f"(d[23]),"+f"(d[24]),"+f"(d[25]),"+f"(d[26]),"+f"(d[27]),"+f"(d[28]),"+f"(d[29]),"+f"(d[30]),"+f"(d[31]),"+f"(d[32]),"+f"(d[33]),"+f"(d[34]),"+f"(d[35])
    : "l"(ad), "l"(bd));
  } else {
    asm volatile("{\n.reg .pred p;\nsetp.ne.b32 p, 0, 0;\n"
    "wgmma.mma_async.sync.aligned.m64n72k16.f32.bf16.bf16 {%0,%1,%2,%3,%4,%5,%6,%7,%8,%9,%10,%11,%12,%13,%14,%15,%16,%17,%18,%19,%20,%21,%22,%23,%24,%25,%26,%27,%28,%29,%30,%31,%32,%33,%34,%35}, %36, %37, p, 1, 1, 0, 1;\n}"
    : "+f"(d[0]),"+f"(d[1]),"+f"(d[2]),"+f"(d[3]),"+f"(d[4]),"+f"(d[5]),"+f"(d[6]),"+f"(d[7]),"+f"(d[8]),"+f"(d[9]),"+f"(d[10]),"+f"(d[11]),"+f"(d[12]),"+f"(d[13]),"+f"(d[14]),"+f"(d[15]),"+f"(d[16]),"+f"(d[17]),"+f"(d[18]),"+f"(d[19]),"+f"(d[20]),"+f"(d[21]),"+f"(d[22]),"+f"(d[23]),"+f"(d[24]),"+f"(d[25]),"+f"(d[26]),"+f"(d[27]),"+f"(d[28]),"+f"(d[29]),"+f"(d[30]),"+f"(d[31]),"+f"(d[32]),"+f"(d[33]),"+f"(d[34]),"+f"(d[35])
    : "l"(ad), "l"(bd));
  }
}
template<int SD> __device__ __forceinline__ void wg_tt64(float* d, uint64_t ad, uint64_t bd) {
  if constexpr (SD) {
    asm volatile("{\n.reg .pred p;\nsetp.eq.b32 p, 0, 0;\n"
    "wgmma.mma_async.sync.aligned.m64n64k16.f32.bf16.bf16 {%0,%1,%2,%3,%4,%5,%6,%7,%8,%9,%10,%11,%12,%13,%14,%15,%16,%17,%18,%19,%20,%21,%22,%23,%24,%25,%26,%27,%28,%29,%30,%31}, %32, %33, p, 1, 1, 1, 1;\n}"
    : "+f"(d[0]),"+f"(d[1]),"+f"(d[2]),"+f"(d[3]),"+f"(d[4]),"+f"(d[5]),"+f"(d[6]),"+f"(d[7]),"+f"(d[8]),"+f"(d[9]),"+f"(d[10]),"+f"(d[11]),"+f"(d[12]),"+f"(d[13]),"+f"(d[14]),"+f"(d[15]),"+f"(d[16]),"+f"(d[17]),"+f"(d[18]),"+f"(d[19]),"+f"(d[20]),"+f"(d[21]),"+f"(d[22]),"+f"(d[23]),"+f"(d[24]),"+f"(d[25]),"+f"(d[26]),"+f"(d[27]),"+f"(d[28]),"+f"(d[29]),"+f"(d[30]),"+f"(d[31])
    : "l"(ad), "l"(bd));
  } else {
    asm volatile("{\n.reg .pred p;\nsetp.ne.b32 p, 0, 0;\n"
    "wgmma.mma_async.sync.aligned.m64n64k16.f32.bf16.bf16 {%0,%1,%2,%3,%4,%5,%6,%7,%8,%9,%10,%11,%12,%13,%14,%15,%16,%17,%18,%19,%20,%21,%22,%23,%24,%25,%26,%27,%28,%29,%30,%31}, %32, %33, p, 1, 1, 1, 1;\n}"
    : "+f"(d[0]),"+f"(d[1]),"+f"(d[2]),"+f"(d[3]),"+f"(d[4]),"+f"(d[5]),"+f"(d[6]),"+f"(d[7]),"+f"(d[8]),"+f"(d[9]),"+f"(d[10]),"+f"(d[11]),"+f"(d[12]),"+f"(d[13]),"+f"(d[14]),"+f"(d[15]),"+f"(d[16]),"+f"(d[17]),"+f"(d[18]),"+f"(d[19]),"+f"(d[20]),"+f"(d[21]),"+f"(d[22]),"+f"(d[23]),"+f"(d[24]),"+f"(d[25]),"+f"(d[26]),"+f"(d[27]),"+f"(d[28]),"+f"(d[29]),"+f"(d[30]),"+f"(d[31])
    : "l"(ad), "l"(bd));
  }
}

template<int V> struct IC { static constexpr int v = V; };
template<int I, int N, class F> __device__ __forceinline__ void sfor(F&& f) {
    if constexpr (I < N) { f(IC<I>{}); sfor<I + 1, N>(f); }
}

enum { K_QKV = 0, K_H = 1 };

struct Ctx {
    uint32_t tph;
    bool pf = false;
};
__device__ __forceinline__ uint32_t v_wgoff() { return (v_tid() >> 7) * 512; }
__device__ __forceinline__ bool v_lane0() { return (v_tid() & 31) == 0; }
__device__ __forceinline__ void release_slot(const Ctx&, int slot) { if (v_lane0()) mbar_arrive(bar(B_EMPTY + slot)); }

__device__ __forceinline__ void turn_wait(const Ctx&) { asm volatile("bar.sync %0, 256;" :: "r"(4 + (v_tid() >> 7)) : "memory"); }
__device__ __forceinline__ void turn_pass(const Ctx&) { asm volatile("bar.arrive %0, 256;" :: "r"(5 - (v_tid() >> 7)) : "memory"); }

template<int KIND, class PART, class POST>
__device__ __forceinline__ void run_step(Ctx& c, float* acc, const uint32_t* a, PART&& part, POST&& post) {
    constexpr int NST = (KIND == K_QKV) ? 6 : 3;
    constexpr int KPS = 36 / NST;
    sfor<0, NST>([&](auto ST) {
        constexpr int st = decltype(ST)::v;
        constexpr int slot = st % 3;
        mbar_wait(bar(B_FULL + slot), c.tph);
        uint32_t wgo = 0;
        if constexpr (st == NST - 1) wgo = v_wgoff();
        if (KIND == K_H && c.pf) prof(44 + st * 5);
        turn_wait(c);
        if (KIND == K_H && c.pf) prof(45 + st * 5);
        wg_fence();
        sfor<0, KPS>([&](auto KK) {
            constexpr int kk = decltype(KK)::v;
            constexpr int ks = st * KPS + kk;
            constexpr int SD = ks ? 1 : 0;
            if constexpr (KIND == K_QKV) {
                constexpr uint64_t bd = mkdesc(RING + slot * SLOT + kk * 2048, 12288, 1024, 1);
                if constexpr (ks < 32) wg_rs72<SD>(acc, a + ks * 4, bd);
                else wg_ss72<SD>(acc, mkdesc(XB + (ks - 32) * 32, 16, 1024, 1) + wgo, bd);
            } else {
                constexpr uint64_t bd = mkdesc(RING + slot * SLOT + kk * 2048, 16, 1024, 1);
                if constexpr (ks < 32) wg_rs64<SD>(acc, a + ks * 4, bd);
                else wg_ss64<SD>(acc, mkdesc(XB + (ks - 32) * 32, 16, 1024, 1) + wgo, bd);
            }
        });
        wg_commit();
        turn_pass(c);
        if (KIND == K_H && c.pf) prof(46 + st * 5);
        part(ST);
        if (KIND == K_H && c.pf) prof(47 + st * 5);
        wg_wait<0>();
        if (KIND == K_H && c.pf) prof(48 + st * 5);
        release_slot(c, slot);
        if constexpr (slot == 2) c.tph ^= 1;
        post(ST);
    });
    if constexpr (KIND == K_QKV) reg_fence<36>(acc); else reg_fence<32>(acc);
}

__device__ __forceinline__ float phi(float t) {
    float e = ex2(t * 1.4426950408889634f);
    return (t > 0.f ? t + 1.0f : e) + 1e-6f;
}
__device__ __forceinline__ float gelu_h(float hx) {
    float u = hx * fmaf(hx * hx, 0.2854192650f, 1.5957691216f);
    return fmaf(hx, tanh_ap(u), hx);
}

struct Params {
    const __nv_bfloat16* x;
    const __nv_bfloat16* wqkv;
    const __nv_bfloat16* wo;
    const __nv_bfloat16* w1;
    const __nv_bfloat16* b1;
    const __nv_bfloat16* w2;
    const __nv_bfloat16* b2;
    __nv_bfloat16* out;
};

__global__ void __launch_bounds__(384, 1)
fused_kernel(const __grid_constant__ CUtensorMap tm_x, const __grid_constant__ CUtensorMap tm_w1,
             const __grid_constant__ CUtensorMap tm_w2, const __grid_constant__ CUtensorMap tm_wo,
             const __grid_constant__ CUtensorMap tm_o, const __grid_constant__ CUtensorMap tm_qkv,
             const __grid_constant__ CUtensorMap tm_qkve, const Params p) {
    extern __shared__ __align__(1024) unsigned char smem_raw[];
    const int tid = threadIdx.x;
    const int bid = blockIdx.x;
    const bool is_main = bid < NMAIN;
    const int j = bid & 7;
    const int m = bid >> 3;

    if (tid == 0) {
        if ((uint32_t)__cvta_generic_to_shared(smem_raw) != SB) __trap();
        for (int i = 0; i < 3; i++) {
            mbar_init(bar(B_FULL + i), 1); mbar_init(bar(B_EMPTY + i), 8);
            mbar_init(bar(B_XFULL + i), 1); mbar_init(bar(B_OFULL + i), 1);
        }
        mbar_init(bar(B_KVB), is_main ? 2 : 8); mbar_init(bar(B_YRDY), 1);
        for (int i = 0; i < 4; i++) mbar_init(bar(B_OFREE + i), 8);
        asm volatile("fence.mbarrier_init.release.cluster;" ::: "memory");
        if (is_main) {
            for (int g = 0; g < 3; g++) {
                mbar_expect_tx(bar(B_XFULL + g), 49152);
                for (int kb = 3 * g; kb < 3 * g + 3; kb++) tma_2d(HA + kb * 16384, &tm_x, bar(B_XFULL + g), kb * 64, m * 128);
            }
            for (int st = 0; st < 3; st++) {
                mbar_expect_tx(bar(B_FULL + st), 96 * 144);
                tma_2d(RING + st * SLOT, &tm_qkv, bar(B_FULL + st), 576 + j * 72, st * 96);
                tma_2d(RING + st * SLOT + 12288, &tm_qkve, bar(B_FULL + st), 576 + j * 72 + 64, st * 96);
            }
        }
    }
    if (tid == 32) sts32(EPO, g_epoch[bid]);
    if (tid >= 40 && tid < 48) sts32(EVC + (tid - 40) * 4, 0);
    if (tid >= 64 && tid < 64 + 288 && is_main) {
        int i = tid - 64;
        uint32_t v = *reinterpret_cast<const uint32_t*>(p.b1 + j * 576 + 2 * i);
        sts32(B1S + 8 * i, __float_as_uint(0.5f * bf_lo(v))); sts32(B1S + 8 * i + 4, __float_as_uint(0.5f * bf_hi(v)));
    }
    if (tid >= 352) {
        int i = tid - 352;
        uint32_t v = *reinterpret_cast<const uint32_t*>(p.b2 + (is_main ? j : 8) * 64 + 2 * i);
        sts32(B2S + 8 * i, v << 16); sts32(B2S + 8 * i + 4, v & 0xffff0000u);
    }
    fence_async_smem();
    __syncthreads();
    uint32_t epoch;
    asm volatile("ld.shared.u32 %0, [%1];" : "=r"(epoch) : "r"(EPO));
    const uint32_t par = epoch & 1;

    if (tid >= 256) {
        asm volatile("setmaxnreg.dec.sync.aligned.u32 24;");
        const int hw = (tid >> 5) - 8, lane = tid & 31;
        if (hw == 0) {
            if (lane == 0) {
                uint32_t n = 0;
                if (is_main) {
                    n = 1;
                    #pragma unroll 1
                    for (int u = 3; u < 18; u++) {
                        const int st = u % 3, step = u / 6;
                        const int col = ((step == 2) ? 0 : (step + 1) * 576) + j * 72, row = (u % 6) * 96;
                        mbar_wait(bar(B_EMPTY + st), (n & 1) ^ 1);
                        mbar_expect_tx(bar(B_FULL + st), 96 * 144);
                        tma_2d(RING + st * SLOT, &tm_qkv, bar(B_FULL + st), col, row);
                        tma_2d(RING + st * SLOT + 12288, &tm_qkve, bar(B_FULL + st), col + 64, row);
                        if (st == 2) n++;
                    }
                }
                const int nsteps = is_main ? 19 : 4;
                #pragma unroll 1
                for (int s = 0; s < nsteps; s++, n++) {
                    const CUtensorMap* tm; int col, row;
                    if (!is_main) { tm = &tm_wo; col = 512; row = 0; }
                    else if (s < 9) { tm = &tm_w1; col = j * 576 + s * 64; row = 0; }
                    else if (s < 18) { tm = &tm_w2; col = (s == 9) ? 512 : (((j + s - 9) & 7) * 64); row = j * 576; }
                    else { tm = &tm_wo; col = j * 64; row = 0; }
                    #pragma unroll 1
                    for (int st = 0; st < 3; st++) {
                        mbar_wait(bar(B_EMPTY + st), (n & 1) ^ 1);
                        mbar_expect_tx(bar(B_FULL + st), SLOT);
                        tma_2d(RING + st * SLOT, tm, bar(B_FULL + st), col, row + st * 192);
                    }
                }
            }
        } else {
            if (is_main) {
                const int t = tid - 288;
                #pragma unroll 1
                for (int i = t; i < 36 * 6; i += 96) {
                    int r = i / 6, q = i - r * 6;
                    prefetch_l2(reinterpret_cast<const char*>(p.wqkv) + (36 * m + r) * 3456 + (q >> 1) * 1152 + j * 144 + (q & 1) * 128);
                }
                __nanosleep(PF1_NS);
                #pragma unroll 1
                for (int i = t; i < 36 * 9; i += 96) {
                    int r = i / 9, q = i - r * 9;
                    prefetch_l2(reinterpret_cast<const char*>(p.w1) + (36 * m + r) * 9216 + j * 1152 + q * 128);
                }
                __nanosleep(PF2_NS);
                #pragma unroll 1
                for (int i = t; i < 36 * 9; i += 96)
                    prefetch_l2(reinterpret_cast<const char*>(p.w2) + (576 * j + 36 * m) * 1152 + i * 128);
                if (t < 41 && (bid * 41 + t) < 5184) prefetch_l2(reinterpret_cast<const char*>(p.wo) + (bid * 41 + t) * 128);
                if (hw != 2) {
                    if (lane == 0) wait_cnt(cnt_kv(j), (epoch + 1) * 16);
                    __syncwarp();
                    const float4* kv = reinterpret_cast<const float4*>(g_kv + (par * 8 + j) * 1440);
                    #pragma unroll 2
                    for (int i = lane + (hw == 1 ? 0 : 32); i < 360; i += 64) {
                        const float4 v = __ldcg(kv + i);
                        const int d = i / 5, e = (i - d * 5) * 4, h = d / 18;
                        const uint32_t base = KVB + (d >> 3) * 128 + (d & 7) * 16;
                        const int n0 = 8 + h * 18 + e;
                        sts32(base + (n0 >> 3) * 1280 + (n0 & 7) * 2, pack_bf16(v.x, v.y));
                        if (e < 16) sts32(base + ((n0 + 2) >> 3) * 1280 + ((n0 + 2) & 7) * 2, pack_bf16(v.z, v.w));
                        else asm volatile("st.shared.u16 [%0], %1;" :: "r"(base + h * 2), "h"((unsigned short)pack_bf16(v.z, 0.f)) : "memory");
                    }
                    fence_async_smem();
                    __syncwarp();
                    if (lane == 0) mbar_arrive(bar(B_KVB));
                }
            }
            if (hw == 1) {
                if (lane == 0) {
                    const int nit = is_main ? 1 : 4;
                    for (int it = 0; it < nit; it++) {
                        const int mt = is_main ? m : ((bid - NMAIN) * 4 + it);
                        const bool wf = is_main || it > 0;
                        const uint32_t fp = is_main ? 0 : ((it - 1) & 1);
                        wait_cnt(cnt_o(mt), (epoch + 1) * 8);
                        fence_async_all();
                        #pragma unroll 1
                        for (int kb = 0; kb < 9; kb++) {
                            const int g = kb / 3;
                            if (kb == 3 * g || kb == 8) { if (wf) mbar_wait(bar(B_OFREE + (kb == 8 ? 3 : g)), fp); }
                            if (kb == 3 * g) mbar_expect_tx(bar(B_OFULL + g), 49152);
                            tma_2d(HA + kb * 16384, &tm_o, bar(B_OFULL + g), kb * 64, mt * 128);
                        }
                    }
                    if (is_main) { wait_cnt(cnt_y(m, j), (epoch + 1) * 7); mbar_arrive(bar(B_YRDY)); }
                }
            } else if (hw == 2) {
                if (!is_main) {
                    if (lane == 0) {
                        #pragma unroll 1
                        for (int it = 0; it < 4; it++) {
                            if (it > 0) mbar_wait(bar(B_KVB), (it - 1) & 1);
                            wait_cnt(cnt_y((bid - NMAIN) * 4 + it, 8), (epoch + 1) * 8);
                            mbar_arrive(bar(B_YRDY));
                        }
                    }
                } else {
                    #pragma unroll 1
                    for (int e = 0; e < 10; e++) {
                        int spin = 0;
                        while (true) {
                            uint32_t v;
                            asm volatile("ld.acquire.cta.shared.u32 %0, [%1];" : "=r"(v) : "r"(EVC + (lane & 7) * 4) : "memory");
                            if (__all_sync(0xffffffffu, v > (uint32_t)e)) break;
                            if (++spin > 20000000) __trap();
                            __nanosleep(20);
                        }
                        if (lane == 0) {
                            unsigned int* cp = (e == 0) ? cnt_kv(j) : (e == 1) ? cnt_o(m) : cnt_y(m, e == 2 ? 8 : ((j + e - 2) & 7));
                            if (e == 1) fence_async_all();
                            __threadfence();
                            asm volatile("red.relaxed.gpu.global.add.u32 [%0], 1;" :: "l"(cp) : "memory");
                        }
                        __syncwarp();
                    }
                }
            } else {
                {
                    const int t0 = is_main ? (m * 9 + j) : ((bid - NMAIN) * 4 * 9 + 8);
                    const int nt = is_main ? 1 : 4;
                    for (int t = 0; t < nt; t++) {
                        uint4* z = reinterpret_cast<uint4*>(g_yacc + (size_t)((par ^ 1) * 144 + t0 + t * 9) * YT_BYTES);
                        for (int i = lane; i < YT_BYTES / 16; i += 32) z[i] = make_uint4(0, 0, 0, 0);
                    }
                    if (is_main && m == 0) {
                        float* z = g_kv + ((par ^ 1) * 8 + j) * 1440;
                        for (int i = lane; i < 1440; i += 32) z[i] = 0.f;
                    }
                }
            }
        }
    } else {
        asm volatile("setmaxnreg.inc.sync.aligned.u32 240;");
        prof(0);
        Ctx c; c.tph = 0;
        float hc[32], pv[36];
        if (tid >> 7) turn_pass(c);
        auto event = [&](uint32_t ev) {
            __syncwarp();
            if (v_lane0()) asm volatile("st.release.cta.shared.u32 [%0], %1;" :: "r"(EVC + (v_tid() >> 3)), "r"(ev) : "memory");
        };
        auto warp_arrive = [&](uint32_t b) { __syncwarp(); if (v_lane0()) mbar_arrive(b); };

        if (is_main) {
            uint32_t a[128];
            float rs0, rs1;
            uint32_t m00, m11;
            auto lrow_off = [&]() { uint32_t t_ = v_tid(); return HA + ((t_ >> 5) * 16 + (t_ & 15)) * 128 + ((((t_ >> 4) & 1) ^ (t_ & 7)) << 4); };
            auto tail_off = [&]() { uint32_t t_ = v_tid(), g = (t_ >> 2) & 7; return XB + ((t_ >> 5) * 16 + g) * 128 + (g << 4) + (t_ & 3) * 4; };
            {
                uint32_t tl[16];
                const uint32_t lrow = lrow_off();
                float cs[2][4] = {{0.f, 0.f, 0.f, 0.f}, {0.f, 0.f, 0.f, 0.f}};
                sfor<0, 36>([&](auto KS) {
                    constexpr int ks = decltype(KS)::v;
                    if constexpr (ks % 12 == 0) mbar_wait(bar(B_XFULL + ks / 12), 0);
                    uint32_t* dst = (ks < 32) ? (a + (ks & 31) * 4) : (tl + (ks & 3) * 4);
                    ldsm4((lrow ^ ((ks % 4) << 5)) + (ks / 4) * 16384, dst);
                    mma_ones(cs[ks & 1], dst);
                });
                prof(2);
                float mean0 = (cs[0][0] + cs[1][0]) * (1.0f / 576.0f), mean1 = (cs[0][2] + cs[1][2]) * (1.0f / 576.0f);
                m00 = pack_bf16(mean0, mean0); m11 = pack_bf16(mean1, mean1);
                rs0 = mean0 - bf_lo(m00); rs1 = mean1 - bf_lo(m11);
                rs0 = -144.0f * rs0 * rs0; rs1 = -144.0f * rs1 * rs1;
                const uint32_t tb = tail_off();
                #pragma unroll
                for (int i = 0; i < 16; i++) {
                    const uint32_t w = sub_bf16x2(tl[i], (i & 1) ? m11 : m00);
                    sts32((tb ^ ((i >> 1) << 4)) + (i & 1) * 1024, w);
                    float lo = bf_lo(w), hi = bf_hi(w);
                    if (i & 1) rs1 = fmaf(lo, lo, fmaf(hi, hi, rs1)); else rs0 = fmaf(lo, lo, fmaf(hi, hi, rs0));
                }
                fence_async_smem();
                #pragma unroll
                for (int i = 0; i < 128; i++) a[i] = sub_bf16x2(a[i], (i & 1) ? m11 : m00);
                named_bar(2 + (tid >> 7), 128);
            }
            prof(3);
            auto cm_off = [&]() { uint32_t t_ = v_tid(); return (t_ >> 5) * 256 + (t_ & 31) * 4; };
            {
                float qc[36];
                #pragma unroll
                for (int i = 0; i < 36; i++) { qc[i] = 0.f; pv[i] = 0.f; }
                #pragma unroll 1
                for (int s = 0; s < 3; s++) {
                    run_step<K_QKV>(c, qc, a, [&](auto ST) {
                        constexpr int st = decltype(ST)::v;
                        if (s == 0) {
                            const uint32_t lrow = lrow_off();
                            sfor<(st * 32) / 6, ((st + 1) * 32) / 6>([&](auto I) {
                                constexpr int ks = decltype(I)::v;
                                uint32_t v[4];
                                ldsm4((lrow ^ ((ks % 4) << 5)) + (ks / 4) * 16384, v);
                                #pragma unroll
                                for (int r = 0; r < 4; r++) {
                                    uint32_t w = sub_bf16x2(v[r], (r & 1) ? m11 : m00);
                                    float lo = bf_lo(w), hi = bf_hi(w);
                                    if (r & 1) rs1 = fmaf(lo, lo, fmaf(hi, hi, rs1)); else rs0 = fmaf(lo, lo, fmaf(hi, hi, rs0));
                                }
                            });
                            if constexpr (st == 5) {
                                rs0 += __shfl_xor_sync(0xffffffffu, rs0, 1); rs1 += __shfl_xor_sync(0xffffffffu, rs1, 1);
                                rs0 += __shfl_xor_sync(0xffffffffu, rs0, 2); rs1 += __shfl_xor_sync(0xffffffffu, rs1, 2);
                                rs0 = rsqrtf(fmaxf(rs0 * (1.0f / 576.0f), 0.f) + 1e-5f);
                                rs1 = rsqrtf(fmaxf(rs1 * (1.0f / 576.0f), 0.f) + 1e-5f);
                                named_bar(1, 256);
                            }
                        } else {
                            const uint32_t cm = cm_off();
                            sfor<0, 9>([&](auto B) {
                                constexpr int b = decltype(B)::v;
                                if constexpr ((b * 6) / 9 == st) {
                                    const float v0 = pv[4 * b] * rs0, v1 = pv[4 * b + 1] * rs0, v2 = pv[4 * b + 2] * rs1, v3 = pv[4 * b + 3] * rs1;
                                    if (s == 1) {
                                        sts32(PKT + b * 2048 + cm, pack_bf16(phi(v0), phi(v1)));
                                        sts32(PKT + b * 2048 + cm + 128, pack_bf16(phi(v2), phi(v3)));
                                    } else {
                                        const uint32_t w0 = pack_bf16(v0, v1), w1 = pack_bf16(v2, v3);
                                        if constexpr (b <= 4) { sts32(VT + b * 2048 + cm, w0); sts32(VT + b * 2048 + cm + 128, w1); }
                                        if constexpr (b >= 4) { sts32(VT + (b + 2) * 2048 + cm, w0); sts32(VT + (b + 2) * 2048 + cm + 128, w1); }
                                        if constexpr (b == 0) {
                                            const uint32_t one = (cm & 12) ? 0u : 0x00003F80u;
                                            sts32(VT + 5 * 2048 + cm, one); sts32(VT + 5 * 2048 + cm + 128, one);
                                        }
                                        if constexpr (b == 8) {
                                            const uint32_t z = KVB + v_tid() * 16;
                                            sts128(z, 0, 0, 0, 0); sts128(z + 4096, 0, 0, 0, 0); sts128(z + 8192, 0, 0, 0, 0);
                                            if (z < KVB + 512) sts128(z + 12288, 0, 0, 0, 0);
                                            fence_async_smem();
                                        }
                                    }
                                }
                            });
                        }
                    }, [](auto) {});
                    reg_copy<36>(pv, qc);
                    prof(4 + s);
                }
            }
            {
                #pragma unroll
                for (int i = 0; i < 32; i++) hc[i] = 0.f;
                named_bar(1, 256);
                const uint32_t wgo = v_wgoff();
                wg_fence();
                sfor<0, 8>([&](auto KS) {
                    constexpr int ks = decltype(KS)::v;
                    wg_tt64<(ks ? 1 : 0)>(hc, mkdesc(PKT + ks * 256, 128, 2048, 0) + wgo,
                                          mkdesc(VT + ks * 256, 128, 2048, 0) + wgo + (wgo >> 2));
                });
                wg_commit();
                const uint32_t pq = PQT + cm_off() + v_wgoff() * 16;
                sfor<0, 9>([&](auto B) {
                    constexpr int b = decltype(B)::v;
                    sts32(pq + b * 1024, pack_bf16(phi(pv[4 * b] * rs0), phi(pv[4 * b + 1] * rs0)));
                    sts32(pq + b * 1024 + 128, pack_bf16(phi(pv[4 * b + 2] * rs1), phi(pv[4 * b + 3] * rs1)));
                });
                fence_async_smem();
                wg_wait<0>();
                reg_fence<32>(hc);
                reg_copy<24>(pv, hc);
            }
            prof(7);
            rs0 *= 0.5f; rs1 *= 0.5f;
            auto gelun = [&](auto B0, auto B1, uint32_t bofs, uint32_t* w) {
                constexpr int b0 = decltype(B0)::v, nb = decltype(B1)::v - b0;
                float2 bv[nb];
                #pragma unroll
                for (int i = 0; i < nb; i++) bv[i] = lds64f(bofs + (b0 + i) * 32);
                #pragma unroll
                for (int i = 0; i < nb; i++) {
                    const int b = b0 + i;
                    w[2 * i]     = pack_bf16(gelu_h(fmaf(pv[4 * b], rs0, bv[i].x)), gelu_h(fmaf(pv[4 * b + 1], rs0, bv[i].y)));
                    w[2 * i + 1] = pack_bf16(gelu_h(fmaf(pv[4 * b + 2], rs1, bv[i].x)), gelu_h(fmaf(pv[4 * b + 3], rs1, bv[i].y)));
                }
            };
            auto spill_off = [&]() { uint32_t t_ = v_tid(); return HA + (t_ >> 7) * 8192 + (t_ & 127) * 8; };
            auto reload = [&](auto S0, auto S1) {
                const uint32_t spill = spill_off();
                sfor<decltype(S0)::v * 8, decltype(S1)::v * 8>([&](auto Q) {
                    constexpr int q = decltype(Q)::v;
                    lds64(spill + (q / 8) * 16384 + (q % 8) * 1024, a + q * 2);
                });
            };
            #pragma unroll 1
            for (int idx = 0; idx < 18; idx++) {
                run_step<K_H>(c, hc, a, [&](auto ST) {
                    constexpr int st = decltype(ST)::v;
                    if (idx >= 10) {
                        if constexpr (st == 0) {
                            const uint32_t b_ = v_bid();
                            const uint32_t chunk = (idx == 10) ? 8 : ((b_ + idx - 10) & 7);
                            unsigned char* yp = g_yacc + ((v_epoch() & 1) * 144 + (b_ >> 3) * 9 + chunk) * YT_BYTES + v_tid() * 16;
                            sfor<0, 4>([&](auto Q) {
                                constexpr int q = decltype(Q)::v;
                                asm volatile("red.global.add.noftz.v4.bf16x2 [%0], {%1,%2,%3,%4};" :: "l"(yp + q * 4096),
                                             "r"(pack_bf16(pv[8 * q], pv[8 * q + 1])), "r"(pack_bf16(pv[8 * q + 2], pv[8 * q + 3])),
                                             "r"(pack_bf16(pv[8 * q + 4], pv[8 * q + 5])), "r"(pack_bf16(pv[8 * q + 6], pv[8 * q + 7])) : "memory");
                            });
                            event(idx - 7);
                        }
                    } else if (idx >= 1) {
                        const uint32_t bofs = B1S + (idx - 1) * 256 + (v_tid() & 3) * 8;
                        if (idx < 9) {
                            if constexpr (st == 0) { if (idx == OSTEP_AT + 1) event(2); }
                            const uint32_t spill = spill_off() + (idx - 1) * 16384;
                            constexpr int b0 = st * 3, b1 = (st == 2 ? 8 : st * 3 + 3);
                            uint32_t w[6];
                            gelun(IC<b0>{}, IC<b1>{}, bofs, w);
                            #pragma unroll
                            for (int b = b0; b < b1; b++) sts64(spill + b * 1024, w[2 * (b - b0)], w[2 * (b - b0) + 1]);
                        } else {
                            if constexpr (st < 2) {
                                const uint32_t tb = tail_off();
                                uint32_t w[8];
                                gelun(IC<st * 4>{}, IC<st * 4 + 4>{}, bofs, w);
                                #pragma unroll
                                for (int i = 0; i < 4; i++) { sts32(tb ^ ((st * 4 + i) << 4), w[2 * i]); sts32((tb ^ ((st * 4 + i) << 4)) + 1024, w[2 * i + 1]); }
                            }
                            if constexpr (st == 1) { fence_async_smem(); named_bar(2 + (v_tid() >> 7), 128); }
                        }
                    } else {
                        if constexpr (st < 2) {
                            constexpr int hf = st;
                            const int t_ = v_tid(), wg = t_ >> 7, t = t_ & 3;
                            float* dst = g_kv + ((v_epoch() & 1) * 8 + (v_bid() & 7)) * 1440;
                            const int d = wg * 32 + ((t_ >> 5) & 3) * 16 + ((t_ >> 2) & 7) + hf * 8;
                            const bool dv = wg ? (d >= 36 && d < 72) : (d < 36);
                            const int e00 = wg * 24 + 2 * t - (d / 18) * 18;
                            float* dp = dst + d * 20 + e00;
                            #pragma unroll
                            for (int i = 0; i < 6; i++) {
                                const int e = e00 + i * 8;
                                const bool blk = wg ? (i >= 1) : (i <= 4);
                                if (dv && blk && e >= 0 && e < 18)
                                    asm volatile("red.global.add.v2.f32 [%0], {%1,%2};" :: "l"(dp + i * 8), "f"(pv[4 * i + 2 * hf]), "f"(pv[4 * i + 2 * hf + 1]) : "memory");
                            }
                            if (dv && t == 0) atomicAdd(dst + d * 20 + 18, wg ? pv[2 * hf] : pv[20 + 2 * hf]);
                            if constexpr (st == 1) event(1);
                        }
                    }
                }, [&](auto ST) {
                    constexpr int st = decltype(ST)::v;
                    if (idx == 8) {
                        reload(IC<3 * st>{}, IC<(st == 2 ? 8 : 3 * st + 3)>{});
                        warp_arrive(bar(B_OFREE + st));
                    }
                });
                reg_copy<32>(pv, hc);
                prof(8 + idx);
                if (idx == OSTEP_AT) {
                    mbar_wait(bar(B_KVB), 0);
                    prof(34);
                    const uint32_t pqo = (v_tid() >> 7) * 576;
                    const int t_ = v_tid(), b_ = v_bid(), t = t_ & 3, l4 = t_ & 28;
                    __nv_bfloat16* op = g_o + (size_t)((b_ >> 3) * 128 + (t_ >> 5) * 16 + ((t_ >> 2) & 7)) * DM + (b_ & 7) * 72 + 2 * t;
                    float r3[2];
                    sfor<0, 2>([&](auto PS) {
                        constexpr int ps = decltype(PS)::v;
                        wg_fence();
                        sfor<0, 5>([&](auto KS) {
                            constexpr int ks = decltype(KS)::v;
                            wg_ss64<(ks ? 1 : 0)>(hc, mkdesc(PQT + ks * 2048, ks == 4 ? 0 : 1024, 128, 0) + pqo, mkdesc(KVB + ps * 8 * 1280 + ks * 256, 128, 1280, 0));
                        });
                        wg_commit();
                        wg_wait<0>();
                        reg_fence<32>(hc);
                        #pragma unroll
                        for (int hf = 0; hf < 2; hf++) {
                            if constexpr (ps == 0) {
                                float r[4];
                                r[0] = rcp(__shfl_sync(0xffffffffu, hc[2 * hf], l4) + 1e-6f);
                                r[1] = rcp(__shfl_sync(0xffffffffu, hc[1 + 2 * hf], l4) + 1e-6f);
                                r[2] = rcp(__shfl_sync(0xffffffffu, hc[2 * hf], l4 + 1) + 1e-6f);
                                r[3] = rcp(__shfl_sync(0xffffffffu, hc[1 + 2 * hf], l4 + 1) + 1e-6f);
                                r3[hf] = r[3];
                                #pragma unroll
                                for (int i = 0; i < 7; i++) {
                                    float rr = (i < 2) ? r[0] : (i == 2) ? (t < 1 ? r[0] : r[1]) : (i == 3) ? r[1] : (i == 4) ? (t < 2 ? r[1] : r[2])
                                             : (i == 5) ? r[2] : (t < 3 ? r[2] : r[3]);
                                    *reinterpret_cast<uint32_t*>(op + hf * 8 * DM + i * 8) = pack_bf16(hc[4 * i + 4 + 2 * hf] * rr, hc[4 * i + 5 + 2 * hf] * rr);
                                }
                            } else {
                                #pragma unroll
                                for (int i = 0; i < 2; i++)
                                    *reinterpret_cast<uint32_t*>(op + hf * 8 * DM + 56 + i * 8) = pack_bf16(hc[4 * i + 2 * hf] * r3[hf], hc[4 * i + 1 + 2 * hf] * r3[hf]);
                            }
                        }
                    });
                }
            }
            warp_arrive(bar(B_OFREE + 3));
        }
        const int b2_ = v_bid(), t2_ = v_tid();
        uint32_t xr[16];
        uint4 yv[4];
        auto load_x = [&](size_t eoff) {
            #pragma unroll
            for (int i = 0; i < 8; i++) {
                xr[2 * i] = __ldg(reinterpret_cast<const uint32_t*>(p.x + eoff + i * 8));
                xr[2 * i + 1] = __ldg(reinterpret_cast<const uint32_t*>(p.x + eoff + 8 * DM + i * 8));
            }
        };
        auto load_y = [&](int tile) {
            const unsigned char* yp = g_yacc + ((v_epoch() & 1) * 144 + tile) * YT_BYTES + t2_ * 16;
            #pragma unroll
            for (int q = 0; q < 4; q++) yv[q] = __ldcg(reinterpret_cast<const uint4*>(yp + q * 4096));
        };
        auto gate = [&]() {
            #pragma unroll
            for (int q = 0; q < 4; q++) {
                const uint4 u = yv[q];
                pv[8 * q] += bf_lo(u.x); pv[8 * q + 1] += bf_hi(u.x); pv[8 * q + 2] += bf_lo(u.y); pv[8 * q + 3] += bf_hi(u.y);
                pv[8 * q + 4] += bf_lo(u.z); pv[8 * q + 5] += bf_hi(u.z); pv[8 * q + 6] += bf_lo(u.w); pv[8 * q + 7] += bf_hi(u.w);
            }
            #pragma unroll
            for (int i = 0; i < 32; i++) pv[i] = pv[i] * rcp(1.0f + ex2(pv[i] * -1.4426950408889634f));
        };
        auto add_b2 = [&]() {
            #pragma unroll
            for (int b = 0; b < 8; b++) {
                float2 bv = lds64f(B2S + b * 32 + (t2_ & 3) * 8);
                pv[4 * b] += bv.x; pv[4 * b + 1] += bv.y; pv[4 * b + 2] += bv.x; pv[4 * b + 3] += bv.y;
            }
        };
        auto store_out = [&](size_t eoff) {
            #pragma unroll
            for (int b = 0; b < 8; b++) {
                *reinterpret_cast<uint32_t*>(p.out + eoff + b * 8) =
                    pack_bf16(fmaf(hc[4 * b], pv[4 * b], bf_lo(xr[2 * b])), fmaf(hc[4 * b + 1], pv[4 * b + 1], bf_hi(xr[2 * b])));
                *reinterpret_cast<uint32_t*>(p.out + eoff + 8 * DM + b * 8) =
                    pack_bf16(fmaf(hc[4 * b + 2], pv[4 * b + 2], bf_lo(xr[2 * b + 1])), fmaf(hc[4 * b + 3], pv[4 * b + 3], bf_hi(xr[2 * b + 1])));
            }
        };
        const int rowoff = (t2_ >> 5) * 16 + ((t2_ >> 2) & 7);
        const bool mainf = b2_ < NMAIN;
        uint32_t sv[16];
        if (!mainf) {
            #pragma unroll
            for (int i = 0; i < 32; i++) hc[i] = 0.f;
        }
        #pragma unroll
        for (int i = 0; i < 16; i++) sv[i] = 0;
        #pragma unroll 1
        for (int job = mainf ? 4 : 0; job < 5; job++) {
            const bool do_s = mainf || job < 4, do_f = job >= 1;
            const int mt = mainf ? (b2_ >> 3) : ((b2_ - NMAIN) * 4 + job - 1);
            const int ch = mainf ? (b2_ & 7) : 8;
            const size_t eoff = (size_t)(mt * 128 + rowoff) * DM + ch * 64 + 2 * (t2_ & 3);
            sfor<0, 3>([&](auto ST) {
                constexpr int st = decltype(ST)::v;
                if (do_s) {
                    mbar_wait(bar(B_FULL + st), c.tph);
                    mbar_wait(bar(B_OFULL + st), job & 1);
                }
                const uint32_t wgo = v_wgoff();
                turn_wait(c);
                wg_fence();
                sfor<0, 12>([&](auto KK) {
                    constexpr int kk = decltype(KK)::v;
                    constexpr int ks = st * 12 + kk;
                    wg_ss64<(ks ? 1 : 0)>(hc, mkdesc(HA + (ks / 4) * 16384 + (ks % 4) * 32, 16, 1024, 1) + wgo,
                                          mkdesc(RING + st * SLOT + kk * 2048, 16, 1024, 1));
                });
                wg_commit();
                if (st < 2 || job < 4 || wgo == 0) turn_pass(c);
                if (do_f) {
                    if constexpr (st == 0) {
                        load_x(eoff);
                        if (!mainf) {
                            #pragma unroll
                            for (int i = 0; i < 32; i++) pv[i] = 0.f;
                        }
                        add_b2();
                    } else if constexpr (st == 1) {
                        prof(26);
                        mbar_wait(bar(B_YRDY), mainf ? 0 : ((job - 1) & 1));
                        prof(27);
                        load_y(mt * 9 + ch);
                        if (!mainf) warp_arrive(bar(B_KVB));
                    } else { prof(28); gate(); prof(29); }
                }
                wg_wait<0>();
                if (v_lane0()) { mbar_arrive(bar(B_EMPTY + st)); mbar_arrive(bar(B_OFREE + st)); if (st == 2) mbar_arrive(bar(B_OFREE + 3)); }
            });
            c.tph ^= 1;
            reg_fence<32>(hc);
            prof(30);
            if (!mainf) {
                #pragma unroll
                for (int i = 0; i < 16; i++) {
                    const uint32_t t = pack_bf16(hc[2 * i], hc[2 * i + 1]);
                    hc[2 * i] = bf_lo(sv[i]); hc[2 * i + 1] = bf_hi(sv[i]);
                    sv[i] = t;
                }
            }
            if (do_f) store_out(eoff);
        }
        prof(40);
        if (t2_ == 0) g_epoch[b2_] = v_epoch() + 1;
    }
}

typedef CUresult (*EncodeFn)(CUtensorMap*, CUtensorMapDataType, cuuint32_t, void*, const cuuint64_t*, const cuuint64_t*,
                             const cuuint32_t*, const cuuint32_t*, CUtensorMapInterleave, CUtensorMapSwizzle,
                             CUtensorMapL2promotion, CUtensorMapFloatOOBfill);

void make_map(EncodeFn enc, CUtensorMap* tm, const void* base, int rows, int cols, int box_rows, int box_cols = 64) {
    cuuint64_t gdim[2] = {(cuuint64_t)cols, (cuuint64_t)rows};
    cuuint64_t gstr[1] = {(cuuint64_t)cols * 2};
    cuuint32_t box[2] = {(cuuint32_t)box_cols, (cuuint32_t)box_rows};
    cuuint32_t estr[2] = {1, 1};
    enc(tm, CU_TENSOR_MAP_DATA_TYPE_BFLOAT16, 2, const_cast<void*>(base), gdim, gstr, box, estr, CU_TENSOR_MAP_INTERLEAVE_NONE,
        CU_TENSOR_MAP_SWIZZLE_128B, CU_TENSOR_MAP_L2_PROMOTION_L2_128B, CU_TENSOR_MAP_FLOAT_OOB_FILL_NONE);
}

}

extern "C" void kernel_launch(void* const* d_in, const int* in_sizes, int n_in, void* d_out, int out_size) {
    static EncodeFn enc = nullptr;
    static void* o_ptr = nullptr;
    if (!enc) {
        void* fn = nullptr;
        cudaDriverEntryPointQueryResult qr;
        cudaGetDriverEntryPoint("cuTensorMapEncodeTiled", &fn, cudaEnableDefault, &qr);
        enc = (EncodeFn)fn;
        cudaGetSymbolAddress(&o_ptr, g_o);
        cudaFuncSetAttribute(fused_kernel, cudaFuncAttributeMaxDynamicSharedMemorySize, SMEM_BYTES);
    }
    Params p;
    p.x = (const __nv_bfloat16*)d_in[0];
    p.wqkv = (const __nv_bfloat16*)d_in[1];
    p.wo = (const __nv_bfloat16*)d_in[2];
    p.w1 = (const __nv_bfloat16*)d_in[4];
    p.b1 = (const __nv_bfloat16*)d_in[5];
    p.w2 = (const __nv_bfloat16*)d_in[6];
    p.b2 = (const __nv_bfloat16*)d_in[7];
    p.out = (__nv_bfloat16*)d_out;
    CUtensorMap tm_x, tm_w1, tm_w2, tm_wo, tm_o, tm_qkv, tm_qkve;
    make_map(enc, &tm_qkv, p.wqkv, DM, 3 * DM, 96);
    make_map(enc, &tm_qkve, p.wqkv, DM, 3 * DM, 96, 8);
    make_map(enc, &tm_x, p.x, SEQ, DM, 128);
    make_map(enc, &tm_w1, p.w1, DM, FF, 192);
    make_map(enc, &tm_w2, p.w2, FF, DM, 192);
    make_map(enc, &tm_wo, p.wo, DM, DM, 192);
    make_map(enc, &tm_o, o_ptr, SEQ, DM, 128);
    fused_kernel<<<NMAIN + NAUX, 384, SMEM_BYTES>>>(tm_x, tm_w1, tm_w2, tm_wo, tm_o, tm_qkv, tm_qkve, p);
}
```

```cpp
#include <cuda_runtime.h>
#include <cuda.h>
#include <cuda_bf16.h>
#include <stdint.h>

#define OSTEP_AT 4
#define KNOB_A 1
#define KNOB_B 0
#define PF1_NS 1000
#define PF2_NS 2000
#define PFIDX 3
#define PF3_NS 800
#define YF32 0

namespace {
constexpr int WAIT_ITERS = 3000000;

constexpr int SEQ = 2048, DM = 576, FF = 4608;
constexpr int NMAIN = 128, NAUX = 4;

constexpr uint32_t SB    = 0x400;
constexpr uint32_t HA    = SB;
constexpr uint32_t XB    = SB + 131072;
constexpr uint32_t RING  = SB + 147456;
constexpr uint32_t SLOT  = 24576;
constexpr uint32_t MISC  = SB + 221184;
constexpr uint32_t BARS  = MISC;
constexpr uint32_t B1S   = MISC + 512;
constexpr uint32_t B2S   = MISC + 2816;
constexpr uint32_t EPO   = MISC + 3072;
constexpr uint32_t EVC   = MISC + 3104;
constexpr uint32_t SMEM_BYTES = 221184 + 3200 + 512;
constexpr uint32_t PKT   = HA + 32768;
constexpr uint32_t VT    = HA + 51200;
constexpr uint32_t PQT   = HA + 98304;
constexpr uint32_t KVB   = HA + 116736;

enum { B_FULL = 0, B_EMPTY = 3, B_XFULL = 6, B_OFULL = 9, B_OFREE = 12  , B_KVB = 16, B_YRDY = 17, B_COUNT = 18 };
__device__ __forceinline__ constexpr uint32_t bar(int i) { return BARS + 8u * i; }

constexpr int YT_BYTES = YF32 ? 32768 : 16384;
__device__ __align__(1024) __nv_bfloat16 g_o[SEQ * DM];
__device__ __align__(1024) unsigned char g_yacc[2 * 16 * 9 * YT_BYTES];
__device__ __align__(128) float g_kv[2 * 8 * 72 * 20];
__device__ __align__(128) unsigned int g_cnt[(8 + 16 + 16 * 9) * 8];
__device__ unsigned int g_epoch[NMAIN + NAUX];
__device__ __forceinline__ unsigned int* cnt_kv(int j) { return g_cnt + j * 8; }
__device__ __forceinline__ unsigned int* cnt_o(int m) { return g_cnt + (8 + m) * 8; }
__device__ __forceinline__ unsigned int* cnt_y(int m, int c) { return g_cnt + (24 + m * 9 + c) * 8; }

__device__ __forceinline__ void mbar_init(uint32_t b, uint32_t cnt) { asm volatile("mbarrier.init.shared::cta.b64 [%0], %1;" :: "r"(b), "r"(cnt)); }
__device__ __forceinline__ void mbar_expect_tx(uint32_t b, uint32_t bytes) { asm volatile("mbarrier.arrive.expect_tx.shared::cta.b64 _, [%0], %1;" :: "r"(b), "r"(bytes) : "memory"); }
__device__ __forceinline__ void mbar_arrive(uint32_t b) { asm volatile("mbarrier.arrive.shared::cta.b64 _, [%0];" :: "r"(b) : "memory"); }
__device__ __forceinline__ void prof(int) {}
__device__ __forceinline__ void mbar_wait(uint32_t b, uint32_t parity) {
    asm volatile("{\n.reg .pred p;\n.reg .u32 c;\nmov.u32 c, 0;\n"
                 "WAIT_LOOP:\nmbarrier.try_wait.parity.shared::cta.b64 p, [%0], %1;\n@p bra WAIT_DONE;\n"
                 "add.u32 c, c, 1;\nsetp.lt.u32 p, c, 4000000;\n@p bra WAIT_LOOP;\ntrap;\nWAIT_DONE:\n}"
                 :: "r"(b), "r"(parity) : "memory");
}
__device__ __forceinline__ void tma_2d(uint32_t dst, const CUtensorMap* tm, uint32_t b, int c0, int c1) {
    asm volatile("cp.async.bulk.tensor.2d.shared::cluster.global.mbarrier::complete_tx::bytes [%0], [%1, {%3, %4}], [%2];"
                 :: "r"(dst), "l"(tm), "r"(b), "r"(c0), "r"(c1) : "memory");
}
__device__ __forceinline__ void fence_async_smem() { asm volatile("fence.proxy.async.shared::cta;" ::: "memory"); }
__device__ __forceinline__ void fence_async_all() { asm volatile("fence.proxy.async;" ::: "memory"); }
__device__ __forceinline__ void named_bar(int id, int n) { asm volatile("bar.sync %0, %1;" :: "r"(id), "r"(n) : "memory"); }
__device__ __forceinline__ void wg_fence() { asm volatile("wgmma.fence.sync.aligned;" ::: "memory"); }
__device__ __forceinline__ void wg_commit() { asm volatile("wgmma.commit_group.sync.aligned;" ::: "memory"); }
template<int N> __device__ __forceinline__ void wg_wait() { asm volatile("wgmma.wait_group.sync.aligned %0;" :: "n"(N) : "memory"); }
template<int N> __device__ __forceinline__ void reg_fence(float* d) {
    #pragma unroll
    for (int i = 0; i < N; i++) asm volatile("" : "+f"(d[i]) :: "memory");
}
template<int N> __device__ __forceinline__ void reg_copy(float* d, const float* s) {
    #pragma unroll
    for (int i = 0; i < N; i++) asm volatile("mov.b32 %0, %1;" : "=f"(d[i]) : "f"(s[i]));
}
__device__ __forceinline__ uint32_t pack_bf16(float lo, float hi) { uint32_t r; asm("cvt.rn.bf16x2.f32 %0, %1, %2;" : "=r"(r) : "f"(hi), "f"(lo)); return r; }
__device__ __forceinline__ float bf_lo(uint32_t v) { return __uint_as_float(v << 16); }
__device__ __forceinline__ float bf_hi(uint32_t v) { return __uint_as_float(v & 0xffff0000u); }
__device__ __forceinline__ uint32_t sub_bf16x2(uint32_t a, uint32_t b) { uint32_t r; asm("sub.rn.bf16x2 %0, %1, %2;" : "=r"(r) : "r"(a), "r"(b)); return r; }
__device__ __forceinline__ float ex2(float x) { float r; asm("ex2.approx.ftz.f32 %0, %1;" : "=f"(r) : "f"(x)); return r; }
__device__ __forceinline__ float rcp(float x) { float r; asm("rcp.approx.ftz.f32 %0, %1;" : "=f"(r) : "f"(x)); return r; }
__device__ __forceinline__ float tanh_ap(float x) { float r; asm("tanh.approx.f32 %0, %1;" : "=f"(r) : "f"(x)); return r; }
__device__ __forceinline__ void sts32(uint32_t a, uint32_t v) { asm volatile("st.shared.b32 [%0], %1;" :: "r"(a), "r"(v)); }
__device__ __forceinline__ void sts128(uint32_t a, uint32_t x, uint32_t y, uint32_t z, uint32_t w) { asm volatile("st.shared.v4.b32 [%0], {%1,%2,%3,%4};" :: "r"(a), "r"(x), "r"(y), "r"(z), "r"(w)); }
__device__ __forceinline__ void sts64(uint32_t a, uint32_t x, uint32_t y) { asm volatile("st.shared.v2.b32 [%0], {%1,%2};" :: "r"(a), "r"(x), "r"(y)); }
__device__ __forceinline__ void lds64(uint32_t a, uint32_t* v) { asm volatile("ld.shared.v2.b32 {%0,%1}, [%2];" : "=r"(v[0]), "=r"(v[1]) : "r"(a)); }
__device__ __forceinline__ void lds128(uint32_t a, uint32_t* v) { asm volatile("ld.shared.v4.b32 {%0,%1,%2,%3}, [%4];" : "=r"(v[0]), "=r"(v[1]), "=r"(v[2]), "=r"(v[3]) : "r"(a) : "memory"); }
__device__ __forceinline__ float2 lds64f(uint32_t a) { float2 v; asm("ld.shared.v2.f32 {%0,%1}, [%2];" : "=f"(v.x), "=f"(v.y) : "r"(a)); return v; }
__device__ __forceinline__ void ldsm4(uint32_t a, uint32_t* v) {
    asm volatile("ldmatrix.sync.aligned.m8n8.x4.shared.b16 {%0,%1,%2,%3}, [%4];" : "=r"(v[0]), "=r"(v[1]), "=r"(v[2]), "=r"(v[3]) : "r"(a));
}
__device__ __forceinline__ void mma_ones(float* c, const uint32_t* a) {
    const uint32_t one2 = 0x3F803F80u;
    asm volatile("mma.sync.aligned.m16n8k16.row.col.f32.bf16.bf16.f32 {%0,%1,%2,%3}, {%4,%5,%6,%7}, {%8,%8}, {%0,%1,%2,%3};"
                 : "+f"(c[0]), "+f"(c[1]), "+f"(c[2]), "+f"(c[3]) : "r"(a[0]), "r"(a[1]), "r"(a[2]), "r"(a[3]), "r"(one2));
}
__device__ __forceinline__ unsigned int ld_acquire(const unsigned int* p) { unsigned int v; asm volatile("ld.acquire.gpu.global.u32 %0, [%1];" : "=r"(v) : "l"(p) : "memory"); return v; }
__device__ __forceinline__ void wait_cnt(const unsigned int* p, unsigned int target) {
    for (int i = 0; i < WAIT_ITERS; i++) {
        if ((int)(ld_acquire(p) - target) >= 0) return;
        __nanosleep(40);
    }
    __trap();
}
__device__ __forceinline__ uint32_t v_tid() { uint32_t r; asm volatile("mov.u32 %0, %%tid.x;" : "=r"(r)); return r; }
__device__ __forceinline__ uint32_t v_bid() { uint32_t r; asm volatile("mov.u32 %0, %%ctaid.x;" : "=r"(r)); return r; }
__device__ __forceinline__ uint32_t v_epoch() { uint32_t r; asm volatile("ld.shared.u32 %0, [%1];" : "=r"(r) : "r"(EPO)); return r; }
__device__ __forceinline__ void prefetch_l2(const void* p) { asm volatile("prefetch.global.L2 [%0];" :: "l"(p)); }

__host__ __device__ constexpr uint64_t mkdesc(uint32_t addr, uint32_t lbo, uint32_t sbo, uint32_t swz) {
    return (uint64_t)((addr & 0x3FFFF) >> 4) | ((uint64_t)((lbo >> 4) & 0x3FFF) << 16) | ((uint64_t)((sbo >> 4) & 0x3FFF) << 32) | ((uint64_t)swz << 62);
}

template<int SD> __device__ __forceinline__ void wg_rs64(float* d, const uint32_t* a, uint64_t bd) {
  if constexpr (SD) {
    asm volatile("{\n.reg .pred p;\nsetp.eq.b32 p, 0, 0;\n"
    "wgmma.mma_async.sync.aligned.m64n64k16.f32.bf16.bf16 {%0,%1,%2,%3,%4,%5,%6,%7,%8,%9,%10,%11,%12,%13,%14,%15,%16,%17,%18,%19,%20,%21,%22,%23,%24,%25,%26,%27,%28,%29,%30,%31}, {%32,%33,%34,%35}, %36, p, 1, 1, 1;\n}"
    : "+f"(d[0]),"+f"(d[1]),"+f"(d[2]),"+f"(d[3]),"+f"(d[4]),"+f"(d[5]),"+f"(d[6]),"+f"(d[7]),"+f"(d[8]),"+f"(d[9]),"+f"(d[10]),"+f"(d[11]),"+f"(d[12]),"+f"(d[13]),"+f"(d[14]),"+f"(d[15]),"+f"(d[16]),"+f"(d[17]),"+f"(d[18]),"+f"(d[19]),"+f"(d[20]),"+f"(d[21]),"+f"(d[22]),"+f"(d[23]),"+f"(d[24]),"+f"(d[25]),"+f"(d[26]),"+f"(d[27]),"+f"(d[28]),"+f"(d[29]),"+f"(d[30]),"+f"(d[31])
    : "r"(a[0]),"r"(a[1]),"r"(a[2]),"r"(a[3]), "l"(bd));
  } else {
    asm volatile("{\n.reg .pred p;\nsetp.ne.b32 p, 0, 0;\n"
    "wgmma.mma_async.sync.aligned.m64n64k16.f32.bf16.bf16 {%0,%1,%2,%3,%4,%5,%6,%7,%8,%9,%10,%11,%12,%13,%14,%15,%16,%17,%18,%19,%20,%21,%22,%23,%24,%25,%26,%27,%28,%29,%30,%31}, {%32,%33,%34,%35}, %36, p, 1, 1, 1;\n}"
    : "+f"(d[0]),"+f"(d[1]),"+f"(d[2]),"+f"(d[3]),"+f"(d[4]),"+f"(d[5]),"+f"(d[6]),"+f"(d[7]),"+f"(d[8]),"+f"(d[9]),"+f"(d[10]),"+f"(d[11]),"+f"(d[12]),"+f"(d[13]),"+f"(d[14]),"+f"(d[15]),"+f"(d[16]),"+f"(d[17]),"+f"(d[18]),"+f"(d[19]),"+f"(d[20]),"+f"(d[21]),"+f"(d[22]),"+f"(d[23]),"+f"(d[24]),"+f"(d[25]),"+f"(d[26]),"+f"(d[27]),"+f"(d[28]),"+f"(d[29]),"+f"(d[30]),"+f"(d[31])
    : "r"(a[0]),"r"(a[1]),"r"(a[2]),"r"(a[3]), "l"(bd));
  }
}
template<int SD> __device__ __forceinline__ void wg_ss64(float* d, uint64_t ad, uint64_t bd) {
  if constexpr (SD) {
    asm volatile("{\n.reg .pred p;\nsetp.eq.b32 p, 0, 0;\n"
    "wgmma.mma_async.sync.aligned.m64n64k16.f32.bf16.bf16 {%0,%1,%2,%3,%4,%5,%6,%7,%8,%9,%10,%11,%12,%13,%14,%15,%16,%17,%18,%19,%20,%21,%22,%23,%24,%25,%26,%27,%28,%29,%30,%31}, %32, %33, p, 1, 1, 0, 1;\n}"
    : "+f"(d[0]),"+f"(d[1]),"+f"(d[2]),"+f"(d[3]),"+f"(d[4]),"+f"(d[5]),"+f"(d[6]),"+f"(d[7]),"+f"(d[8]),"+f"(d[9]),"+f"(d[10]),"+f"(d[11]),"+f"(d[12]),"+f"(d[13]),"+f"(d[14]),"+f"(d[15]),"+f"(d[16]),"+f"(d[17]),"+f"(d[18]),"+f"(d[19]),"+f"(d[20]),"+f"(d[21]),"+f"(d[22]),"+f"(d[23]),"+f"(d[24]),"+f"(d[25]),"+f"(d[26]),"+f"(d[27]),"+f"(d[28]),"+f"(d[29]),"+f"(d[30]),"+f"(d[31])
    : "l"(ad), "l"(bd));
  } else {
    asm volatile("{\n.reg .pred p;\nsetp.ne.b32 p, 0, 0;\n"
    "wgmma.mma_async.sync.aligned.m64n64k16.f32.bf16.bf16 {%0,%1,%2,%3,%4,%5,%6,%7,%8,%9,%10,%11,%12,%13,%14,%15,%16,%17,%18,%19,%20,%21,%22,%23,%24,%25,%26,%27,%28,%29,%30,%31}, %32, %33, p, 1, 1, 0, 1;\n}"
    : "+f"(d[0]),"+f"(d[1]),"+f"(d[2]),"+f"(d[3]),"+f"(d[4]),"+f"(d[5]),"+f"(d[6]),"+f"(d[7]),"+f"(d[8]),"+f"(d[9]),"+f"(d[10]),"+f"(d[11]),"+f"(d[12]),"+f"(d[13]),"+f"(d[14]),"+f"(d[15]),"+f"(d[16]),"+f"(d[17]),"+f"(d[18]),"+f"(d[19]),"+f"(d[20]),"+f"(d[21]),"+f"(d[22]),"+f"(d[23]),"+f"(d[24]),"+f"(d[25]),"+f"(d[26]),"+f"(d[27]),"+f"(d[28]),"+f"(d[29]),"+f"(d[30]),"+f"(d[31])
    : "l"(ad), "l"(bd));
  }
}
template<int SD> __device__ __forceinline__ void wg_rs72(float* d, const uint32_t* a, uint64_t bd) {
  if constexpr (SD) {
    asm volatile("{\n.reg .pred p;\nsetp.eq.b32 p, 0, 0;\n"
    "wgmma.mma_async.sync.aligned.m64n72k16.f32.bf16.bf16 {%0,%1,%2,%3,%4,%5,%6,%7,%8,%9,%10,%11,%12,%13,%14,%15,%16,%17,%18,%19,%20,%21,%22,%23,%24,%25,%26,%27,%28,%29,%30,%31,%32,%33,%34,%35}, {%36,%37,%38,%39}, %40, p, 1, 1, 1;\n}"
    : "+f"(d[0]),"+f"(d[1]),"+f"(d[2]),"+f"(d[3]),"+f"(d[4]),"+f"(d[5]),"+f"(d[6]),"+f"(d[7]),"+f"(d[8]),"+f"(d[9]),"+f"(d[10]),"+f"(d[11]),"+f"(d[12]),"+f"(d[13]),"+f"(d[14]),"+f"(d[15]),"+f"(d[16]),"+f"(d[17]),"+f"(d[18]),"+f"(d[19]),"+f"(d[20]),"+f"(d[21]),"+f"(d[22]),"+f"(d[23]),"+f"(d[24]),"+f"(d[25]),"+f"(d[26]),"+f"(d[27]),"+f"(d[28]),"+f"(d[29]),"+f"(d[30]),"+f"(d[31]),"+f"(d[32]),"+f"(d[33]),"+f"(d[34]),"+f"(d[35])
    : "r"(a[0]),"r"(a[1]),"r"(a[2]),"r"(a[3]), "l"(bd));
  } else {
    asm volatile("{\n.reg .pred p;\nsetp.ne.b32 p, 0, 0;\n"
    "wgmma.mma_async.sync.aligned.m64n72k16.f32.bf16.bf16 {%0,%1,%2,%3,%4,%5,%6,%7,%8,%9,%10,%11,%12,%13,%14,%15,%16,%17,%18,%19,%20,%21,%22,%23,%24,%25,%26,%27,%28,%29,%30,%31,%32,%33,%34,%35}, {%36,%37,%38,%39}, %40, p, 1, 1, 1;\n}"
    : "+f"(d[0]),"+f"(d[1]),"+f"(d[2]),"+f"(d[3]),"+f"(d[4]),"+f"(d[5]),"+f"(d[6]),"+f"(d[7]),"+f"(d[8]),"+f"(d[9]),"+f"(d[10]),"+f"(d[11]),"+f"(d[12]),"+f"(d[13]),"+f"(d[14]),"+f"(d[15]),"+f"(d[16]),"+f"(d[17]),"+f"(d[18]),"+f"(d[19]),"+f"(d[20]),"+f"(d[21]),"+f"(d[22]),"+f"(d[23]),"+f"(d[24]),"+f"(d[25]),"+f"(d[26]),"+f"(d[27]),"+f"(d[28]),"+f"(d[29]),"+f"(d[30]),"+f"(d[31]),"+f"(d[32]),"+f"(d[33]),"+f"(d[34]),"+f"(d[35])
    : "r"(a[0]),"r"(a[1]),"r"(a[2]),"r"(a[3]), "l"(bd));
  }
}
template<int SD> __device__ __forceinline__ void wg_ss72(float* d, uint64_t ad, uint64_t bd) {
  if constexpr (SD) {
    asm volatile("{\n.reg .pred p;\nsetp.eq.b32 p, 0, 0;\n"
    "wgmma.mma_async.sync.aligned.m64n72k16.f32.bf16.bf16 {%0,%1,%2,%3,%4,%5,%6,%7,%8,%9,%10,%11,%12,%13,%14,%15,%16,%17,%18,%19,%20,%21,%22,%23,%24,%25,%26,%27,%28,%29,%30,%31,%32,%33,%34,%35}, %36, %37, p, 1, 1, 0, 1;\n}"
    : "+f"(d[0]),"+f"(d[1]),"+f"(d[2]),"+f"(d[3]),"+f"(d[4]),"+f"(d[5]),"+f"(d[6]),"+f"(d[7]),"+f"(d[8]),"+f"(d[9]),"+f"(d[10]),"+f"(d[11]),"+f"(d[12]),"+f"(d[13]),"+f"(d[14]),"+f"(d[15]),"+f"(d[16]),"+f"(d[17]),"+f"(d[18]),"+f"(d[19]),"+f"(d[20]),"+f"(d[21]),"+f"(d[22]),"+f"(d[23]),"+f"(d[24]),"+f"(d[25]),"+f"(d[26]),"+f"(d[27]),"+f"(d[28]),"+f"(d[29]),"+f"(d[30]),"+f"(d[31]),"+f"(d[32]),"+f"(d[33]),"+f"(d[34]),"+f"(d[35])
    : "l"(ad), "l"(bd));
  } else {
    asm volatile("{\n.reg .pred p;\nsetp.ne.b32 p, 0, 0;\n"
    "wgmma.mma_async.sync.aligned.m64n72k16.f32.bf16.bf16 {%0,%1,%2,%3,%4,%5,%6,%7,%8,%9,%10,%11,%12,%13,%14,%15,%16,%17,%18,%19,%20,%21,%22,%23,%24,%25,%26,%27,%28,%29,%30,%31,%32,%33,%34,%35}, %36, %37, p, 1, 1, 0, 1;\n}"
    : "+f"(d[0]),"+f"(d[1]),"+f"(d[2]),"+f"(d[3]),"+f"(d[4]),"+f"(d[5]),"+f"(d[6]),"+f"(d[7]),"+f"(d[8]),"+f"(d[9]),"+f"(d[10]),"+f"(d[11]),"+f"(d[12]),"+f"(d[13]),"+f"(d[14]),"+f"(d[15]),"+f"(d[16]),"+f"(d[17]),"+f"(d[18]),"+f"(d[19]),"+f"(d[20]),"+f"(d[21]),"+f"(d[22]),"+f"(d[23]),"+f"(d[24]),"+f"(d[25]),"+f"(d[26]),"+f"(d[27]),"+f"(d[28]),"+f"(d[29]),"+f"(d[30]),"+f"(d[31]),"+f"(d[32]),"+f"(d[33]),"+f"(d[34]),"+f"(d[35])
    : "l"(ad), "l"(bd));
  }
}
template<int SD> __device__ __forceinline__ void wg_tt64(float* d, uint64_t ad, uint64_t bd) {
  if constexpr (SD) {
    asm volatile("{\n.reg .pred p;\nsetp.eq.b32 p, 0, 0;\n"
    "wgmma.mma_async.sync.aligned.m64n64k16.f32.bf16.bf16 {%0,%1,%2,%3,%4,%5,%6,%7,%8,%9,%10,%11,%12,%13,%14,%15,%16,%17,%18,%19,%20,%21,%22,%23,%24,%25,%26,%27,%28,%29,%30,%31}, %32, %33, p, 1, 1, 1, 1;\n}"
    : "+f"(d[0]),"+f"(d[1]),"+f"(d[2]),"+f"(d[3]),"+f"(d[4]),"+f"(d[5]),"+f"(d[6]),"+f"(d[7]),"+f"(d[8]),"+f"(d[9]),"+f"(d[10]),"+f"(d[11]),"+f"(d[12]),"+f"(d[13]),"+f"(d[14]),"+f"(d[15]),"+f"(d[16]),"+f"(d[17]),"+f"(d[18]),"+f"(d[19]),"+f"(d[20]),"+f"(d[21]),"+f"(d[22]),"+f"(d[23]),"+f"(d[24]),"+f"(d[25]),"+f"(d[26]),"+f"(d[27]),"+f"(d[28]),"+f"(d[29]),"+f"(d[30]),"+f"(d[31])
    : "l"(ad), "l"(bd));
  } else {
    asm volatile("{\n.reg .pred p;\nsetp.ne.b32 p, 0, 0;\n"
    "wgmma.mma_async.sync.aligned.m64n64k16.f32.bf16.bf16 {%0,%1,%2,%3,%4,%5,%6,%7,%8,%9,%10,%11,%12,%13,%14,%15,%16,%17,%18,%19,%20,%21,%22,%23,%24,%25,%26,%27,%28,%29,%30,%31}, %32, %33, p, 1, 1, 1, 1;\n}"
    : "+f"(d[0]),"+f"(d[1]),"+f"(d[2]),"+f"(d[3]),"+f"(d[4]),"+f"(d[5]),"+f"(d[6]),"+f"(d[7]),"+f"(d[8]),"+f"(d[9]),"+f"(d[10]),"+f"(d[11]),"+f"(d[12]),"+f"(d[13]),"+f"(d[14]),"+f"(d[15]),"+f"(d[16]),"+f"(d[17]),"+f"(d[18]),"+f"(d[19]),"+f"(d[20]),"+f"(d[21]),"+f"(d[22]),"+f"(d[23]),"+f"(d[24]),"+f"(d[25]),"+f"(d[26]),"+f"(d[27]),"+f"(d[28]),"+f"(d[29]),"+f"(d[30]),"+f"(d[31])
    : "l"(ad), "l"(bd));
  }
}

template<int V> struct IC { static constexpr int v = V; };
template<int I, int N, class F> __device__ __forceinline__ void sfor(F&& f) {
    if constexpr (I < N) { f(IC<I>{}); sfor<I + 1, N>(f); }
}

enum { K_QKV = 0, K_H = 1 };

struct Ctx {
    uint32_t tph;
    uint32_t tid;
    bool pf = false;
};
__device__ __forceinline__ void release_slot(const Ctx& c, int slot) { if ((c.tid & 31) == 0) mbar_arrive(bar(B_EMPTY + slot)); }

__device__ __forceinline__ void turn_wait(const Ctx& c) { asm volatile("bar.sync %0, 256;" :: "r"(4 + (c.tid >> 7)) : "memory"); }
__device__ __forceinline__ void turn_pass(const Ctx& c) { asm volatile("bar.arrive %0, 256;" :: "r"(5 - (c.tid >> 7)) : "memory"); }

template<int KIND, class PART, class POST>
__device__ __forceinline__ void run_step(Ctx& c, float* acc, const uint32_t* a, PART&& part, POST&& post) {
    constexpr int NST = (KIND == K_QKV) ? 6 : 3;
    constexpr int KPS = 36 / NST;
    sfor<0, NST>([&](auto ST) {
        constexpr int st = decltype(ST)::v;
        constexpr int slot = st % 3;
        mbar_wait(bar(B_FULL + slot), c.tph);
        uint32_t wgo = 0;
        if constexpr (st == NST - 1) wgo = (c.tid >> 7) * 512;
        if (KIND == K_H && c.pf) prof(44 + st * 5);
        turn_wait(c);
        if (KIND == K_H && c.pf) prof(45 + st * 5);
        wg_fence();
        sfor<0, KPS>([&](auto KK) {
            constexpr int kk = decltype(KK)::v;
            constexpr int ks = st * KPS + kk;
            constexpr int SD = ks ? 1 : 0;
            if constexpr (KIND == K_QKV) {
                constexpr uint64_t bd = mkdesc(RING + slot * SLOT + kk * 2048, 12288, 1024, 1);
                if constexpr (ks < 32) wg_rs72<SD>(acc, a + ks * 4, bd);
                else wg_ss72<SD>(acc, mkdesc(XB + (ks - 32) * 32, 16, 1024, 1) + wgo, bd);
            } else {
                constexpr uint64_t bd = mkdesc(RING + slot * SLOT + kk * 2048, 16, 1024, 1);
                if constexpr (ks < 32) wg_rs64<SD>(acc, a + ks * 4, bd);
                else wg_ss64<SD>(acc, mkdesc(XB + (ks - 32) * 32, 16, 1024, 1) + wgo, bd);
            }
        });
        wg_commit();
        turn_pass(c);
        if (KIND == K_H && c.pf) prof(46 + st * 5);
        part(ST);
        if (KIND == K_H && c.pf) prof(47 + st * 5);
        wg_wait<0>();
        if (KIND == K_H && c.pf) prof(48 + st * 5);
        release_slot(c, slot);
        if constexpr (slot == 2) c.tph ^= 1;
        post(ST);
    });
    if constexpr (KIND == K_QKV) reg_fence<36>(acc); else reg_fence<32>(acc);
}

__device__ __forceinline__ float phi(float t) {
    float e = ex2(t * 1.4426950408889634f);
    return (t > 0.f ? t + 1.0f : e) + 1e-6f;
}
__device__ __forceinline__ float gelu_h(float hx) {
    float u = hx * fmaf(hx * hx, 0.2854192650f, 1.5957691216f);
    return fmaf(hx, tanh_ap(u), hx);
}

struct Params {
    const __nv_bfloat16* x;
    const __nv_bfloat16* wqkv;
    const __nv_bfloat16* wo;
    const __nv_bfloat16* w1;
    const __nv_bfloat16* b1;
    const __nv_bfloat16* w2;
    const __nv_bfloat16* b2;
    __nv_bfloat16* out;
};

__global__ void __launch_bounds__(384, 1)
fused_kernel(const __grid_constant__ CUtensorMap tm_x, const __grid_constant__ CUtensorMap tm_w1,
             const __grid_constant__ CUtensorMap tm_w2, const __grid_constant__ CUtensorMap tm_wo,
             const __grid_constant__ CUtensorMap tm_o, const __grid_constant__ CUtensorMap tm_qkv,
             const __grid_constant__ CUtensorMap tm_qkve, const Params p) {
    extern __shared__ __align__(1024) unsigned char smem_raw[];
    const int tid = threadIdx.x;
    const int bid = blockIdx.x;
    const bool is_main = bid < NMAIN;
    const int j = bid & 7;
    const int m = bid >> 3;

    if (tid == 0) {
        if ((uint32_t)__cvta_generic_to_shared(smem_raw) != SB) __trap();
        for (int i = 0; i < 3; i++) {
            mbar_init(bar(B_FULL + i), 1); mbar_init(bar(B_EMPTY + i), 8);
            mbar_init(bar(B_XFULL + i), 1); mbar_init(bar(B_OFULL + i), 1);
        }
        mbar_init(bar(B_KVB), is_main ? 2 : 8); mbar_init(bar(B_YRDY), 1);
        for (int i = 0; i < 4; i++) mbar_init(bar(B_OFREE + i), 8);
        asm volatile("fence.mbarrier_init.release.cluster;" ::: "memory");
        if (is_main) {
            for (int g = 0; g < 3; g++) {
                mbar_expect_tx(bar(B_XFULL + g), 49152);
                for (int kb = 3 * g; kb < 3 * g + 3; kb++) tma_2d(HA + kb * 16384, &tm_x, bar(B_XFULL + g), kb * 64, m * 128);
            }
            for (int st = 0; st < 3; st++) {
                mbar_expect_tx(bar(B_FULL + st), 96 * 144);
                tma_2d(RING + st * SLOT, &tm_qkv, bar(B_FULL + st), 576 + j * 72, st * 96);
                tma_2d(RING + st * SLOT + 12288, &tm_qkve, bar(B_FULL + st), 576 + j * 72 + 64, st * 96);
            }
        }
    }
    if (tid == 32) sts32(EPO, g_epoch[bid]);
    if (tid >= 40 && tid < 48) sts32(EVC + (tid - 40) * 4, 0);
    if (tid >= 64 && tid < 64 + 288 && is_main) {
        int i = tid - 64;
        uint32_t v = *reinterpret_cast<const uint32_t*>(p.b1 + j * 576 + 2 * i);
        sts32(B1S + 8 * i, __float_as_uint(0.5f * bf_lo(v))); sts32(B1S + 8 * i + 4, __float_as_uint(0.5f * bf_hi(v)));
    }
    if (tid >= 352) {
        int i = tid - 352;
        uint32_t v = *reinterpret_cast<const uint32_t*>(p.b2 + (is_main ? j : 8) * 64 + 2 * i);
        sts32(B2S + 8 * i, v << 16); sts32(B2S + 8 * i + 4, v & 0xffff0000u);
    }
    fence_async_smem();
    __syncthreads();
    uint32_t epoch;
    asm volatile("ld.shared.u32 %0, [%1];" : "=r"(epoch) : "r"(EPO));
    const uint32_t par = epoch & 1;

    if (tid >= 256) {
        asm volatile("setmaxnreg.dec.sync.aligned.u32 24;");
        const int hw = (tid >> 5) - 8, lane = tid & 31;
        if (hw == 0) {
            if (lane == 0) {
                uint32_t n = 0;
                if (is_main) {
                    n = 1;
                    #pragma unroll 1
                    for (int u = 3; u < 18; u++) {
                        const int st = u % 3, step = u / 6;
                        const int col = ((step == 2) ? 0 : (step + 1) * 576) + j * 72, row = (u % 6) * 96;
                        mbar_wait(bar(B_EMPTY + st), (n & 1) ^ 1);
                        mbar_expect_tx(bar(B_FULL + st), 96 * 144);
                        tma_2d(RING + st * SLOT, &tm_qkv, bar(B_FULL + st), col, row);
                        tma_2d(RING + st * SLOT + 12288, &tm_qkve, bar(B_FULL + st), col + 64, row);
                        if (st == 2) n++;
                    }
                }
                const int nsteps = is_main ? 19 : 4;
                #pragma unroll 1
                for (int s = 0; s < nsteps; s++, n++) {
                    const CUtensorMap* tm; int col, row;
                    if (!is_main) { tm = &tm_wo; col = 512; row = 0; }
                    else if (s < 9) { tm = &tm_w1; col = j * 576 + s * 64; row = 0; }
                    else if (s < 18) { tm = &tm_w2; col = (s == 9) ? 512 : (((j + s - 9) & 7) * 64); row = j * 576; }
                    else { tm = &tm_wo; col = j * 64; row = 0; }
                    #pragma unroll 1
                    for (int st = 0; st < 3; st++) {
                        mbar_wait(bar(B_EMPTY + st), (n & 1) ^ 1);
                        mbar_expect_tx(bar(B_FULL + st), SLOT);
                        tma_2d(RING + st * SLOT, tm, bar(B_FULL + st), col, row + st * 192);
                    }
                }
            }
        } else {
            if (is_main) {
                const int t = tid - 288;
                #pragma unroll 1
                for (int i = t; i < 36 * 6; i += 96) {
                    int r = i / 6, q = i - r * 6;
                    prefetch_l2(reinterpret_cast<const char*>(p.wqkv) + (36 * m + r) * 3456 + (q >> 1) * 1152 + j * 144 + (q & 1) * 128);
                }
                __nanosleep(PF1_NS);
                #pragma unroll 1
                for (int i = t; i < 36 * 9; i += 96) {
                    int r = i / 9, q = i - r * 9;
                    prefetch_l2(reinterpret_cast<const char*>(p.w1) + (36 * m + r) * 9216 + j * 1152 + q * 128);
                    __nanosleep(PF3_NS);
                }
                __nanosleep(PF2_NS);
                #pragma unroll 1
                for (int i = t; i < 36 * 9; i += 96)
                    prefetch_l2(reinterpret_cast<const char*>(p.w2) + (576 * j + 36 * m) * 1152 + i * 128);
                if (t < 41 && (bid * 41 + t) < 5184) prefetch_l2(reinterpret_cast<const char*>(p.wo) + (bid * 41 + t) * 128);
                if (hw != 2) {
                    if (lane == 0) wait_cnt(cnt_kv(j), (epoch + 1) * 16);
                    __syncwarp();
                    const float4* kv = reinterpret_cast<const float4*>(g_kv + (par * 8 + j) * 1440);
                    #pragma unroll 2
                    for (int i = lane + (hw == 1 ? 0 : 32); i < 360; i += 64) {
                        const float4 v = __ldcg(kv + i);
                        const int d = i / 5, e = (i - d * 5) * 4, h = d / 18;
                        const uint32_t base = KVB + (d >> 3) * 128 + (d & 7) * 16;
                        const int n0 = 8 + h * 18 + e;
                        sts32(base + (n0 >> 3) * 1280 + (n0 & 7) * 2, pack_bf16(v.x, v.y));
                        if (e < 16) sts32(base + ((n0 + 2) >> 3) * 1280 + ((n0 + 2) & 7) * 2, pack_bf16(v.z, v.w));
                        else asm volatile("st.shared.u16 [%0], %1;" :: "r"(base + h * 2), "h"((unsigned short)pack_bf16(v.z, 0.f)) : "memory");
                    }
                    fence_async_smem();
                    __syncwarp();
                    if (lane == 0) mbar_arrive(bar(B_KVB));
                }
            }
            if (hw == 1) {
                if (lane == 0) {
                    const int nit = is_main ? 1 : 4;
                    for (int it = 0; it < nit; it++) {
                        const int mt = is_main ? m : ((bid - NMAIN) * 4 + it);
                        const bool wf = is_main || it > 0;
                        const uint32_t fp = is_main ? 0 : ((it - 1) & 1);
                        wait_cnt(cnt_o(mt), (epoch + 1) * 8);
                        fence_async_all();
                        #pragma unroll 1
                        for (int kb = 0; kb < 9; kb++) {
                            const int g = kb / 3;
                            if (kb == 3 * g || kb == 8) { if (wf) mbar_wait(bar(B_OFREE + (kb == 8 ? 3 : g)), fp); }
                            if (kb == 3 * g) mbar_expect_tx(bar(B_OFULL + g), 49152);
                            tma_2d(HA + kb * 16384, &tm_o, bar(B_OFULL + g), kb * 64, mt * 128);
                        }
                    }
                    if (is_main) { wait_cnt(cnt_y(m, j), (epoch + 1) * 7); mbar_arrive(bar(B_YRDY)); }
                }
            } else if (hw == 2) {
                if (!is_main) {
                    if (lane == 0) {
                        #pragma unroll 1
                        for (int it = 0; it < 4; it++) {
                            if (it > 0) mbar_wait(bar(B_KVB), (it - 1) & 1);
                            wait_cnt(cnt_y((bid - NMAIN) * 4 + it, 8), (epoch + 1) * 8);
                            mbar_arrive(bar(B_YRDY));
                        }
                    }
                } else {
                    #pragma unroll 1
                    for (int e = 0; e < 10; e++) {
                        int spin = 0;
                        while (true) {
                            uint32_t v;
                            asm volatile("ld.acquire.cta.shared.u32 %0, [%1];" : "=r"(v) : "r"(EVC + (lane & 7) * 4) : "memory");
                            if (__all_sync(0xffffffffu, v > (uint32_t)e)) break;
                            if (++spin > 20000000) __trap();
                            __nanosleep(20);
                        }
                        if (lane == 0) {
                            unsigned int* cp = (e == 0) ? cnt_kv(j) : (e == 1) ? cnt_o(m) : cnt_y(m, e == 2 ? 8 : ((j + e - 2) & 7));
                            if (e == 1) fence_async_all();
                            __threadfence();
                            asm volatile("red.relaxed.gpu.global.add.u32 [%0], 1;" :: "l"(cp) : "memory");
                        }
                        __syncwarp();
                    }
                }
            } else {
                {
                    const int t0 = is_main ? (m * 9 + j) : ((bid - NMAIN) * 4 * 9 + 8);
                    const int nt = is_main ? 1 : 4;
                    for (int t = 0; t < nt; t++) {
                        uint4* z = reinterpret_cast<uint4*>(g_yacc + (size_t)((par ^ 1) * 144 + t0 + t * 9) * YT_BYTES);
                        for (int i = lane; i < YT_BYTES / 16; i += 32) z[i] = make_uint4(0, 0, 0, 0);
                    }
                    if (is_main && m == 0) {
                        float* z = g_kv + ((par ^ 1) * 8 + j) * 1440;
                        for (int i = lane; i < 1440; i += 32) z[i] = 0.f;
                    }
                }
            }
        }
    } else {
        asm volatile("setmaxnreg.inc.sync.aligned.u32 240;");
        prof(0);
        Ctx c; c.tph = 0; c.tid = v_tid();
        float hc[32], pv[36];
        if (tid >> 7) turn_pass(c);
        auto event = [&](uint32_t ev) {
            __syncwarp();
            if (((c.tid & 31) == 0)) asm volatile("st.release.cta.shared.u32 [%0], %1;" :: "r"(EVC + (c.tid >> 3)), "r"(ev) : "memory");
        };
        auto warp_arrive = [&](uint32_t b) { __syncwarp(); if (((c.tid & 31) == 0)) mbar_arrive(b); };

        if (is_main) {
            uint32_t a[128];
            float rs0, rs1;
            uint32_t m00, m11;
            auto lrow_off = [&]() { uint32_t t_ = c.tid; return HA + ((t_ >> 5) * 16 + (t_ & 15)) * 128 + ((((t_ >> 4) & 1) ^ (t_ & 7)) << 4); };
            auto tail_off = [&]() { uint32_t t_ = c.tid, g = (t_ >> 2) & 7; return XB + ((t_ >> 5) * 16 + g) * 128 + (g << 4) + (t_ & 3) * 4; };
            {
                uint32_t tl[16];
                const uint32_t lrow = lrow_off();
                float cs[2][4] = {{0.f, 0.f, 0.f, 0.f}, {0.f, 0.f, 0.f, 0.f}};
                sfor<0, 36>([&](auto KS) {
                    constexpr int ks = decltype(KS)::v;
                    if constexpr (ks % 12 == 0) mbar_wait(bar(B_XFULL + ks / 12), 0);
                    uint32_t* dst = (ks < 32) ? (a + (ks & 31) * 4) : (tl + (ks & 3) * 4);
                    ldsm4((lrow ^ ((ks % 4) << 5)) + (ks / 4) * 16384, dst);
                    mma_ones(cs[ks & 1], dst);
                });
                prof(2);
                float mean0 = (cs[0][0] + cs[1][0]) * (1.0f / 576.0f), mean1 = (cs[0][2] + cs[1][2]) * (1.0f / 576.0f);
                m00 = pack_bf16(mean0, mean0); m11 = pack_bf16(mean1, mean1);
                rs0 = mean0 - bf_lo(m00); rs1 = mean1 - bf_lo(m11);
                rs0 = -144.0f * rs0 * rs0; rs1 = -144.0f * rs1 * rs1;
                const uint32_t tb = tail_off();
                #pragma unroll
                for (int i = 0; i < 16; i++) {
                    const uint32_t w = sub_bf16x2(tl[i], (i & 1) ? m11 : m00);
                    sts32((tb ^ ((i >> 1) << 4)) + (i & 1) * 1024, w);
                    float lo = bf_lo(w), hi = bf_hi(w);
                    if (i & 1) rs1 = fmaf(lo, lo, fmaf(hi, hi, rs1)); else rs0 = fmaf(lo, lo, fmaf(hi, hi, rs0));
                }
                fence_async_smem();
                #pragma unroll
                for (int i = 0; i < 128; i++) a[i] = sub_bf16x2(a[i], (i & 1) ? m11 : m00);
                named_bar(2 + (tid >> 7), 128);
            }
            prof(3);
            auto cm_off = [&]() { uint32_t t_ = c.tid; return (t_ >> 5) * 256 + (t_ & 31) * 4; };
            {
                float qc[36];
                #pragma unroll
                for (int i = 0; i < 36; i++) { qc[i] = 0.f; pv[i] = 0.f; }
                #pragma unroll 1
                for (int s = 0; s < 3; s++) {
                    run_step<K_QKV>(c, qc, a, [&](auto ST) {
                        constexpr int st = decltype(ST)::v;
                        if (s == 0) {
                            const uint32_t lrow = lrow_off();
                            sfor<(st * 32) / 6, ((st + 1) * 32) / 6>([&](auto I) {
                                constexpr int ks = decltype(I)::v;
                                uint32_t v[4];
                                ldsm4((lrow ^ ((ks % 4) << 5)) + (ks / 4) * 16384, v);
                                #pragma unroll
                                for (int r = 0; r < 4; r++) {
                                    uint32_t w = sub_bf16x2(v[r], (r & 1) ? m11 : m00);
                                    float lo = bf_lo(w), hi = bf_hi(w);
                                    if (r & 1) rs1 = fmaf(lo, lo, fmaf(hi, hi, rs1)); else rs0 = fmaf(lo, lo, fmaf(hi, hi, rs0));
                                }
                            });
                            if constexpr (st == 5) {
                                rs0 += __shfl_xor_sync(0xffffffffu, rs0, 1); rs1 += __shfl_xor_sync(0xffffffffu, rs1, 1);
                                rs0 += __shfl_xor_sync(0xffffffffu, rs0, 2); rs1 += __shfl_xor_sync(0xffffffffu, rs1, 2);
                                rs0 = rsqrtf(fmaxf(rs0 * (1.0f / 576.0f), 0.f) + 1e-5f);
                                rs1 = rsqrtf(fmaxf(rs1 * (1.0f / 576.0f), 0.f) + 1e-5f);
                                named_bar(1, 256);
                            }
                        } else {
                            const uint32_t cm = cm_off();
                            sfor<0, 9>([&](auto B) {
                                constexpr int b = decltype(B)::v;
                                if constexpr ((b * 6) / 9 == st) {
                                    const float v0 = pv[4 * b] * rs0, v1 = pv[4 * b + 1] * rs0, v2 = pv[4 * b + 2] * rs1, v3 = pv[4 * b + 3] * rs1;
                                    if (s == 1) {
                                        sts32(PKT + b * 2048 + cm, pack_bf16(phi(v0), phi(v1)));
                                        sts32(PKT + b * 2048 + cm + 128, pack_bf16(phi(v2), phi(v3)));
                                    } else {
                                        const uint32_t w0 = pack_bf16(v0, v1), w1 = pack_bf16(v2, v3);
                                        if constexpr (b <= 4) { sts32(VT + b * 2048 + cm, w0); sts32(VT + b * 2048 + cm + 128, w1); }
                                        if constexpr (b >= 4) { sts32(VT + (b + 2) * 2048 + cm, w0); sts32(VT + (b + 2) * 2048 + cm + 128, w1); }
                                        if constexpr (b == 0) {
                                            const uint32_t one = (cm & 12) ? 0u : 0x00003F80u;
                                            sts32(VT + 5 * 2048 + cm, one); sts32(VT + 5 * 2048 + cm + 128, one);
                                        }
                                        if constexpr (b == 8) {
                                            const uint32_t z = KVB + c.tid * 16;
                                            sts128(z, 0, 0, 0, 0); sts128(z + 4096, 0, 0, 0, 0); sts128(z + 8192, 0, 0, 0, 0);
                                            if (z < KVB + 512) sts128(z + 12288, 0, 0, 0, 0);
                                            fence_async_smem();
                                        }
                                    }
                                }
                            });
                        }
                    }, [](auto) {});
                    reg_copy<36>(pv, qc);
                    prof(4 + s);
                }
            }
            {
                #pragma unroll
                for (int i = 0; i < 32; i++) hc[i] = 0.f;
                named_bar(1, 256);
                const uint32_t wgo = ((c.tid >> 7) * 512);
                wg_fence();
                sfor<0, 8>([&](auto KS) {
                    constexpr int ks = decltype(KS)::v;
                    wg_tt64<(ks ? 1 : 0)>(hc, mkdesc(PKT + ks * 256, 128, 2048, 0) + wgo,
                                          mkdesc(VT + ks * 256, 128, 2048, 0) + wgo + (wgo >> 2));
                });
                wg_commit();
                const uint32_t pq = PQT + cm_off() + ((c.tid >> 7) * 512) * 16;
                sfor<0, 9>([&](auto B) {
                    constexpr int b = decltype(B)::v;
                    sts32(pq + b * 1024, pack_bf16(phi(pv[4 * b] * rs0), phi(pv[4 * b + 1] * rs0)));
                    sts32(pq + b * 1024 + 128, pack_bf16(phi(pv[4 * b + 2] * rs1), phi(pv[4 * b + 3] * rs1)));
                });
                fence_async_smem();
                wg_wait<0>();
                reg_fence<32>(hc);
                reg_copy<24>(pv, hc);
            }
            prof(7);
            rs0 *= 0.5f; rs1 *= 0.5f;
            auto gelun = [&](auto B0, auto B1, uint32_t bofs, uint32_t* w) {
                constexpr int b0 = decltype(B0)::v, nb = decltype(B1)::v - b0;
                float2 bv[nb];
                #pragma unroll
                for (int i = 0; i < nb; i++) bv[i] = lds64f(bofs + (b0 + i) * 32);
                #pragma unroll
                for (int i = 0; i < nb; i++) {
                    const int b = b0 + i;
                    w[2 * i]     = pack_bf16(gelu_h(fmaf(pv[4 * b], rs0, bv[i].x)), gelu_h(fmaf(pv[4 * b + 1], rs0, bv[i].y)));
                    w[2 * i + 1] = pack_bf16(gelu_h(fmaf(pv[4 * b + 2], rs1, bv[i].x)), gelu_h(fmaf(pv[4 * b + 3], rs1, bv[i].y)));
                }
            };
            auto spill_off = [&]() { uint32_t t_ = c.tid; return HA + (t_ >> 7) * 8192 + (t_ & 127) * 8; };
            auto reload = [&](auto S0, auto S1) {
                const uint32_t spill = spill_off();
                sfor<decltype(S0)::v * 8, decltype(S1)::v * 8>([&](auto Q) {
                    constexpr int q = decltype(Q)::v;
                    lds64(spill + (q / 8) * 16384 + (q % 8) * 1024, a + q * 2);
                });
            };
            #pragma unroll 1
            for (int idx = 0; idx < 18; idx++) {
                run_step<K_H>(c, hc, a, [&](auto ST) {
                    constexpr int st = decltype(ST)::v;
                    if (idx >= 10) {
                        if constexpr (st < 2) {
                            const uint32_t b_ = v_bid();
                            const uint32_t chunk = (idx == 10) ? 8 : ((b_ + idx - 10) & 7);
                            unsigned char* yp = g_yacc + ((v_epoch() & 1) * 144 + (b_ >> 3) * 9 + chunk) * YT_BYTES + c.tid * 16;
                            sfor<2 * st, 2 * st + 2>([&](auto Q) {
                                constexpr int q = decltype(Q)::v;
                                asm volatile("red.global.add.noftz.v4.bf16x2 [%0], {%1,%2,%3,%4};" :: "l"(yp + q * 4096),
                                             "r"(pack_bf16(pv[8 * q], pv[8 * q + 1])), "r"(pack_bf16(pv[8 * q + 2], pv[8 * q + 3])),
                                             "r"(pack_bf16(pv[8 * q + 4], pv[8 * q + 5])), "r"(pack_bf16(pv[8 * q + 6], pv[8 * q + 7])) : "memory");
                            });
                            if constexpr (st == 1) event(idx - 7);
                        }
                    } else if (idx >= 1) {
                        const uint32_t bofs = B1S + (idx - 1) * 256 + (c.tid & 3) * 8;
                        if (idx < 9) {
                            if constexpr (st == 0) { if (idx == OSTEP_AT + 1) event(2); }
                            const uint32_t spill = spill_off() + (idx - 1) * 16384;
                            constexpr int b0 = st * 3, b1 = (st == 2 ? 8 : st * 3 + 3);
                            uint32_t w[6];
                            gelun(IC<b0>{}, IC<b1>{}, bofs, w);
                            #pragma unroll
                            for (int b = b0; b < b1; b++) sts64(spill + b * 1024, w[2 * (b - b0)], w[2 * (b - b0) + 1]);
                        } else {
                            if constexpr (st < 2) {
                                const uint32_t tb = tail_off();
                                uint32_t w[8];
                                gelun(IC<st * 4>{}, IC<st * 4 + 4>{}, bofs, w);
                                #pragma unroll
                                for (int i = 0; i < 4; i++) { sts32(tb ^ ((st * 4 + i) << 4), w[2 * i]); sts32((tb ^ ((st * 4 + i) << 4)) + 1024, w[2 * i + 1]); }
                            }
                            if constexpr (st == 1) { fence_async_smem(); named_bar(2 + (c.tid >> 7), 128); }
                        }
                    } else {
                        if constexpr (st < 2) {
                            constexpr int hf = st;
                            const int t_ = c.tid, wg = t_ >> 7, t = t_ & 3;
                            float* dst = g_kv + ((v_epoch() & 1) * 8 + (v_bid() & 7)) * 1440;
                            const int d = wg * 32 + ((t_ >> 5) & 3) * 16 + ((t_ >> 2) & 7) + hf * 8;
                            const bool dv = wg ? (d >= 36 && d < 72) : (d < 36);
                            const int e00 = wg * 24 + 2 * t - (d / 18) * 18;
                            float* dp = dst + d * 20 + e00;
                            #pragma unroll
                            for (int i = 0; i < 6; i++) {
                                const int e = e00 + i * 8;
                                const bool blk = wg ? (i >= 1) : (i <= 4);
                                if (dv && blk && e >= 0 && e < 18)
                                    asm volatile("red.global.add.v2.f32 [%0], {%1,%2};" :: "l"(dp + i * 8), "f"(pv[4 * i + 2 * hf]), "f"(pv[4 * i + 2 * hf + 1]) : "memory");
                            }
                            if (dv && t == 0) atomicAdd(dst + d * 20 + 18, wg ? pv[2 * hf] : pv[20 + 2 * hf]);
                            if constexpr (st == 1) event(1);
                        }
                    }
                }, [&](auto ST) {
                    constexpr int st = decltype(ST)::v;
                    if (idx == 8) {
                        reload(IC<3 * st>{}, IC<(st == 2 ? 8 : 3 * st + 3)>{});
                        warp_arrive(bar(B_OFREE + st));
                    }
                });
                reg_copy<32>(pv, hc);
                prof(8 + idx);
                if (idx == OSTEP_AT) {
                    mbar_wait(bar(B_KVB), 0);
                    prof(34);
                    const uint32_t pqo = (c.tid >> 7) * 576;
                    const int t_ = c.tid, b_ = v_bid(), t = t_ & 3, l4 = t_ & 28;
                    __nv_bfloat16* op = g_o + (size_t)((b_ >> 3) * 128 + (t_ >> 5) * 16 + ((t_ >> 2) & 7)) * DM + (b_ & 7) * 72 + 2 * t;
                    float r3[2];
                    sfor<0, 2>([&](auto PS) {
                        constexpr int ps = decltype(PS)::v;
                        wg_fence();
                        sfor<0, 5>([&](auto KS) {
                            constexpr int ks = decltype(KS)::v;
                            wg_ss64<(ks ? 1 : 0)>(hc, mkdesc(PQT + ks * 2048, ks == 4 ? 0 : 1024, 128, 0) + pqo, mkdesc(KVB + ps * 8 * 1280 + ks * 256, 128, 1280, 0));
                        });
                        wg_commit();
                        wg_wait<0>();
                        reg_fence<32>(hc);
                        #pragma unroll
                        for (int hf = 0; hf < 2; hf++) {
                            if constexpr (ps == 0) {
                                float r[4];
                                r[0] = rcp(__shfl_sync(0xffffffffu, hc[2 * hf], l4) + 1e-6f);
                                r[1] = rcp(__shfl_sync(0xffffffffu, hc[1 + 2 * hf], l4) + 1e-6f);
                                r[2] = rcp(__shfl_sync(0xffffffffu, hc[2 * hf], l4 + 1) + 1e-6f);
                                r[3] = rcp(__shfl_sync(0xffffffffu, hc[1 + 2 * hf], l4 + 1) + 1e-6f);
                                r3[hf] = r[3];
                                #pragma unroll
                                for (int i = 0; i < 7; i++) {
                                    float rr = (i < 2) ? r[0] : (i == 2) ? (t < 1 ? r[0] : r[1]) : (i == 3) ? r[1] : (i == 4) ? (t < 2 ? r[1] : r[2])
                                             : (i == 5) ? r[2] : (t < 3 ? r[2] : r[3]);
                                    *reinterpret_cast<uint32_t*>(op + hf * 8 * DM + i * 8) = pack_bf16(hc[4 * i + 4 + 2 * hf] * rr, hc[4 * i + 5 + 2 * hf] * rr);
                                }
                            } else {
                                #pragma unroll
                                for (int i = 0; i < 2; i++)
                                    *reinterpret_cast<uint32_t*>(op + hf * 8 * DM + 56 + i * 8) = pack_bf16(hc[4 * i + 2 * hf] * r3[hf], hc[4 * i + 1 + 2 * hf] * r3[hf]);
                            }
                        }
                    });
                }
            }
            warp_arrive(bar(B_OFREE + 3));
        }
        const int b2_ = v_bid(), t2_ = c.tid;
        uint32_t xr[16];
        uint4 yv[4];
        auto load_x = [&](size_t eoff) {
            #pragma unroll
            for (int i = 0; i < 8; i++) {
                xr[2 * i] = __ldg(reinterpret_cast<const uint32_t*>(p.x + eoff + i * 8));
                xr[2 * i + 1] = __ldg(reinterpret_cast<const uint32_t*>(p.x + eoff + 8 * DM + i * 8));
            }
        };
        auto load_y = [&](int tile) {
            const unsigned char* yp = g_yacc + ((v_epoch() & 1) * 144 + tile) * YT_BYTES + t2_ * 16;
            #pragma unroll
            for (int q = 0; q < 4; q++) yv[q] = __ldcg(reinterpret_cast<const uint4*>(yp + q * 4096));
        };
        auto gate = [&]() {
            #pragma unroll
            for (int q = 0; q < 4; q++) {
                const uint4 u = yv[q];
                pv[8 * q] += bf_lo(u.x); pv[8 * q + 1] += bf_hi(u.x); pv[8 * q + 2] += bf_lo(u.y); pv[8 * q + 3] += bf_hi(u.y);
                pv[8 * q + 4] += bf_lo(u.z); pv[8 * q + 5] += bf_hi(u.z); pv[8 * q + 6] += bf_lo(u.w); pv[8 * q + 7] += bf_hi(u.w);
            }
            #pragma unroll
            for (int i = 0; i < 32; i++) pv[i] = pv[i] * rcp(1.0f + ex2(pv[i] * -1.4426950408889634f));
        };
        auto add_b2 = [&]() {
            #pragma unroll
            for (int b = 0; b < 8; b++) {
                float2 bv = lds64f(B2S + b * 32 + (t2_ & 3) * 8);
                pv[4 * b] += bv.x; pv[4 * b + 1] += bv.y; pv[4 * b + 2] += bv.x; pv[4 * b + 3] += bv.y;
            }
        };
        auto store_out = [&](size_t eoff) {
            #pragma unroll
            for (int b = 0; b < 8; b++) {
                *reinterpret_cast<uint32_t*>(p.out + eoff + b * 8) =
                    pack_bf16(fmaf(hc[4 * b], pv[4 * b], bf_lo(xr[2 * b])), fmaf(hc[4 * b + 1], pv[4 * b + 1], bf_hi(xr[2 * b])));
                *reinterpret_cast<uint32_t*>(p.out + eoff + 8 * DM + b * 8) =
                    pack_bf16(fmaf(hc[4 * b + 2], pv[4 * b + 2], bf_lo(xr[2 * b + 1])), fmaf(hc[4 * b + 3], pv[4 * b + 3], bf_hi(xr[2 * b + 1])));
            }
        };
        const int rowoff = (t2_ >> 5) * 16 + ((t2_ >> 2) & 7);
        const bool mainf = b2_ < NMAIN;
        uint32_t sv[64];
        if (!mainf) {
            #pragma unroll
            for (int i = 0; i < 32; i++) hc[i] = 0.f;
        }
        #pragma unroll
        for (int i = 0; i < 64; i++) sv[i] = 0;
        #pragma unroll 1
        for (int job = mainf ? 7 : 0; job < 8; job++) {
            const bool do_s = mainf || job < 4, do_f = job >= 4;
            const int mt = mainf ? (b2_ >> 3) : ((b2_ - NMAIN) * 4 + (job & 3));
            const uint32_t jpar = mainf ? 0 : (job & 1);
            const int ch = mainf ? (b2_ & 7) : 8;
            const size_t eoff = (size_t)(mt * 128 + rowoff) * DM + ch * 64 + 2 * (t2_ & 3);
            sfor<0, 3>([&](auto ST) {
                constexpr int st = decltype(ST)::v;
                if (do_s) {
                    mbar_wait(bar(B_FULL + st), c.tph);
                    mbar_wait(bar(B_OFULL + st), jpar);
                }
                if (!mainf && job < 5) prof(44 + job * 3 + st);
                const uint32_t wgo = ((c.tid >> 7) * 512);
                turn_wait(c);
                wg_fence();
                sfor<0, 12>([&](auto KK) {
                    constexpr int kk = decltype(KK)::v;
                    constexpr int ks = st * 12 + kk;
                    wg_ss64<(ks ? 1 : 0)>(hc, mkdesc(HA + (ks / 4) * 16384 + (ks % 4) * 32, 16, 1024, 1) + wgo,
                                          mkdesc(RING + st * SLOT + kk * 2048, 16, 1024, 1));
                });
                wg_commit();
                if (st < 2 || job < 7 || wgo == 0) turn_pass(c);
                if (do_f) {
                    if constexpr (st == 0) {
                        load_x(eoff);
                        if (!mainf) {
                            #pragma unroll
                            for (int i = 0; i < 32; i++) pv[i] = 0.f;
                        }
                        add_b2();
                    } else if constexpr (st == 1) {
                        prof(26);
                        mbar_wait(bar(B_YRDY), jpar);
                        prof(27);
                        load_y(mt * 9 + ch);
                        if (!mainf) warp_arrive(bar(B_KVB));
                    } else { prof(28); gate(); prof(29); }
                }
                wg_wait<0>();
                if (do_s && ((c.tid & 31) == 0)) { mbar_arrive(bar(B_EMPTY + st)); mbar_arrive(bar(B_OFREE + st)); if (st == 2) mbar_arrive(bar(B_OFREE + 3)); }
            });
            c.tph ^= 1;
            reg_fence<32>(hc);
            prof(30);
            if (!mainf) {
                #pragma unroll
                for (int i = 0; i < 16; i++) {
                    const uint32_t t = pack_bf16(hc[2 * i], hc[2 * i + 1]);
                    hc[2 * i] = bf_lo(sv[i]); hc[2 * i + 1] = bf_hi(sv[i]);
                    sv[i] = sv[i + 16]; sv[i + 16] = sv[i + 32]; sv[i + 32] = sv[i + 48]; sv[i + 48] = t;
                }
            }
            if (!mainf) prof(8 + 2 * job);
            if (do_f) store_out(eoff);
            if (!mainf) prof(9 + 2 * job);
        }
        prof(40);
        if (t2_ == 0) g_epoch[b2_] = v_epoch() + 1;
    }
}

typedef CUresult (*EncodeFn)(CUtensorMap*, CUtensorMapDataType, cuuint32_t, void*, const cuuint64_t*, const cuuint64_t*,
                             const cuuint32_t*, const cuuint32_t*, CUtensorMapInterleave, CUtensorMapSwizzle,
                             CUtensorMapL2promotion, CUtensorMapFloatOOBfill);

void make_map(EncodeFn enc, CUtensorMap* tm, const void* base, int rows, int cols, int box_rows, int box_cols = 64) {
    cuuint64_t gdim[2] = {(cuuint64_t)cols, (cuuint64_t)rows};
    cuuint64_t gstr[1] = {(cuuint64_t)cols * 2};
    cuuint32_t box[2] = {(cuuint32_t)box_cols, (cuuint32_t)box_rows};
    cuuint32_t estr[2] = {1, 1};
    enc(tm, CU_TENSOR_MAP_DATA_TYPE_BFLOAT16, 2, const_cast<void*>(base), gdim, gstr, box, estr, CU_TENSOR_MAP_INTERLEAVE_NONE,
        CU_TENSOR_MAP_SWIZZLE_128B, CU_TENSOR_MAP_L2_PROMOTION_L2_128B, CU_TENSOR_MAP_FLOAT_OOB_FILL_NONE);
}

}

extern "C" void kernel_launch(void* const* d_in, const int* in_sizes, int n_in, void* d_out, int out_size) {
    static EncodeFn enc = nullptr;
    static void* o_ptr = nullptr;
    if (!enc) {
        void* fn = nullptr;
        cudaDriverEntryPointQueryResult qr;
        cudaGetDriverEntryPoint("cuTensorMapEncodeTiled", &fn, cudaEnableDefault, &qr);
        enc = (EncodeFn)fn;
        cudaGetSymbolAddress(&o_ptr, g_o);
        cudaFuncSetAttribute(fused_kernel, cudaFuncAttributeMaxDynamicSharedMemorySize, SMEM_BYTES);
    }
    Params p;
    p.x = (const __nv_bfloat16*)d_in[0];
    p.wqkv = (const __nv_bfloat16*)d_in[1];
    p.wo = (const __nv_bfloat16*)d_in[2];
    p.w1 = (const __nv_bfloat16*)d_in[4];
    p.b1 = (const __nv_bfloat16*)d_in[5];
    p.w2 = (const __nv_bfloat16*)d_in[6];
    p.b2 = (const __nv_bfloat16*)d_in[7];
    p.out = (__nv_bfloat16*)d_out;
    CUtensorMap tm_x, tm_w1, tm_w2, tm_wo, tm_o, tm_qkv, tm_qkve;
    make_map(enc, &tm_qkv, p.wqkv, DM, 3 * DM, 96);
    make_map(enc, &tm_qkve, p.wqkv, DM, 3 * DM, 96, 8);
    make_map(enc, &tm_x, p.x, SEQ, DM, 128);
    make_map(enc, &tm_w1, p.w1, DM, FF, 192);
    make_map(enc, &tm_w2, p.w2, FF, DM, 192);
    make_map(enc, &tm_wo, p.wo, DM, DM, 192);
    make_map(enc, &tm_o, o_ptr, SEQ, DM, 128);
    fused_kernel<<<NMAIN + NAUX, 384, SMEM_BYTES>>>(tm_x, tm_w1, tm_w2, tm_wo, tm_o, tm_qkv, tm_qkve, p);
}
```

```cpp
#include <cuda_runtime.h>
#include <cuda.h>
#include <cuda_bf16.h>
#include <stdint.h>

#define OSTEP_AT 4
#define KNOB_A 1
#define KNOB_B 0
#define PF1_NS 1000
#define PF2_NS 2000
#define PFIDX 3
#define PF3_NS 800
#define YF32 0

namespace {
constexpr int WAIT_ITERS = 3000000;

constexpr int SEQ = 2048, DM = 576, FF = 4608;
constexpr int NMAIN = 128, NAUX = 4;

constexpr uint32_t SB    = 0x400;
constexpr uint32_t HA    = SB;
constexpr uint32_t XB    = SB + 131072;
constexpr uint32_t RING  = SB + 147456;
constexpr uint32_t SLOT  = 24576;
constexpr uint32_t MISC  = SB + 221184;
constexpr uint32_t BARS  = MISC;
constexpr uint32_t B1S   = MISC + 512;
constexpr uint32_t B2S   = MISC + 2816;
constexpr uint32_t EPO   = MISC + 3072;
constexpr uint32_t EVC   = MISC + 3104;
constexpr uint32_t SMEM_BYTES = 221184 + 3200 + 512;
constexpr uint32_t PKT   = HA + 32768;
constexpr uint32_t VT    = HA + 51200;
constexpr uint32_t PQT   = HA + 98304;
constexpr uint32_t KVB   = HA + 116736;

enum { B_FULL = 0, B_EMPTY = 3, B_XFULL = 6, B_OFULL = 9, B_OFREE = 12  , B_KVB = 16, B_YRDY = 17, B_COUNT = 18 };
__device__ __forceinline__ constexpr uint32_t bar(int i) { return BARS + 8u * i; }

constexpr int YT_BYTES = YF32 ? 32768 : 16384;
__device__ __align__(1024) __nv_bfloat16 g_o[SEQ * DM];
__device__ __align__(1024) unsigned char g_yacc[2 * 16 * 9 * YT_BYTES];
__device__ __align__(128) float g_kv[2 * 8 * 72 * 20];
__device__ __align__(128) unsigned int g_cnt[(8 + 16 + 16 * 9) * 8];
__device__ unsigned int g_epoch[NMAIN + NAUX];
__device__ __forceinline__ unsigned int* cnt_kv(int j) { return g_cnt + j * 8; }
__device__ __forceinline__ unsigned int* cnt_o(int m) { return g_cnt + (8 + m) * 8; }
__device__ __forceinline__ unsigned int* cnt_y(int m, int c) { return g_cnt + (24 + m * 9 + c) * 8; }

__device__ __forceinline__ void mbar_init(uint32_t b, uint32_t cnt) { asm volatile("mbarrier.init.shared::cta.b64 [%0], %1;" :: "r"(b), "r"(cnt)); }
__device__ __forceinline__ void mbar_expect_tx(uint32_t b, uint32_t bytes) { asm volatile("mbarrier.arrive.expect_tx.shared::cta.b64 _, [%0], %1;" :: "r"(b), "r"(bytes) : "memory"); }
__device__ __forceinline__ void mbar_arrive(uint32_t b) { asm volatile("mbarrier.arrive.shared::cta.b64 _, [%0];" :: "r"(b) : "memory"); }
__device__ __forceinline__ void prof(int) {}
__device__ __forceinline__ void mbar_wait(uint32_t b, uint32_t parity) {
    asm volatile("{\n.reg .pred p;\n.reg .u32 c;\nmov.u32 c, 0;\n"
                 "WAIT_LOOP:\nmbarrier.try_wait.parity.shared::cta.b64 p, [%0], %1;\n@p bra WAIT_DONE;\n"
                 "add.u32 c, c, 1;\nsetp.lt.u32 p, c, 4000000;\n@p bra WAIT_LOOP;\ntrap;\nWAIT_DONE:\n}"
                 :: "r"(b), "r"(parity) : "memory");
}
__device__ __forceinline__ void tma_2d(uint32_t dst, const CUtensorMap* tm, uint32_t b, int c0, int c1) {
    asm volatile("cp.async.bulk.tensor.2d.shared::cluster.global.mbarrier::complete_tx::bytes [%0], [%1, {%3, %4}], [%2];"
                 :: "r"(dst), "l"(tm), "r"(b), "r"(c0), "r"(c1) : "memory");
}
__device__ __forceinline__ void fence_async_smem() { asm volatile("fence.proxy.async.shared::cta;" ::: "memory"); }
__device__ __forceinline__ void fence_async_all() { asm volatile("fence.proxy.async;" ::: "memory"); }
__device__ __forceinline__ void named_bar(int id, int n) { asm volatile("bar.sync %0, %1;" :: "r"(id), "r"(n) : "memory"); }
__device__ __forceinline__ void wg_fence() { asm volatile("wgmma.fence.sync.aligned;" ::: "memory"); }
__device__ __forceinline__ void wg_commit() { asm volatile("wgmma.commit_group.sync.aligned;" ::: "memory"); }
template<int N> __device__ __forceinline__ void wg_wait() { asm volatile("wgmma.wait_group.sync.aligned %0;" :: "n"(N) : "memory"); }
template<int N> __device__ __forceinline__ void reg_fence(float* d) {
    #pragma unroll
    for (int i = 0; i < N; i++) asm volatile("" : "+f"(d[i]) :: "memory");
}
template<int N> __device__ __forceinline__ void reg_copy(float* d, const float* s) {
    #pragma unroll
    for (int i = 0; i < N; i++) asm volatile("mov.b32 %0, %1;" : "=f"(d[i]) : "f"(s[i]));
}
__device__ __forceinline__ uint32_t pack_bf16(float lo, float hi) { uint32_t r; asm("cvt.rn.bf16x2.f32 %0, %1, %2;" : "=r"(r) : "f"(hi), "f"(lo)); return r; }
__device__ __forceinline__ float bf_lo(uint32_t v) { return __uint_as_float(v << 16); }
__device__ __forceinline__ float bf_hi(uint32_t v) { return __uint_as_float(v & 0xffff0000u); }
__device__ __forceinline__ uint32_t sub_bf16x2(uint32_t a, uint32_t b) { uint32_t r; asm("sub.rn.bf16x2 %0, %1, %2;" : "=r"(r) : "r"(a), "r"(b)); return r; }
__device__ __forceinline__ float ex2(float x) { float r; asm("ex2.approx.ftz.f32 %0, %1;" : "=f"(r) : "f"(x)); return r; }
__device__ __forceinline__ float rcp(float x) { float r; asm("rcp.approx.ftz.f32 %0, %1;" : "=f"(r) : "f"(x)); return r; }
__device__ __forceinline__ float tanh_ap(float x) { float r; asm("tanh.approx.f32 %0, %1;" : "=f"(r) : "f"(x)); return r; }
__device__ __forceinline__ void sts32(uint32_t a, uint32_t v) { asm volatile("st.shared.b32 [%0], %1;" :: "r"(a), "r"(v)); }
__device__ __forceinline__ void sts128(uint32_t a, uint32_t x, uint32_t y, uint32_t z, uint32_t w) { asm volatile("st.shared.v4.b32 [%0], {%1,%2,%3,%4};" :: "r"(a), "r"(x), "r"(y), "r"(z), "r"(w)); }
__device__ __forceinline__ void sts64(uint32_t a, uint32_t x, uint32_t y) { asm volatile("st.shared.v2.b32 [%0], {%1,%2};" :: "r"(a), "r"(x), "r"(y)); }
__device__ __forceinline__ void lds64(uint32_t a, uint32_t* v) { asm volatile("ld.shared.v2.b32 {%0,%1}, [%2];" : "=r"(v[0]), "=r"(v[1]) : "r"(a)); }
__device__ __forceinline__ void lds128(uint32_t a, uint32_t* v) { asm volatile("ld.shared.v4.b32 {%0,%1,%2,%3}, [%4];" : "=r"(v[0]), "=r"(v[1]), "=r"(v[2]), "=r"(v[3]) : "r"(a) : "memory"); }
__device__ __forceinline__ float2 lds64f(uint32_t a) { float2 v; asm("ld.shared.v2.f32 {%0,%1}, [%2];" : "=f"(v.x), "=f"(v.y) : "r"(a)); return v; }
__device__ __forceinline__ void ldsm4(uint32_t a, uint32_t* v) {
    asm volatile("ldmatrix.sync.aligned.m8n8.x4.shared.b16 {%0,%1,%2,%3}, [%4];" : "=r"(v[0]), "=r"(v[1]), "=r"(v[2]), "=r"(v[3]) : "r"(a));
}
__device__ __forceinline__ void mma_ones(float* c, const uint32_t* a) {
    const uint32_t one2 = 0x3F803F80u;
    asm volatile("mma.sync.aligned.m16n8k16.row.col.f32.bf16.bf16.f32 {%0,%1,%2,%3}, {%4,%5,%6,%7}, {%8,%8}, {%0,%1,%2,%3};"
                 : "+f"(c[0]), "+f"(c[1]), "+f"(c[2]), "+f"(c[3]) : "r"(a[0]), "r"(a[1]), "r"(a[2]), "r"(a[3]), "r"(one2));
}
__device__ __forceinline__ unsigned int ld_acquire(const unsigned int* p) { unsigned int v; asm volatile("ld.acquire.gpu.global.u32 %0, [%1];" : "=r"(v) : "l"(p) : "memory"); return v; }
__device__ __forceinline__ void wait_cnt(const unsigned int* p, unsigned int target) {
    for (int i = 0; i < WAIT_ITERS; i++) {
        if ((int)(ld_acquire(p) - target) >= 0) return;
        __nanosleep(40);
    }
    __trap();
}
__device__ __forceinline__ uint32_t v_tid() { uint32_t r; asm volatile("mov.u32 %0, %%tid.x;" : "=r"(r)); return r; }
__device__ __forceinline__ uint32_t v_bid() { uint32_t r; asm volatile("mov.u32 %0, %%ctaid.x;" : "=r"(r)); return r; }
__device__ __forceinline__ uint32_t v_epoch() { uint32_t r; asm volatile("ld.shared.u32 %0, [%1];" : "=r"(r) : "r"(EPO)); return r; }
__device__ __forceinline__ void prefetch_l2(const void* p) { asm volatile("prefetch.global.L2 [%0];" :: "l"(p)); }

__host__ __device__ constexpr uint64_t mkdesc(uint32_t addr, uint32_t lbo, uint32_t sbo, uint32_t swz) {
    return (uint64_t)((addr & 0x3FFFF) >> 4) | ((uint64_t)((lbo >> 4) & 0x3FFF) << 16) | ((uint64_t)((sbo >> 4) & 0x3FFF) << 32) | ((uint64_t)swz << 62);
}

template<int SD> __device__ __forceinline__ void wg_rs64(float* d, const uint32_t* a, uint64_t bd) {
  if constexpr (SD) {
    asm volatile("{\n.reg .pred p;\nsetp.eq.b32 p, 0, 0;\n"
    "wgmma.mma_async.sync.aligned.m64n64k16.f32.bf16.bf16 {%0,%1,%2,%3,%4,%5,%6,%7,%8,%9,%10,%11,%12,%13,%14,%15,%16,%17,%18,%19,%20,%21,%22,%23,%24,%25,%26,%27,%28,%29,%30,%31}, {%32,%33,%34,%35}, %36, p, 1, 1, 1;\n}"
    : "+f"(d[0]),"+f"(d[1]),"+f"(d[2]),"+f"(d[3]),"+f"(d[4]),"+f"(d[5]),"+f"(d[6]),"+f"(d[7]),"+f"(d[8]),"+f"(d[9]),"+f"(d[10]),"+f"(d[11]),"+f"(d[12]),"+f"(d[13]),"+f"(d[14]),"+f"(d[15]),"+f"(d[16]),"+f"(d[17]),"+f"(d[18]),"+f"(d[19]),"+f"(d[20]),"+f"(d[21]),"+f"(d[22]),"+f"(d[23]),"+f"(d[24]),"+f"(d[25]),"+f"(d[26]),"+f"(d[27]),"+f"(d[28]),"+f"(d[29]),"+f"(d[30]),"+f"(d[31])
    : "r"(a[0]),"r"(a[1]),"r"(a[2]),"r"(a[3]), "l"(bd));
  } else {
    asm volatile("{\n.reg .pred p;\nsetp.ne.b32 p, 0, 0;\n"
    "wgmma.mma_async.sync.aligned.m64n64k16.f32.bf16.bf16 {%0,%1,%2,%3,%4,%5,%6,%7,%8,%9,%10,%11,%12,%13,%14,%15,%16,%17,%18,%19,%20,%21,%22,%23,%24,%25,%26,%27,%28,%29,%30,%31}, {%32,%33,%34,%35}, %36, p, 1, 1, 1;\n}"
    : "+f"(d[0]),"+f"(d[1]),"+f"(d[2]),"+f"(d[3]),"+f"(d[4]),"+f"(d[5]),"+f"(d[6]),"+f"(d[7]),"+f"(d[8]),"+f"(d[9]),"+f"(d[10]),"+f"(d[11]),"+f"(d[12]),"+f"(d[13]),"+f"(d[14]),"+f"(d[15]),"+f"(d[16]),"+f"(d[17]),"+f"(d[18]),"+f"(d[19]),"+f"(d[20]),"+f"(d[21]),"+f"(d[22]),"+f"(d[23]),"+f"(d[24]),"+f"(d[25]),"+f"(d[26]),"+f"(d[27]),"+f"(d[28]),"+f"(d[29]),"+f"(d[30]),"+f"(d[31])
    : "r"(a[0]),"r"(a[1]),"r"(a[2]),"r"(a[3]), "l"(bd));
  }
}
template<int SD> __device__ __forceinline__ void wg_ss64(float* d, uint64_t ad, uint64_t bd) {
  if constexpr (SD) {
    asm volatile("{\n.reg .pred p;\nsetp.eq.b32 p, 0, 0;\n"
    "wgmma.mma_async.sync.aligned.m64n64k16.f32.bf16.bf16 {%0,%1,%2,%3,%4,%5,%6,%7,%8,%9,%10,%11,%12,%13,%14,%15,%16,%17,%18,%19,%20,%21,%22,%23,%24,%25,%26,%27,%28,%29,%30,%31}, %32, %33, p, 1, 1, 0, 1;\n}"
    : "+f"(d[0]),"+f"(d[1]),"+f"(d[2]),"+f"(d[3]),"+f"(d[4]),"+f"(d[5]),"+f"(d[6]),"+f"(d[7]),"+f"(d[8]),"+f"(d[9]),"+f"(d[10]),"+f"(d[11]),"+f"(d[12]),"+f"(d[13]),"+f"(d[14]),"+f"(d[15]),"+f"(d[16]),"+f"(d[17]),"+f"(d[18]),"+f"(d[19]),"+f"(d[20]),"+f"(d[21]),"+f"(d[22]),"+f"(d[23]),"+f"(d[24]),"+f"(d[25]),"+f"(d[26]),"+f"(d[27]),"+f"(d[28]),"+f"(d[29]),"+f"(d[30]),"+f"(d[31])
    : "l"(ad), "l"(bd));
  } else {
    asm volatile("{\n.reg .pred p;\nsetp.ne.b32 p, 0, 0;\n"
    "wgmma.mma_async.sync.aligned.m64n64k16.f32.bf16.bf16 {%0,%1,%2,%3,%4,%5,%6,%7,%8,%9,%10,%11,%12,%13,%14,%15,%16,%17,%18,%19,%20,%21,%22,%23,%24,%25,%26,%27,%28,%29,%30,%31}, %32, %33, p, 1, 1, 0, 1;\n}"
    : "+f"(d[0]),"+f"(d[1]),"+f"(d[2]),"+f"(d[3]),"+f"(d[4]),"+f"(d[5]),"+f"(d[6]),"+f"(d[7]),"+f"(d[8]),"+f"(d[9]),"+f"(d[10]),"+f"(d[11]),"+f"(d[12]),"+f"(d[13]),"+f"(d[14]),"+f"(d[15]),"+f"(d[16]),"+f"(d[17]),"+f"(d[18]),"+f"(d[19]),"+f"(d[20]),"+f"(d[21]),"+f"(d[22]),"+f"(d[23]),"+f"(d[24]),"+f"(d[25]),"+f"(d[26]),"+f"(d[27]),"+f"(d[28]),"+f"(d[29]),"+f"(d[30]),"+f"(d[31])
    : "l"(ad), "l"(bd));
  }
}
template<int SD> __device__ __forceinline__ void wg_rs72(float* d, const uint32_t* a, uint64_t bd) {
  if constexpr (SD) {
    asm volatile("{\n.reg .pred p;\nsetp.eq.b32 p, 0, 0;\n"
    "wgmma.mma_async.sync.aligned.m64n72k16.f32.bf16.bf16 {%0,%1,%2,%3,%4,%5,%6,%7,%8,%9,%10,%11,%12,%13,%14,%15,%16,%17,%18,%19,%20,%21,%22,%23,%24,%25,%26,%27,%28,%29,%30,%31,%32,%33,%34,%35}, {%36,%37,%38,%39}, %40, p, 1, 1, 1;\n}"
    : "+f"(d[0]),"+f"(d[1]),"+f"(d[2]),"+f"(d[3]),"+f"(d[4]),"+f"(d[5]),"+f"(d[6]),"+f"(d[7]),"+f"(d[8]),"+f"(d[9]),"+f"(d[10]),"+f"(d[11]),"+f"(d[12]),"+f"(d[13]),"+f"(d[14]),"+f"(d[15]),"+f"(d[16]),"+f"(d[17]),"+f"(d[18]),"+f"(d[19]),"+f"(d[20]),"+f"(d[21]),"+f"(d[22]),"+f"(d[23]),"+f"(d[24]),"+f"(d[25]),"+f"(d[26]),"+f"(d[27]),"+f"(d[28]),"+f"(d[29]),"+f"(d[30]),"+f"(d[31]),"+f"(d[32]),"+f"(d[33]),"+f"(d[34]),"+f"(d[35])
    : "r"(a[0]),"r"(a[1]),"r"(a[2]),"r"(a[3]), "l"(bd));
  } else {
    asm volatile("{\n.reg .pred p;\nsetp.ne.b32 p, 0, 0;\n"
    "wgmma.mma_async.sync.aligned.m64n72k16.f32.bf16.bf16 {%0,%1,%2,%3,%4,%5,%6,%7,%8,%9,%10,%11,%12,%13,%14,%15,%16,%17,%18,%19,%20,%21,%22,%23,%24,%25,%26,%27,%28,%29,%30,%31,%32,%33,%34,%35}, {%36,%37,%38,%39}, %40, p, 1, 1, 1;\n}"
    : "+f"(d[0]),"+f"(d[1]),"+f"(d[2]),"+f"(d[3]),"+f"(d[4]),"+f"(d[5]),"+f"(d[6]),"+f"(d[7]),"+f"(d[8]),"+f"(d[9]),"+f"(d[10]),"+f"(d[11]),"+f"(d[12]),"+f"(d[13]),"+f"(d[14]),"+f"(d[15]),"+f"(d[16]),"+f"(d[17]),"+f"(d[18]),"+f"(d[19]),"+f"(d[20]),"+f"(d[21]),"+f"(d[22]),"+f"(d[23]),"+f"(d[24]),"+f"(d[25]),"+f"(d[26]),"+f"(d[27]),"+f"(d[28]),"+f"(d[29]),"+f"(d[30]),"+f"(d[31]),"+f"(d[32]),"+f"(d[33]),"+f"(d[34]),"+f"(d[35])
    : "r"(a[0]),"r"(a[1]),"r"(a[2]),"r"(a[3]), "l"(bd));
  }
}
template<int SD> __device__ __forceinline__ void wg_ss72(float* d, uint64_t ad, uint64_t bd) {
  if constexpr (SD) {
    asm volatile("{\n.reg .pred p;\nsetp.eq.b32 p, 0, 0;\n"
    "wgmma.mma_async.sync.aligned.m64n72k16.f32.bf16.bf16 {%0,%1,%2,%3,%4,%5,%6,%7,%8,%9,%10,%11,%12,%13,%14,%15,%16,%17,%18,%19,%20,%21,%22,%23,%24,%25,%26,%27,%28,%29,%30,%31,%32,%33,%34,%35}, %36, %37, p, 1, 1, 0, 1;\n}"
    : "+f"(d[0]),"+f"(d[1]),"+f"(d[2]),"+f"(d[3]),"+f"(d[4]),"+f"(d[5]),"+f"(d[6]),"+f"(d[7]),"+f"(d[8]),"+f"(d[9]),"+f"(d[10]),"+f"(d[11]),"+f"(d[12]),"+f"(d[13]),"+f"(d[14]),"+f"(d[15]),"+f"(d[16]),"+f"(d[17]),"+f"(d[18]),"+f"(d[19]),"+f"(d[20]),"+f"(d[21]),"+f"(d[22]),"+f"(d[23]),"+f"(d[24]),"+f"(d[25]),"+f"(d[26]),"+f"(d[27]),"+f"(d[28]),"+f"(d[29]),"+f"(d[30]),"+f"(d[31]),"+f"(d[32]),"+f"(d[33]),"+f"(d[34]),"+f"(d[35])
    : "l"(ad), "l"(bd));
  } else {
    asm volatile("{\n.reg .pred p;\nsetp.ne.b32 p, 0, 0;\n"
    "wgmma.mma_async.sync.aligned.m64n72k16.f32.bf16.bf16 {%0,%1,%2,%3,%4,%5,%6,%7,%8,%9,%10,%11,%12,%13,%14,%15,%16,%17,%18,%19,%20,%21,%22,%23,%24,%25,%26,%27,%28,%29,%30,%31,%32,%33,%34,%35}, %36, %37, p, 1, 1, 0, 1;\n}"
    : "+f"(d[0]),"+f"(d[1]),"+f"(d[2]),"+f"(d[3]),"+f"(d[4]),"+f"(d[5]),"+f"(d[6]),"+f"(d[7]),"+f"(d[8]),"+f"(d[9]),"+f"(d[10]),"+f"(d[11]),"+f"(d[12]),"+f"(d[13]),"+f"(d[14]),"+f"(d[15]),"+f"(d[16]),"+f"(d[17]),"+f"(d[18]),"+f"(d[19]),"+f"(d[20]),"+f"(d[21]),"+f"(d[22]),"+f"(d[23]),"+f"(d[24]),"+f"(d[25]),"+f"(d[26]),"+f"(d[27]),"+f"(d[28]),"+f"(d[29]),"+f"(d[30]),"+f"(d[31]),"+f"(d[32]),"+f"(d[33]),"+f"(d[34]),"+f"(d[35])
    : "l"(ad), "l"(bd));
  }
}
template<int SD> __device__ __forceinline__ void wg_tt64(float* d, uint64_t ad, uint64_t bd) {
  if constexpr (SD) {
    asm volatile("{\n.reg .pred p;\nsetp.eq.b32 p, 0, 0;\n"
    "wgmma.mma_async.sync.aligned.m64n64k16.f32.bf16.bf16 {%0,%1,%2,%3,%4,%5,%6,%7,%8,%9,%10,%11,%12,%13,%14,%15,%16,%17,%18,%19,%20,%21,%22,%23,%24,%25,%26,%27,%28,%29,%30,%31}, %32, %33, p, 1, 1, 1, 1;\n}"
    : "+f"(d[0]),"+f"(d[1]),"+f"(d[2]),"+f"(d[3]),"+f"(d[4]),"+f"(d[5]),"+f"(d[6]),"+f"(d[7]),"+f"(d[8]),"+f"(d[9]),"+f"(d[10]),"+f"(d[11]),"+f"(d[12]),"+f"(d[13]),"+f"(d[14]),"+f"(d[15]),"+f"(d[16]),"+f"(d[17]),"+f"(d[18]),"+f"(d[19]),"+f"(d[20]),"+f"(d[21]),"+f"(d[22]),"+f"(d[23]),"+f"(d[24]),"+f"(d[25]),"+f"(d[26]),"+f"(d[27]),"+f"(d[28]),"+f"(d[29]),"+f"(d[30]),"+f"(d[31])
    : "l"(ad), "l"(bd));
  } else {
    asm volatile("{\n.reg .pred p;\nsetp.ne.b32 p, 0, 0;\n"
    "wgmma.mma_async.sync.aligned.m64n64k16.f32.bf16.bf16 {%0,%1,%2,%3,%4,%5,%6,%7,%8,%9,%10,%11,%12,%13,%14,%15,%16,%17,%18,%19,%20,%21,%22,%23,%24,%25,%26,%27,%28,%29,%30,%31}, %32, %33, p, 1, 1, 1, 1;\n}"
    : "+f"(d[0]),"+f"(d[1]),"+f"(d[2]),"+f"(d[3]),"+f"(d[4]),"+f"(d[5]),"+f"(d[6]),"+f"(d[7]),"+f"(d[8]),"+f"(d[9]),"+f"(d[10]),"+f"(d[11]),"+f"(d[12]),"+f"(d[13]),"+f"(d[14]),"+f"(d[15]),"+f"(d[16]),"+f"(d[17]),"+f"(d[18]),"+f"(d[19]),"+f"(d[20]),"+f"(d[21]),"+f"(d[22]),"+f"(d[23]),"+f"(d[24]),"+f"(d[25]),"+f"(d[26]),"+f"(d[27]),"+f"(d[28]),"+f"(d[29]),"+f"(d[30]),"+f"(d[31])
    : "l"(ad), "l"(bd));
  }
}

template<int V> struct IC { static constexpr int v = V; };
template<int I, int N, class F> __device__ __forceinline__ void sfor(F&& f) {
    if constexpr (I < N) { f(IC<I>{}); sfor<I + 1, N>(f); }
}

enum { K_QKV = 0, K_H = 1 };

struct Ctx {
    uint32_t tph;
    uint32_t tid;
    bool pf = false;
};
__device__ __forceinline__ void release_slot(const Ctx& c, int slot) { if ((c.tid & 31) == 0) mbar_arrive(bar(B_EMPTY + slot)); }

__device__ __forceinline__ void turn_wait(const Ctx& c) { asm volatile("bar.sync %0, 256;" :: "r"(4 + (c.tid >> 7)) : "memory"); }
__device__ __forceinline__ void turn_pass(const Ctx& c) { asm volatile("bar.arrive %0, 256;" :: "r"(5 - (c.tid >> 7)) : "memory"); }

template<int KIND, class PART, class POST>
__device__ __forceinline__ void run_step(Ctx& c, float* acc, const uint32_t* a, PART&& part, POST&& post) {
    constexpr int NST = (KIND == K_QKV) ? 6 : 3;
    constexpr int KPS = 36 / NST;
    sfor<0, NST>([&](auto ST) {
        constexpr int st = decltype(ST)::v;
        constexpr int slot = st % 3;
        mbar_wait(bar(B_FULL + slot), c.tph);
        uint32_t wgo = 0;
        if constexpr (st == NST - 1) wgo = (c.tid >> 7) * 512;
        if (KIND == K_H && c.pf) prof(44 + st * 5);
        turn_wait(c);
        if (KIND == K_H && c.pf) prof(45 + st * 5);
        wg_fence();
        sfor<0, KPS>([&](auto KK) {
            constexpr int kk = decltype(KK)::v;
            constexpr int ks = st * KPS + kk;
            constexpr int SD = ks ? 1 : 0;
            if constexpr (KIND == K_QKV) {
                constexpr uint64_t bd = mkdesc(RING + slot * SLOT + kk * 2048, 12288, 1024, 1);
                if constexpr (ks < 32) wg_rs72<SD>(acc, a + ks * 4, bd);
                else wg_ss72<SD>(acc, mkdesc(XB + (ks - 32) * 32, 16, 1024, 1) + wgo, bd);
            } else {
                constexpr uint64_t bd = mkdesc(RING + slot * SLOT + kk * 2048, 16, 1024, 1);
                if constexpr (ks < 32) wg_rs64<SD>(acc, a + ks * 4, bd);
                else wg_ss64<SD>(acc, mkdesc(XB + (ks - 32) * 32, 16, 1024, 1) + wgo, bd);
            }
        });
        wg_commit();
        turn_pass(c);
        if (KIND == K_H && c.pf) prof(46 + st * 5);
        part(ST);
        if (KIND == K_H && c.pf) prof(47 + st * 5);
        wg_wait<0>();
        if (KIND == K_H && c.pf) prof(48 + st * 5);
        release_slot(c, slot);
        if constexpr (slot == 2) c.tph ^= 1;
        post(ST);
    });
    if constexpr (KIND == K_QKV) reg_fence<36>(acc); else reg_fence<32>(acc);
}

__device__ __forceinline__ float phi(float t) {
    float e = ex2(t * 1.4426950408889634f);
    return (t > 0.f ? t + 1.0f : e) + 1e-6f;
}
__device__ __forceinline__ float gelu_h(float hx) {
    float u = hx * fmaf(hx * hx, 0.2854192650f, 1.5957691216f);
    return fmaf(hx, tanh_ap(u), hx);
}

struct Params {
    const __nv_bfloat16* x;
    const __nv_bfloat16* wqkv;
    const __nv_bfloat16* wo;
    const __nv_bfloat16* w1;
    const __nv_bfloat16* b1;
    const __nv_bfloat16* w2;
    const __nv_bfloat16* b2;
    __nv_bfloat16* out;
};

__global__ void __launch_bounds__(384, 1)
fused_kernel(const __grid_constant__ CUtensorMap tm_x, const __grid_constant__ CUtensorMap tm_w1,
             const __grid_constant__ CUtensorMap tm_w2, const __grid_constant__ CUtensorMap tm_wo,
             const __grid_constant__ CUtensorMap tm_o, const __grid_constant__ CUtensorMap tm_qkv,
             const __grid_constant__ CUtensorMap tm_qkve, const Params p) {
    extern __shared__ __align__(1024) unsigned char smem_raw[];
    const int tid = threadIdx.x;
    const int bid = blockIdx.x;
    const bool is_main = bid < NMAIN;
    const int j = bid & 7;
    const int m = bid >> 3;

    if (tid == 0) {
        if ((uint32_t)__cvta_generic_to_shared(smem_raw) != SB) __trap();
        for (int i = 0; i < 3; i++) {
            mbar_init(bar(B_FULL + i), 1); mbar_init(bar(B_EMPTY + i), 8);
            mbar_init(bar(B_XFULL + i), 1); mbar_init(bar(B_OFULL + i), 1);
        }
        mbar_init(bar(B_KVB), is_main ? 2 : 8); mbar_init(bar(B_YRDY), 1);
        for (int i = 0; i < 4; i++) mbar_init(bar(B_OFREE + i), 8);
        asm volatile("fence.mbarrier_init.release.cluster;" ::: "memory");
        if (is_main) {
            for (int g = 0; g < 3; g++) {
                mbar_expect_tx(bar(B_XFULL + g), 49152);
                for (int kb = 3 * g; kb < 3 * g + 3; kb++) tma_2d(HA + kb * 16384, &tm_x, bar(B_XFULL + g), kb * 64, m * 128);
            }
            for (int st = 0; st < 3; st++) {
                mbar_expect_tx(bar(B_FULL + st), 96 * 144);
                tma_2d(RING + st * SLOT, &tm_qkv, bar(B_FULL + st), 576 + j * 72, st * 96);
                tma_2d(RING + st * SLOT + 12288, &tm_qkve, bar(B_FULL + st), 576 + j * 72 + 64, st * 96);
            }
        }
    }
    if (tid == 32) sts32(EPO, g_epoch[bid]);
    if (tid >= 40 && tid < 48) sts32(EVC + (tid - 40) * 4, 0);
    if (tid >= 64 && tid < 64 + 288 && is_main) {
        int i = tid - 64;
        uint32_t v = *reinterpret_cast<const uint32_t*>(p.b1 + j * 576 + 2 * i);
        sts32(B1S + 8 * i, __float_as_uint(0.5f * bf_lo(v))); sts32(B1S + 8 * i + 4, __float_as_uint(0.5f * bf_hi(v)));
    }
    if (tid >= 352) {
        int i = tid - 352;
        uint32_t v = *reinterpret_cast<const uint32_t*>(p.b2 + (is_main ? j : 8) * 64 + 2 * i);
        sts32(B2S + 8 * i, v << 16); sts32(B2S + 8 * i + 4, v & 0xffff0000u);
    }
    fence_async_smem();
    __syncthreads();
    uint32_t epoch;
    asm volatile("ld.shared.u32 %0, [%1];" : "=r"(epoch) : "r"(EPO));
    const uint32_t par = epoch & 1;

    if (tid >= 256) {
        asm volatile("setmaxnreg.dec.sync.aligned.u32 24;");
        const int hw = (tid >> 5) - 8, lane = tid & 31;
        if (hw == 0) {
            if (lane == 0) {
                uint32_t n = 0;
                if (is_main) {
                    n = 1;
                    #pragma unroll 1
                    for (int u = 3; u < 18; u++) {
                        const int st = u % 3, step = u / 6;
                        const int col = ((step == 2) ? 0 : (step + 1) * 576) + j * 72, row = (u % 6) * 96;
                        mbar_wait(bar(B_EMPTY + st), (n & 1) ^ 1);
                        mbar_expect_tx(bar(B_FULL + st), 96 * 144);
                        tma_2d(RING + st * SLOT, &tm_qkv, bar(B_FULL + st), col, row);
                        tma_2d(RING + st * SLOT + 12288, &tm_qkve, bar(B_FULL + st), col + 64, row);
                        if (st == 2) n++;
                    }
                }
                const int nsteps = is_main ? 19 : 1;
                #pragma unroll 1
                for (int s = 0; s < nsteps; s++, n++) {
                    const CUtensorMap* tm; int col, row;
                    if (!is_main) { tm = &tm_wo; col = 512; row = 0; }
                    else if (s < 9) { tm = &tm_w1; col = j * 576 + s * 64; row = 0; }
                    else if (s < 18) { tm = &tm_w2; col = (s == 9) ? 512 : (((j + s - 9) & 7) * 64); row = j * 576; }
                    else { tm = &tm_wo; col = j * 64; row = 0; }
                    #pragma unroll 1
                    for (int st = 0; st < 3; st++) {
                        mbar_wait(bar(B_EMPTY + st), (n & 1) ^ 1);
                        mbar_expect_tx(bar(B_FULL + st), SLOT);
                        tma_2d(RING + st * SLOT, tm, bar(B_FULL + st), col, row + st * 192);
                    }
                }
            }
        } else {
            if (is_main) {
                const int t = tid - 288;
                #pragma unroll 1
                for (int i = t; i < 36 * 6; i += 96) {
                    int r = i / 6, q = i - r * 6;
                    prefetch_l2(reinterpret_cast<const char*>(p.wqkv) + (36 * m + r) * 3456 + (q >> 1) * 1152 + j * 144 + (q & 1) * 128);
                }
                __nanosleep(PF1_NS);
                #pragma unroll 1
                for (int i = t; i < 36 * 9; i += 96) {
                    int r = i / 9, q = i - r * 9;
                    prefetch_l2(reinterpret_cast<const char*>(p.w1) + (36 * m + r) * 9216 + j * 1152 + q * 128);
                    __nanosleep(PF3_NS);
                }
                __nanosleep(PF2_NS);
                #pragma unroll 1
                for (int i = t; i < 36 * 9; i += 96)
                    prefetch_l2(reinterpret_cast<const char*>(p.w2) + (576 * j + 36 * m) * 1152 + i * 128);
                if (t < 41 && (bid * 41 + t) < 5184) prefetch_l2(reinterpret_cast<const char*>(p.wo) + (bid * 41 + t) * 128);
                if (hw != 2) {
                    if (lane == 0) wait_cnt(cnt_kv(j), (epoch + 1) * 16);
                    __syncwarp();
                    const float4* kv = reinterpret_cast<const float4*>(g_kv + (par * 8 + j) * 1440);
                    #pragma unroll 2
                    for (int i = lane + (hw == 1 ? 0 : 32); i < 360; i += 64) {
                        const float4 v = __ldcg(kv + i);
                        const int d = i / 5, e = (i - d * 5) * 4, h = d / 18;
                        const uint32_t base = KVB + (d >> 3) * 128 + (d & 7) * 16;
                        const int n0 = 8 + h * 18 + e;
                        sts32(base + (n0 >> 3) * 1280 + (n0 & 7) * 2, pack_bf16(v.x, v.y));
                        if (e < 16) sts32(base + ((n0 + 2) >> 3) * 1280 + ((n0 + 2) & 7) * 2, pack_bf16(v.z, v.w));
                        else asm volatile("st.shared.u16 [%0], %1;" :: "r"(base + h * 2), "h"((unsigned short)pack_bf16(v.z, 0.f)) : "memory");
                    }
                    fence_async_smem();
                    __syncwarp();
                    if (lane == 0) mbar_arrive(bar(B_KVB));
                }
            }
            if (hw == 1) {
                if (lane == 0) {
                    const int nit = is_main ? 1 : 4;
                    for (int it = 0; it < nit; it++) {
                        const int mt = is_main ? m : ((bid - NMAIN) * 4 + it);
                        const bool wf = is_main || it > 0;
                        const uint32_t fp = is_main ? 0 : ((it - 1) & 1);
                        wait_cnt(cnt_o(mt), (epoch + 1) * 8);
                        fence_async_all();
                        #pragma unroll 1
                        for (int kb = 0; kb < 9; kb++) {
                            const int g = kb / 3;
                            if (kb == 3 * g || kb == 8) { if (wf) mbar_wait(bar(B_OFREE + (kb == 8 ? 3 : g)), fp); }
                            if (kb == 3 * g) mbar_expect_tx(bar(B_OFULL + g), 49152);
                            tma_2d(HA + kb * 16384, &tm_o, bar(B_OFULL + g), kb * 64, mt * 128);
                        }
                    }
                    if (is_main) { wait_cnt(cnt_y(m, j), (epoch + 1) * 7); mbar_arrive(bar(B_YRDY)); }
                }
            } else if (hw == 2) {
                if (!is_main) {
                    if (lane == 0) {
                        #pragma unroll 1
                        for (int it = 0; it < 4; it++) {
                            if (it > 0) mbar_wait(bar(B_KVB), (it - 1) & 1);
                            wait_cnt(cnt_y((bid - NMAIN) * 4 + it, 8), (epoch + 1) * 8);
                            mbar_arrive(bar(B_YRDY));
                        }
                    }
                } else {
                    #pragma unroll 1
                    for (int e = 0; e < 10; e++) {
                        int spin = 0;
                        while (true) {
                            uint32_t v;
                            asm volatile("ld.acquire.cta.shared.u32 %0, [%1];" : "=r"(v) : "r"(EVC + (lane & 7) * 4) : "memory");
                            if (__all_sync(0xffffffffu, v > (uint32_t)e)) break;
                            if (++spin > 20000000) __trap();
                            __nanosleep(20);
                        }
                        if (lane == 0) {
                            unsigned int* cp = (e == 0) ? cnt_kv(j) : (e == 1) ? cnt_o(m) : cnt_y(m, e == 2 ? 8 : ((j + e - 2) & 7));
                            if (e == 1) fence_async_all();
                            __threadfence();
                            asm volatile("red.relaxed.gpu.global.add.u32 [%0], 1;" :: "l"(cp) : "memory");
                        }
                        __syncwarp();
                    }
                }
            } else {
                {
                    const int t0 = is_main ? (m * 9 + j) : ((bid - NMAIN) * 4 * 9 + 8);
                    const int nt = is_main ? 1 : 4;
                    for (int t = 0; t < nt; t++) {
                        uint4* z = reinterpret_cast<uint4*>(g_yacc + (size_t)((par ^ 1) * 144 + t0 + t * 9) * YT_BYTES);
                        for (int i = lane; i < YT_BYTES / 16; i += 32) z[i] = make_uint4(0, 0, 0, 0);
                    }
                    if (is_main && m == 0) {
                        float* z = g_kv + ((par ^ 1) * 8 + j) * 1440;
                        for (int i = lane; i < 1440; i += 32) z[i] = 0.f;
                    }
                }
            }
        }
    } else {
        asm volatile("setmaxnreg.inc.sync.aligned.u32 240;");
        prof(0);
        Ctx c; c.tph = 0; c.tid = v_tid();
        float hc[32], pv[36];
        if (tid >> 7) turn_pass(c);
        auto event = [&](uint32_t ev) {
            __syncwarp();
            if (((c.tid & 31) == 0)) asm volatile("st.release.cta.shared.u32 [%0], %1;" :: "r"(EVC + (c.tid >> 3)), "r"(ev) : "memory");
        };
        auto warp_arrive = [&](uint32_t b) { __syncwarp(); if (((c.tid & 31) == 0)) mbar_arrive(b); };

        if (is_main) {
            uint32_t a[128];
            float rs0, rs1;
            uint32_t m00, m11;
            auto lrow_off = [&]() { uint32_t t_ = c.tid; return HA + ((t_ >> 5) * 16 + (t_ & 15)) * 128 + ((((t_ >> 4) & 1) ^ (t_ & 7)) << 4); };
            auto tail_off = [&]() { uint32_t t_ = c.tid, g = (t_ >> 2) & 7; return XB + ((t_ >> 5) * 16 + g) * 128 + (g << 4) + (t_ & 3) * 4; };
            {
                uint32_t tl[16];
                const uint32_t lrow = lrow_off();
                float cs[2][4] = {{0.f, 0.f, 0.f, 0.f}, {0.f, 0.f, 0.f, 0.f}};
                sfor<0, 36>([&](auto KS) {
                    constexpr int ks = decltype(KS)::v;
                    if constexpr (ks % 12 == 0) mbar_wait(bar(B_XFULL + ks / 12), 0);
                    uint32_t* dst = (ks < 32) ? (a + (ks & 31) * 4) : (tl + (ks & 3) * 4);
                    ldsm4((lrow ^ ((ks % 4) << 5)) + (ks / 4) * 16384, dst);
                    mma_ones(cs[ks & 1], dst);
                });
                prof(2);
                float mean0 = (cs[0][0] + cs[1][0]) * (1.0f / 576.0f), mean1 = (cs[0][2] + cs[1][2]) * (1.0f / 576.0f);
                m00 = pack_bf16(mean0, mean0); m11 = pack_bf16(mean1, mean1);
                rs0 = mean0 - bf_lo(m00); rs1 = mean1 - bf_lo(m11);
                rs0 = -144.0f * rs0 * rs0; rs1 = -144.0f * rs1 * rs1;
                const uint32_t tb = tail_off();
                #pragma unroll
                for (int i = 0; i < 16; i++) {
                    const uint32_t w = sub_bf16x2(tl[i], (i & 1) ? m11 : m00);
                    sts32((tb ^ ((i >> 1) << 4)) + (i & 1) * 1024, w);
                    float lo = bf_lo(w), hi = bf_hi(w);
                    if (i & 1) rs1 = fmaf(lo, lo, fmaf(hi, hi, rs1)); else rs0 = fmaf(lo, lo, fmaf(hi, hi, rs0));
                }
                fence_async_smem();
                #pragma unroll
                for (int i = 0; i < 128; i++) a[i] = sub_bf16x2(a[i], (i & 1) ? m11 : m00);
                named_bar(2 + (tid >> 7), 128);
            }
            prof(3);
            auto cm_off = [&]() { uint32_t t_ = c.tid; return (t_ >> 5) * 256 + (t_ & 31) * 4; };
            {
                float qc[36];
                #pragma unroll
                for (int i = 0; i < 36; i++) { qc[i] = 0.f; pv[i] = 0.f; }
                #pragma unroll 1
                for (int s = 0; s < 3; s++) {
                    run_step<K_QKV>(c, qc, a, [&](auto ST) {
                        constexpr int st = decltype(ST)::v;
                        if (s == 0) {
                            const uint32_t lrow = lrow_off();
                            sfor<(st * 32) / 6, ((st + 1) * 32) / 6>([&](auto I) {
                                constexpr int ks = decltype(I)::v;
                                uint32_t v[4];
                                ldsm4((lrow ^ ((ks % 4) << 5)) + (ks / 4) * 16384, v);
                                #pragma unroll
                                for (int r = 0; r < 4; r++) {
                                    uint32_t w = sub_bf16x2(v[r], (r & 1) ? m11 : m00);
                                    float lo = bf_lo(w), hi = bf_hi(w);
                                    if (r & 1) rs1 = fmaf(lo, lo, fmaf(hi, hi, rs1)); else rs0 = fmaf(lo, lo, fmaf(hi, hi, rs0));
                                }
                            });
                            if constexpr (st == 5) {
                                rs0 += __shfl_xor_sync(0xffffffffu, rs0, 1); rs1 += __shfl_xor_sync(0xffffffffu, rs1, 1);
                                rs0 += __shfl_xor_sync(0xffffffffu, rs0, 2); rs1 += __shfl_xor_sync(0xffffffffu, rs1, 2);
                                rs0 = rsqrtf(fmaxf(rs0 * (1.0f / 576.0f), 0.f) + 1e-5f);
                                rs1 = rsqrtf(fmaxf(rs1 * (1.0f / 576.0f), 0.f) + 1e-5f);
                                named_bar(1, 256);
                            }
                        } else {
                            const uint32_t cm = cm_off();
                            sfor<0, 9>([&](auto B) {
                                constexpr int b = decltype(B)::v;
                                if constexpr ((b * 6) / 9 == st) {
                                    const float v0 = pv[4 * b] * rs0, v1 = pv[4 * b + 1] * rs0, v2 = pv[4 * b + 2] * rs1, v3 = pv[4 * b + 3] * rs1;
                                    if (s == 1) {
                                        sts32(PKT + b * 2048 + cm, pack_bf16(phi(v0), phi(v1)));
                                        sts32(PKT + b * 2048 + cm + 128, pack_bf16(phi(v2), phi(v3)));
                                    } else {
                                        const uint32_t w0 = pack_bf16(v0, v1), w1 = pack_bf16(v2, v3);
                                        if constexpr (b <= 4) { sts32(VT + b * 2048 + cm, w0); sts32(VT + b * 2048 + cm + 128, w1); }
                                        if constexpr (b >= 4) { sts32(VT + (b + 2) * 2048 + cm, w0); sts32(VT + (b + 2) * 2048 + cm + 128, w1); }
                                        if constexpr (b == 0) {
                                            const uint32_t one = (cm & 12) ? 0u : 0x00003F80u;
                                            sts32(VT + 5 * 2048 + cm, one); sts32(VT + 5 * 2048 + cm + 128, one);
                                        }
                                        if constexpr (b == 8) {
                                            const uint32_t z = KVB + c.tid * 16;
                                            sts128(z, 0, 0, 0, 0); sts128(z + 4096, 0, 0, 0, 0); sts128(z + 8192, 0, 0, 0, 0);
                                            if (z < KVB + 512) sts128(z + 12288, 0, 0, 0, 0);
                                            fence_async_smem();
                                        }
                                    }
                                }
                            });
                        }
                    }, [](auto) {});
                    reg_copy<36>(pv, qc);
                    prof(4 + s);
                }
            }
            {
                #pragma unroll
                for (int i = 0; i < 32; i++) hc[i] = 0.f;
                named_bar(1, 256);
                const uint32_t wgo = ((c.tid >> 7) * 512);
                wg_fence();
                sfor<0, 8>([&](auto KS) {
                    constexpr int ks = decltype(KS)::v;
                    wg_tt64<(ks ? 1 : 0)>(hc, mkdesc(PKT + ks * 256, 128, 2048, 0) + wgo,
                                          mkdesc(VT + ks * 256, 128, 2048, 0) + wgo + (wgo >> 2));
                });
                wg_commit();
                const uint32_t pq = PQT + cm_off() + ((c.tid >> 7) * 512) * 16;
                sfor<0, 9>([&](auto B) {
                    constexpr int b = decltype(B)::v;
                    sts32(pq + b * 1024, pack_bf16(phi(pv[4 * b] * rs0), phi(pv[4 * b + 1] * rs0)));
                    sts32(pq + b * 1024 + 128, pack_bf16(phi(pv[4 * b + 2] * rs1), phi(pv[4 * b + 3] * rs1)));
                });
                fence_async_smem();
                wg_wait<0>();
                reg_fence<32>(hc);
                reg_copy<24>(pv, hc);
            }
            prof(7);
            rs0 *= 0.5f; rs1 *= 0.5f;
            auto gelun = [&](auto B0, auto B1, uint32_t bofs, uint32_t* w) {
                constexpr int b0 = decltype(B0)::v, nb = decltype(B1)::v - b0;
                float2 bv[nb];
                #pragma unroll
                for (int i = 0; i < nb; i++) bv[i] = lds64f(bofs + (b0 + i) * 32);
                #pragma unroll
                for (int i = 0; i < nb; i++) {
                    const int b = b0 + i;
                    w[2 * i]     = pack_bf16(gelu_h(fmaf(pv[4 * b], rs0, bv[i].x)), gelu_h(fmaf(pv[4 * b + 1], rs0, bv[i].y)));
                    w[2 * i + 1] = pack_bf16(gelu_h(fmaf(pv[4 * b + 2], rs1, bv[i].x)), gelu_h(fmaf(pv[4 * b + 3], rs1, bv[i].y)));
                }
            };
            auto spill_off = [&]() { uint32_t t_ = c.tid; return HA + (t_ >> 7) * 8192 + (t_ & 127) * 8; };
            auto reload = [&](auto S0, auto S1) {
                const uint32_t spill = spill_off();
                sfor<decltype(S0)::v * 8, decltype(S1)::v * 8>([&](auto Q) {
                    constexpr int q = decltype(Q)::v;
                    lds64(spill + (q / 8) * 16384 + (q % 8) * 1024, a + q * 2);
                });
            };
            #pragma unroll 1
            for (int idx = 0; idx < 18; idx++) {
                run_step<K_H>(c, hc, a, [&](auto ST) {
                    constexpr int st = decltype(ST)::v;
                    if (idx >= 10) {
                        if constexpr (st < 2) {
                            const uint32_t b_ = v_bid();
                            const uint32_t chunk = (idx == 10) ? 8 : ((b_ + idx - 10) & 7);
                            unsigned char* yp = g_yacc + ((v_epoch() & 1) * 144 + (b_ >> 3) * 9 + chunk) * YT_BYTES + c.tid * 16;
                            sfor<2 * st, 2 * st + 2>([&](auto Q) {
                                constexpr int q = decltype(Q)::v;
                                asm volatile("red.global.add.noftz.v4.bf16x2 [%0], {%1,%2,%3,%4};" :: "l"(yp + q * 4096),
                                             "r"(pack_bf16(pv[8 * q], pv[8 * q + 1])), "r"(pack_bf16(pv[8 * q + 2], pv[8 * q + 3])),
                                             "r"(pack_bf16(pv[8 * q + 4], pv[8 * q + 5])), "r"(pack_bf16(pv[8 * q + 6], pv[8 * q + 7])) : "memory");
                            });
                            if constexpr (st == 1) event(idx - 7);
                        }
                    } else if (idx >= 1) {
                        const uint32_t bofs = B1S + (idx - 1) * 256 + (c.tid & 3) * 8;
                        if (idx < 9) {
                            if constexpr (st == 0) { if (idx == OSTEP_AT + 1) event(2); }
                            const uint32_t spill = spill_off() + (idx - 1) * 16384;
                            constexpr int b0 = st * 3, b1 = (st == 2 ? 8 : st * 3 + 3);
                            uint32_t w[6];
                            gelun(IC<b0>{}, IC<b1>{}, bofs, w);
                            #pragma unroll
                            for (int b = b0; b < b1; b++) sts64(spill + b * 1024, w[2 * (b - b0)], w[2 * (b - b0) + 1]);
                        } else {
                            if constexpr (st < 2) {
                                const uint32_t tb = tail_off();
                                uint32_t w[8];
                                gelun(IC<st * 4>{}, IC<st * 4 + 4>{}, bofs, w);
                                #pragma unroll
                                for (int i = 0; i < 4; i++) { sts32(tb ^ ((st * 4 + i) << 4), w[2 * i]); sts32((tb ^ ((st * 4 + i) << 4)) + 1024, w[2 * i + 1]); }
                            }
                            if constexpr (st == 1) { fence_async_smem(); named_bar(2 + (c.tid >> 7), 128); }
                        }
                    } else {
                        if constexpr (st < 2) {
                            constexpr int hf = st;
                            const int t_ = c.tid, wg = t_ >> 7, t = t_ & 3;
                            float* dst = g_kv + ((v_epoch() & 1) * 8 + (v_bid() & 7)) * 1440;
                            const int d = wg * 32 + ((t_ >> 5) & 3) * 16 + ((t_ >> 2) & 7) + hf * 8;
                            const bool dv = wg ? (d >= 36 && d < 72) : (d < 36);
                            const int e00 = wg * 24 + 2 * t - (d / 18) * 18;
                            float* dp = dst + d * 20 + e00;
                            #pragma unroll
                            for (int i = 0; i < 6; i++) {
                                const int e = e00 + i * 8;
                                const bool blk = wg ? (i >= 1) : (i <= 4);
                                if (dv && blk && e >= 0 && e < 18)
                                    asm volatile("red.global.add.v2.f32 [%0], {%1,%2};" :: "l"(dp + i * 8), "f"(pv[4 * i + 2 * hf]), "f"(pv[4 * i + 2 * hf + 1]) : "memory");
                            }
                            if (dv && t == 0) atomicAdd(dst + d * 20 + 18, wg ? pv[2 * hf] : pv[20 + 2 * hf]);
                            if constexpr (st == 1) event(1);
                        }
                    }
                }, [&](auto ST) {
                    constexpr int st = decltype(ST)::v;
                    if (idx == 8) {
                        reload(IC<3 * st>{}, IC<(st == 2 ? 8 : 3 * st + 3)>{});
                        warp_arrive(bar(B_OFREE + st));
                    }
                });
                reg_copy<32>(pv, hc);
                prof(8 + idx);
                if (idx == OSTEP_AT) {
                    mbar_wait(bar(B_KVB), 0);
                    prof(34);
                    const uint32_t pqo = (c.tid >> 7) * 576;
                    const int t_ = c.tid, b_ = v_bid(), t = t_ & 3, l4 = t_ & 28;
                    __nv_bfloat16* op = g_o + (size_t)((b_ >> 3) * 128 + (t_ >> 5) * 16 + ((t_ >> 2) & 7)) * DM + (b_ & 7) * 72 + 2 * t;
                    float r3[2];
                    sfor<0, 2>([&](auto PS) {
                        constexpr int ps = decltype(PS)::v;
                        wg_fence();
                        sfor<0, 5>([&](auto KS) {
                            constexpr int ks = decltype(KS)::v;
                            wg_ss64<(ks ? 1 : 0)>(hc, mkdesc(PQT + ks * 2048, ks == 4 ? 0 : 1024, 128, 0) + pqo, mkdesc(KVB + ps * 8 * 1280 + ks * 256, 128, 1280, 0));
                        });
                        wg_commit();
                        wg_wait<0>();
                        reg_fence<32>(hc);
                        #pragma unroll
                        for (int hf = 0; hf < 2; hf++) {
                            if constexpr (ps == 0) {
                                float r[4];
                                r[0] = rcp(__shfl_sync(0xffffffffu, hc[2 * hf], l4) + 1e-6f);
                                r[1] = rcp(__shfl_sync(0xffffffffu, hc[1 + 2 * hf], l4) + 1e-6f);
                                r[2] = rcp(__shfl_sync(0xffffffffu, hc[2 * hf], l4 + 1) + 1e-6f);
                                r[3] = rcp(__shfl_sync(0xffffffffu, hc[1 + 2 * hf], l4 + 1) + 1e-6f);
                                r3[hf] = r[3];
                                #pragma unroll
                                for (int i = 0; i < 7; i++) {
                                    float rr = (i < 2) ? r[0] : (i == 2) ? (t < 1 ? r[0] : r[1]) : (i == 3) ? r[1] : (i == 4) ? (t < 2 ? r[1] : r[2])
                                             : (i == 5) ? r[2] : (t < 3 ? r[2] : r[3]);
                                    *reinterpret_cast<uint32_t*>(op + hf * 8 * DM + i * 8) = pack_bf16(hc[4 * i + 4 + 2 * hf] * rr, hc[4 * i + 5 + 2 * hf] * rr);
                                }
                            } else {
                                #pragma unroll
                                for (int i = 0; i < 2; i++)
                                    *reinterpret_cast<uint32_t*>(op + hf * 8 * DM + 56 + i * 8) = pack_bf16(hc[4 * i + 2 * hf] * r3[hf], hc[4 * i + 1 + 2 * hf] * r3[hf]);
                            }
                        }
                    });
                }
            }
            warp_arrive(bar(B_OFREE + 3));
        }
        const int b2_ = v_bid(), t2_ = c.tid;
        uint32_t xr[16];
        uint4 yv[4];
        auto load_x = [&](size_t eoff) {
            #pragma unroll
            for (int i = 0; i < 8; i++) {
                xr[2 * i] = __ldg(reinterpret_cast<const uint32_t*>(p.x + eoff + i * 8));
                xr[2 * i + 1] = __ldg(reinterpret_cast<const uint32_t*>(p.x + eoff + 8 * DM + i * 8));
            }
        };
        auto load_y = [&](int tile) {
            const unsigned char* yp = g_yacc + ((v_epoch() & 1) * 144 + tile) * YT_BYTES + t2_ * 16;
            #pragma unroll
            for (int q = 0; q < 4; q++) yv[q] = __ldcg(reinterpret_cast<const uint4*>(yp + q * 4096));
        };
        auto gate = [&]() {
            #pragma unroll
            for (int q = 0; q < 4; q++) {
                const uint4 u = yv[q];
                pv[8 * q] += bf_lo(u.x); pv[8 * q + 1] += bf_hi(u.x); pv[8 * q + 2] += bf_lo(u.y); pv[8 * q + 3] += bf_hi(u.y);
                pv[8 * q + 4] += bf_lo(u.z); pv[8 * q + 5] += bf_hi(u.z); pv[8 * q + 6] += bf_lo(u.w); pv[8 * q + 7] += bf_hi(u.w);
            }
            #pragma unroll
            for (int i = 0; i < 32; i++) pv[i] = pv[i] * rcp(1.0f + ex2(pv[i] * -1.4426950408889634f));
        };
        auto add_b2 = [&]() {
            #pragma unroll
            for (int b = 0; b < 8; b++) {
                float2 bv = lds64f(B2S + b * 32 + (t2_ & 3) * 8);
                pv[4 * b] += bv.x; pv[4 * b + 1] += bv.y; pv[4 * b + 2] += bv.x; pv[4 * b + 3] += bv.y;
            }
        };
        auto store_out = [&](size_t eoff) {
            #pragma unroll
            for (int b = 0; b < 8; b++) {
                *reinterpret_cast<uint32_t*>(p.out + eoff + b * 8) =
                    pack_bf16(fmaf(hc[4 * b], pv[4 * b], bf_lo(xr[2 * b])), fmaf(hc[4 * b + 1], pv[4 * b + 1], bf_hi(xr[2 * b])));
                *reinterpret_cast<uint32_t*>(p.out + eoff + 8 * DM + b * 8) =
                    pack_bf16(fmaf(hc[4 * b + 2], pv[4 * b + 2], bf_lo(xr[2 * b + 1])), fmaf(hc[4 * b + 3], pv[4 * b + 3], bf_hi(xr[2 * b + 1])));
            }
        };
        const int rowoff = (t2_ >> 5) * 16 + ((t2_ >> 2) & 7);
        const bool mainf = b2_ < NMAIN;
        uint32_t sv[16];
        if (!mainf) {
            #pragma unroll
            for (int i = 0; i < 32; i++) hc[i] = 0.f;
        }
        #pragma unroll
        for (int i = 0; i < 16; i++) sv[i] = 0;
        #pragma unroll 1
        for (int job = mainf ? 4 : 0; job < 5; job++) {
            const bool do_s = mainf || job < 4, do_f = job >= 1;
            const int mt = mainf ? (b2_ >> 3) : ((b2_ - NMAIN) * 4 + job - 1);
            const int ch = mainf ? (b2_ & 7) : 8;
            const size_t eoff = (size_t)(mt * 128 + rowoff) * DM + ch * 64 + 2 * (t2_ & 3);
            sfor<0, 3>([&](auto ST) {
                constexpr int st = decltype(ST)::v;
                if (do_s) {
                    mbar_wait(bar(B_FULL + st), c.tph);
                    mbar_wait(bar(B_OFULL + st), job & 1);
                }
                if (!mainf && job < 5) prof(44 + job * 3 + st);
                const uint32_t wgo = ((c.tid >> 7) * 512);
                turn_wait(c);
                wg_fence();
                sfor<0, 12>([&](auto KK) {
                    constexpr int kk = decltype(KK)::v;
                    constexpr int ks = st * 12 + kk;
                    wg_ss64<(ks ? 1 : 0)>(hc, mkdesc(HA + (ks / 4) * 16384 + (ks % 4) * 32, 16, 1024, 1) + wgo,
                                          mkdesc(RING + st * SLOT + kk * 2048, 16, 1024, 1));
                });
                wg_commit();
                if (st < 2 || job < 4 || wgo == 0) turn_pass(c);
                if (do_f) {
                    if constexpr (st == 0) {
                        load_x(eoff);
                        if (!mainf) {
                            #pragma unroll
                            for (int i = 0; i < 32; i++) pv[i] = 0.f;
                        }
                        add_b2();
                    } else if constexpr (st == 1) {
                        prof(26);
                        mbar_wait(bar(B_YRDY), mainf ? 0 : ((job - 1) & 1));
                        prof(27);
                        load_y(mt * 9 + ch);
                        if (!mainf) warp_arrive(bar(B_KVB));
                    } else { prof(28); gate(); prof(29); }
                }
                wg_wait<0>();
                if (do_s && ((c.tid & 31) == 0)) { mbar_arrive(bar(B_EMPTY + st)); mbar_arrive(bar(B_OFREE + st)); if (st == 2) mbar_arrive(bar(B_OFREE + 3)); }
            });
            reg_fence<32>(hc);
            prof(30);
            if (!mainf) {
                #pragma unroll
                for (int i = 0; i < 16; i++) {
                    const uint32_t t = pack_bf16(hc[2 * i], hc[2 * i + 1]);
                    hc[2 * i] = bf_lo(sv[i]); hc[2 * i + 1] = bf_hi(sv[i]);
                    sv[i] = t;
                }
            }
            if (!mainf) prof(8 + 2 * job);
            if (do_f) store_out(eoff);
            if (!mainf) prof(9 + 2 * job);
        }
        prof(40);
        if (t2_ == 0) g_epoch[b2_] = v_epoch() + 1;
    }
}

typedef CUresult (*EncodeFn)(CUtensorMap*, CUtensorMapDataType, cuuint32_t, void*, const cuuint64_t*, const cuuint64_t*,
                             const cuuint32_t*, const cuuint32_t*, CUtensorMapInterleave, CUtensorMapSwizzle,
                             CUtensorMapL2promotion, CUtensorMapFloatOOBfill);

void make_map(EncodeFn enc, CUtensorMap* tm, const void* base, int rows, int cols, int box_rows, int box_cols = 64) {
    cuuint64_t gdim[2] = {(cuuint64_t)cols, (cuuint64_t)rows};
    cuuint64_t gstr[1] = {(cuuint64_t)cols * 2};
    cuuint32_t box[2] = {(cuuint32_t)box_cols, (cuuint32_t)box_rows};
    cuuint32_t estr[2] = {1, 1};
    enc(tm, CU_TENSOR_MAP_DATA_TYPE_BFLOAT16, 2, const_cast<void*>(base), gdim, gstr, box, estr, CU_TENSOR_MAP_INTERLEAVE_NONE,
        CU_TENSOR_MAP_SWIZZLE_128B, CU_TENSOR_MAP_L2_PROMOTION_L2_128B, CU_TENSOR_MAP_FLOAT_OOB_FILL_NONE);
}

}

extern "C" void kernel_launch(void* const* d_in, const int* in_sizes, int n_in, void* d_out, int out_size) {
    static EncodeFn enc = nullptr;
    static void* o_ptr = nullptr;
    if (!enc) {
        void* fn = nullptr;
        cudaDriverEntryPointQueryResult qr;
        cudaGetDriverEntryPoint("cuTensorMapEncodeTiled", &fn, cudaEnableDefault, &qr);
        enc = (EncodeFn)fn;
        cudaGetSymbolAddress(&o_ptr, g_o);
        cudaFuncSetAttribute(fused_kernel, cudaFuncAttributeMaxDynamicSharedMemorySize, SMEM_BYTES);
    }
    Params p;
    p.x = (const __nv_bfloat16*)d_in[0];
    p.wqkv = (const __nv_bfloat16*)d_in[1];
    p.wo = (const __nv_bfloat16*)d_in[2];
    p.w1 = (const __nv_bfloat16*)d_in[4];
    p.b1 = (const __nv_bfloat16*)d_in[5];
    p.w2 = (const __nv_bfloat16*)d_in[6];
    p.b2 = (const __nv_bfloat16*)d_in[7];
    p.out = (__nv_bfloat16*)d_out;
    CUtensorMap tm_x, tm_w1, tm_w2, tm_wo, tm_o, tm_qkv, tm_qkve;
    make_map(enc, &tm_qkv, p.wqkv, DM, 3 * DM, 96);
    make_map(enc, &tm_qkve, p.wqkv, DM, 3 * DM, 96, 8);
    make_map(enc, &tm_x, p.x, SEQ, DM, 128);
    make_map(enc, &tm_w1, p.w1, DM, FF, 192);
    make_map(enc, &tm_w2, p.w2, FF, DM, 192);
    make_map(enc, &tm_wo, p.wo, DM, DM, 192);
    make_map(enc, &tm_o, o_ptr, SEQ, DM, 128);
    fused_kernel<<<NMAIN + NAUX, 384, SMEM_BYTES>>>(tm_x, tm_w1, tm_w2, tm_wo, tm_o, tm_qkv, tm_qkve, p);
}
```

```cpp
#include <cuda_runtime.h>
#include <cuda.h>
#include <cuda_bf16.h>
#include <stdint.h>

#define OSTEP_AT 4
#define KNOB_A 1
#define KNOB_B 0
#define PF1_NS 1000
#define PF2_NS 2000
#define PFIDX 3
#define PF3_NS 800
#define YF32 0

namespace {
constexpr int WAIT_ITERS = 3000000;

constexpr int SEQ = 2048, DM = 576, FF = 4608;
constexpr int NMAIN = 128, NAUX = 4;

constexpr uint32_t SB    = 0x400;
constexpr uint32_t HA    = SB;
constexpr uint32_t XB    = SB + 131072;
constexpr uint32_t RING  = SB + 147456;
constexpr uint32_t SLOT  = 24576;
constexpr uint32_t MISC  = SB + 221184;
constexpr uint32_t BARS  = MISC;
constexpr uint32_t B1S   = MISC + 512;
constexpr uint32_t B2S   = MISC + 2816;
constexpr uint32_t EPO   = MISC + 3072;
constexpr uint32_t EVC   = MISC + 3104;
constexpr uint32_t SMEM_BYTES = 221184 + 3200 + 512;
constexpr uint32_t PKT   = HA + 32768;
constexpr uint32_t VT    = HA + 51200;
constexpr uint32_t PQT   = HA + 98304;
constexpr uint32_t KVB   = HA + 116736;

enum { B_FULL = 0, B_EMPTY = 3, B_XFULL = 6, B_OFULL = 9, B_O8FULL = 10, B_OFREE = 11, B_O8FREE = 12, B_KVB = 13, B_YRDY = 14, B_COUNT = 15 };
__device__ __forceinline__ constexpr uint32_t bar(int i) { return BARS + 8u * i; }

constexpr int YT_BYTES = YF32 ? 32768 : 16384;
__device__ __align__(1024) __nv_bfloat16 g_o[SEQ * DM];
__device__ __align__(1024) unsigned char g_yacc[2 * 16 * 9 * YT_BYTES];
__device__ __align__(128) float g_kv[2 * 8 * 72 * 20];
__device__ __align__(128) unsigned int g_cnt[(8 + 16 + 16 * 9) * 8];
__device__ unsigned int g_epoch[NMAIN + NAUX];
__device__ __forceinline__ unsigned int* cnt_kv(int j) { return g_cnt + j * 8; }
__device__ __forceinline__ unsigned int* cnt_o(int m) { return g_cnt + (8 + m) * 8; }
__device__ __forceinline__ unsigned int* cnt_y(int m, int c) { return g_cnt + (24 + m * 9 + c) * 8; }

__device__ __forceinline__ void mbar_init(uint32_t b, uint32_t cnt) { asm volatile("mbarrier.init.shared::cta.b64 [%0], %1;" :: "r"(b), "r"(cnt)); }
__device__ __forceinline__ void mbar_expect_tx(uint32_t b, uint32_t bytes) { asm volatile("mbarrier.arrive.expect_tx.shared::cta.b64 _, [%0], %1;" :: "r"(b), "r"(bytes) : "memory"); }
__device__ __forceinline__ void mbar_arrive(uint32_t b) { asm volatile("mbarrier.arrive.shared::cta.b64 _, [%0];" :: "r"(b) : "memory"); }
__device__ __forceinline__ void prof(int) {}
__device__ __forceinline__ void mbar_wait(uint32_t b, uint32_t parity) {
    asm volatile("{\n.reg .pred p;\n.reg .u32 c;\nmov.u32 c, 0;\n"
                 "WAIT_LOOP:\nmbarrier.try_wait.parity.shared::cta.b64 p, [%0], %1;\n@p bra WAIT_DONE;\n"
                 "add.u32 c, c, 1;\nsetp.lt.u32 p, c, 4000000;\n@p bra WAIT_LOOP;\ntrap;\nWAIT_DONE:\n}"
                 :: "r"(b), "r"(parity) : "memory");
}
__device__ __forceinline__ void tma_2d(uint32_t dst, const CUtensorMap* tm, uint32_t b, int c0, int c1) {
    asm volatile("cp.async.bulk.tensor.2d.shared::cluster.global.mbarrier::complete_tx::bytes [%0], [%1, {%3, %4}], [%2];"
                 :: "r"(dst), "l"(tm), "r"(b), "r"(c0), "r"(c1) : "memory");
}
__device__ __forceinline__ void fence_async_smem() { asm volatile("fence.proxy.async.shared::cta;" ::: "memory"); }
__device__ __forceinline__ void fence_async_all() { asm volatile("fence.proxy.async;" ::: "memory"); }
__device__ __forceinline__ void named_bar(int id, int n) { asm volatile("bar.sync %0, %1;" :: "r"(id), "r"(n) : "memory"); }
__device__ __forceinline__ void wg_fence() { asm volatile("wgmma.fence.sync.aligned;" ::: "memory"); }
__device__ __forceinline__ void wg_commit() { asm volatile("wgmma.commit_group.sync.aligned;" ::: "memory"); }
template<int N> __device__ __forceinline__ void wg_wait() { asm volatile("wgmma.wait_group.sync.aligned %0;" :: "n"(N) : "memory"); }
template<int N> __device__ __forceinline__ void reg_fence(float* d) {
    #pragma unroll
    for (int i = 0; i < N; i++) asm volatile("" : "+f"(d[i]) :: "memory");
}
template<int N> __device__ __forceinline__ void reg_copy(float* d, const float* s) {
    #pragma unroll
    for (int i = 0; i < N; i++) asm volatile("mov.b32 %0, %1;" : "=f"(d[i]) : "f"(s[i]));
}
__device__ __forceinline__ uint32_t pack_bf16(float lo, float hi) { uint32_t r; asm("cvt.rn.bf16x2.f32 %0, %1, %2;" : "=r"(r) : "f"(hi), "f"(lo)); return r; }
__device__ __forceinline__ float bf_lo(uint32_t v) { return __uint_as_float(v << 16); }
__device__ __forceinline__ float bf_hi(uint32_t v) { return __uint_as_float(v & 0xffff0000u); }
__device__ __forceinline__ uint32_t sub_bf16x2(uint32_t a, uint32_t b) { uint32_t r; asm("sub.rn.bf16x2 %0, %1, %2;" : "=r"(r) : "r"(a), "r"(b)); return r; }
__device__ __forceinline__ float ex2(float x) { float r; asm("ex2.approx.ftz.f32 %0, %1;" : "=f"(r) : "f"(x)); return r; }
__device__ __forceinline__ float rcp(float x) { float r; asm("rcp.approx.ftz.f32 %0, %1;" : "=f"(r) : "f"(x)); return r; }
__device__ __forceinline__ float tanh_ap(float x) { float r; asm("tanh.approx.f32 %0, %1;" : "=f"(r) : "f"(x)); return r; }
__device__ __forceinline__ void sts32(uint32_t a, uint32_t v) { asm volatile("st.shared.b32 [%0], %1;" :: "r"(a), "r"(v)); }
__device__ __forceinline__ void sts128(uint32_t a, uint32_t x, uint32_t y, uint32_t z, uint32_t w) { asm volatile("st.shared.v4.b32 [%0], {%1,%2,%3,%4};" :: "r"(a), "r"(x), "r"(y), "r"(z), "r"(w)); }
__device__ __forceinline__ void sts64(uint32_t a, uint32_t x, uint32_t y) { asm volatile("st.shared.v2.b32 [%0], {%1,%2};" :: "r"(a), "r"(x), "r"(y)); }
__device__ __forceinline__ void lds64(uint32_t a, uint32_t* v) { asm volatile("ld.shared.v2.b32 {%0,%1}, [%2];" : "=r"(v[0]), "=r"(v[1]) : "r"(a)); }
__device__ __forceinline__ void lds128(uint32_t a, uint32_t* v) { asm volatile("ld.shared.v4.b32 {%0,%1,%2,%3}, [%4];" : "=r"(v[0]), "=r"(v[1]), "=r"(v[2]), "=r"(v[3]) : "r"(a) : "memory"); }
__device__ __forceinline__ float2 lds64f(uint32_t a) { float2 v; asm("ld.shared.v2.f32 {%0,%1}, [%2];" : "=f"(v.x), "=f"(v.y) : "r"(a)); return v; }
__device__ __forceinline__ void ldsm4(uint32_t a, uint32_t* v) {
    asm volatile("ldmatrix.sync.aligned.m8n8.x4.shared.b16 {%0,%1,%2,%3}, [%4];" : "=r"(v[0]), "=r"(v[1]), "=r"(v[2]), "=r"(v[3]) : "r"(a));
}
__device__ __forceinline__ void mma_ones(float* c, const uint32_t* a) {
    const uint32_t one2 = 0x3F803F80u;
    asm volatile("mma.sync.aligned.m16n8k16.row.col.f32.bf16.bf16.f32 {%0,%1,%2,%3}, {%4,%5,%6,%7}, {%8,%8}, {%0,%1,%2,%3};"
                 : "+f"(c[0]), "+f"(c[1]), "+f"(c[2]), "+f"(c[3]) : "r"(a[0]), "r"(a[1]), "r"(a[2]), "r"(a[3]), "r"(one2));
}
__device__ __forceinline__ unsigned int ld_acquire(const unsigned int* p) { unsigned int v; asm volatile("ld.acquire.gpu.global.u32 %0, [%1];" : "=r"(v) : "l"(p) : "memory"); return v; }
__device__ __forceinline__ void wait_cnt(const unsigned int* p, unsigned int target) {
    for (int i = 0; i < WAIT_ITERS; i++) {
        if ((int)(ld_acquire(p) - target) >= 0) return;
        __nanosleep(40);
    }
    __trap();
}
__device__ __forceinline__ uint32_t v_tid() { uint32_t r; asm volatile("mov.u32 %0, %%tid.x;" : "=r"(r)); return r; }
__device__ __forceinline__ uint32_t v_bid() { uint32_t r; asm volatile("mov.u32 %0, %%ctaid.x;" : "=r"(r)); return r; }
__device__ __forceinline__ uint32_t v_epoch() { uint32_t r; asm volatile("ld.shared.u32 %0, [%1];" : "=r"(r) : "r"(EPO)); return r; }
__device__ __forceinline__ void prefetch_l2(const void* p) { asm volatile("prefetch.global.L2 [%0];" :: "l"(p)); }

__host__ __device__ constexpr uint64_t mkdesc(uint32_t addr, uint32_t lbo, uint32_t sbo, uint32_t swz) {
    return (uint64_t)((addr & 0x3FFFF) >> 4) | ((uint64_t)((lbo >> 4) & 0x3FFF) << 16) | ((uint64_t)((sbo >> 4) & 0x3FFF) << 32) | ((uint64_t)swz << 62);
}

template<int SD> __device__ __forceinline__ void wg_rs64(float* d, const uint32_t* a, uint64_t bd) {
  if constexpr (SD) {
    asm volatile("{\n.reg .pred p;\nsetp.eq.b32 p, 0, 0;\n"
    "wgmma.mma_async.sync.aligned.m64n64k16.f32.bf16.bf16 {%0,%1,%2,%3,%4,%5,%6,%7,%8,%9,%10,%11,%12,%13,%14,%15,%16,%17,%18,%19,%20,%21,%22,%23,%24,%25,%26,%27,%28,%29,%30,%31}, {%32,%33,%34,%35}, %36, p, 1, 1, 1;\n}"
    : "+f"(d[0]),"+f"(d[1]),"+f"(d[2]),"+f"(d[3]),"+f"(d[4]),"+f"(d[5]),"+f"(d[6]),"+f"(d[7]),"+f"(d[8]),"+f"(d[9]),"+f"(d[10]),"+f"(d[11]),"+f"(d[12]),"+f"(d[13]),"+f"(d[14]),"+f"(d[15]),"+f"(d[16]),"+f"(d[17]),"+f"(d[18]),"+f"(d[19]),"+f"(d[20]),"+f"(d[21]),"+f"(d[22]),"+f"(d[23]),"+f"(d[24]),"+f"(d[25]),"+f"(d[26]),"+f"(d[27]),"+f"(d[28]),"+f"(d[29]),"+f"(d[30]),"+f"(d[31])
    : "r"(a[0]),"r"(a[1]),"r"(a[2]),"r"(a[3]), "l"(bd));
  } else {
    asm volatile("{\n.reg .pred p;\nsetp.ne.b32 p, 0, 0;\n"
    "wgmma.mma_async.sync.aligned.m64n64k16.f32.bf16.bf16 {%0,%1,%2,%3,%4,%5,%6,%7,%8,%9,%10,%11,%12,%13,%14,%15,%16,%17,%18,%19,%20,%21,%22,%23,%24,%25,%26,%27,%28,%29,%30,%31}, {%32,%33,%34,%35}, %36, p, 1, 1, 1;\n}"
    : "+f"(d[0]),"+f"(d[1]),"+f"(d[2]),"+f"(d[3]),"+f"(d[4]),"+f"(d[5]),"+f"(d[6]),"+f"(d[7]),"+f"(d[8]),"+f"(d[9]),"+f"(d[10]),"+f"(d[11]),"+f"(d[12]),"+f"(d[13]),"+f"(d[14]),"+f"(d[15]),"+f"(d[16]),"+f"(d[17]),"+f"(d[18]),"+f"(d[19]),"+f"(d[20]),"+f"(d[21]),"+f"(d[22]),"+f"(d[23]),"+f"(d[24]),"+f"(d[25]),"+f"(d[26]),"+f"(d[27]),"+f"(d[28]),"+f"(d[29]),"+f"(d[30]),"+f"(d[31])
    : "r"(a[0]),"r"(a[1]),"r"(a[2]),"r"(a[3]), "l"(bd));
  }
}
template<int SD> __device__ __forceinline__ void wg_ss64(float* d, uint64_t ad, uint64_t bd) {
  if constexpr (SD) {
    asm volatile("{\n.reg .pred p;\nsetp.eq.b32 p, 0, 0;\n"
    "wgmma.mma_async.sync.aligned.m64n64k16.f32.bf16.bf16 {%0,%1,%2,%3,%4,%5,%6,%7,%8,%9,%10,%11,%12,%13,%14,%15,%16,%17,%18,%19,%20,%21,%22,%23,%24,%25,%26,%27,%28,%29,%30,%31}, %32, %33, p, 1, 1, 0, 1;\n}"
    : "+f"(d[0]),"+f"(d[1]),"+f"(d[2]),"+f"(d[3]),"+f"(d[4]),"+f"(d[5]),"+f"(d[6]),"+f"(d[7]),"+f"(d[8]),"+f"(d[9]),"+f"(d[10]),"+f"(d[11]),"+f"(d[12]),"+f"(d[13]),"+f"(d[14]),"+f"(d[15]),"+f"(d[16]),"+f"(d[17]),"+f"(d[18]),"+f"(d[19]),"+f"(d[20]),"+f"(d[21]),"+f"(d[22]),"+f"(d[23]),"+f"(d[24]),"+f"(d[25]),"+f"(d[26]),"+f"(d[27]),"+f"(d[28]),"+f"(d[29]),"+f"(d[30]),"+f"(d[31])
    : "l"(ad), "l"(bd));
  } else {
    asm volatile("{\n.reg .pred p;\nsetp.ne.b32 p, 0, 0;\n"
    "wgmma.mma_async.sync.aligned.m64n64k16.f32.bf16.bf16 {%0,%1,%2,%3,%4,%5,%6,%7,%8,%9,%10,%11,%12,%13,%14,%15,%16,%17,%18,%19,%20,%21,%22,%23,%24,%25,%26,%27,%28,%29,%30,%31}, %32, %33, p, 1, 1, 0, 1;\n}"
    : "+f"(d[0]),"+f"(d[1]),"+f"(d[2]),"+f"(d[3]),"+f"(d[4]),"+f"(d[5]),"+f"(d[6]),"+f"(d[7]),"+f"(d[8]),"+f"(d[9]),"+f"(d[10]),"+f"(d[11]),"+f"(d[12]),"+f"(d[13]),"+f"(d[14]),"+f"(d[15]),"+f"(d[16]),"+f"(d[17]),"+f"(d[18]),"+f"(d[19]),"+f"(d[20]),"+f"(d[21]),"+f"(d[22]),"+f"(d[23]),"+f"(d[24]),"+f"(d[25]),"+f"(d[26]),"+f"(d[27]),"+f"(d[28]),"+f"(d[29]),"+f"(d[30]),"+f"(d[31])
    : "l"(ad), "l"(bd));
  }
}
template<int SD> __device__ __forceinline__ void wg_rs72(float* d, const uint32_t* a, uint64_t bd) {
  if constexpr (SD) {
    asm volatile("{\n.reg .pred p;\nsetp.eq.b32 p, 0, 0;\n"
    "wgmma.mma_async.sync.aligned.m64n72k16.f32.bf16.bf16 {%0,%1,%2,%3,%4,%5,%6,%7,%8,%9,%10,%11,%12,%13,%14,%15,%16,%17,%18,%19,%20,%21,%22,%23,%24,%25,%26,%27,%28,%29,%30,%31,%32,%33,%34,%35}, {%36,%37,%38,%39}, %40, p, 1, 1, 1;\n}"
    : "+f"(d[0]),"+f"(d[1]),"+f"(d[2]),"+f"(d[3]),"+f"(d[4]),"+f"(d[5]),"+f"(d[6]),"+f"(d[7]),"+f"(d[8]),"+f"(d[9]),"+f"(d[10]),"+f"(d[11]),"+f"(d[12]),"+f"(d[13]),"+f"(d[14]),"+f"(d[15]),"+f"(d[16]),"+f"(d[17]),"+f"(d[18]),"+f"(d[19]),"+f"(d[20]),"+f"(d[21]),"+f"(d[22]),"+f"(d[23]),"+f"(d[24]),"+f"(d[25]),"+f"(d[26]),"+f"(d[27]),"+f"(d[28]),"+f"(d[29]),"+f"(d[30]),"+f"(d[31]),"+f"(d[32]),"+f"(d[33]),"+f"(d[34]),"+f"(d[35])
    : "r"(a[0]),"r"(a[1]),"r"(a[2]),"r"(a[3]), "l"(bd));
  } else {
    asm volatile("{\n.reg .pred p;\nsetp.ne.b32 p, 0, 0;\n"
    "wgmma.mma_async.sync.aligned.m64n72k16.f32.bf16.bf16 {%0,%1,%2,%3,%4,%5,%6,%7,%8,%9,%10,%11,%12,%13,%14,%15,%16,%17,%18,%19,%20,%21,%22,%23,%24,%25,%26,%27,%28,%29,%30,%31,%32,%33,%34,%35}, {%36,%37,%38,%39}, %40, p, 1, 1, 1;\n}"
    : "+f"(d[0]),"+f"(d[1]),"+f"(d[2]),"+f"(d[3]),"+f"(d[4]),"+f"(d[5]),"+f"(d[6]),"+f"(d[7]),"+f"(d[8]),"+f"(d[9]),"+f"(d[10]),"+f"(d[11]),"+f"(d[12]),"+f"(d[13]),"+f"(d[14]),"+f"(d[15]),"+f"(d[16]),"+f"(d[17]),"+f"(d[18]),"+f"(d[19]),"+f"(d[20]),"+f"(d[21]),"+f"(d[22]),"+f"(d[23]),"+f"(d[24]),"+f"(d[25]),"+f"(d[26]),"+f"(d[27]),"+f"(d[28]),"+f"(d[29]),"+f"(d[30]),"+f"(d[31]),"+f"(d[32]),"+f"(d[33]),"+f"(d[34]),"+f"(d[35])
    : "r"(a[0]),"r"(a[1]),"r"(a[2]),"r"(a[3]), "l"(bd));
  }
}
template<int SD> __device__ __forceinline__ void wg_ss72(float* d, uint64_t ad, uint64_t bd) {
  if constexpr (SD) {
    asm volatile("{\n.reg .pred p;\nsetp.eq.b32 p, 0, 0;\n"
    "wgmma.mma_async.sync.aligned.m64n72k16.f32.bf16.bf16 {%0,%1,%2,%3,%4,%5,%6,%7,%8,%9,%10,%11,%12,%13,%14,%15,%16,%17,%18,%19,%20,%21,%22,%23,%24,%25,%26,%27,%28,%29,%30,%31,%32,%33,%34,%35}, %36, %37, p, 1, 1, 0, 1;\n}"
    : "+f"(d[0]),"+f"(d[1]),"+f"(d[2]),"+f"(d[3]),"+f"(d[4]),"+f"(d[5]),"+f"(d[6]),"+f"(d[7]),"+f"(d[8]),"+f"(d[9]),"+f"(d[10]),"+f"(d[11]),"+f"(d[12]),"+f"(d[13]),"+f"(d[14]),"+f"(d[15]),"+f"(d[16]),"+f"(d[17]),"+f"(d[18]),"+f"(d[19]),"+f"(d[20]),"+f"(d[21]),"+f"(d[22]),"+f"(d[23]),"+f"(d[24]),"+f"(d[25]),"+f"(d[26]),"+f"(d[27]),"+f"(d[28]),"+f"(d[29]),"+f"(d[30]),"+f"(d[31]),"+f"(d[32]),"+f"(d[33]),"+f"(d[34]),"+f"(d[35])
    : "l"(ad), "l"(bd));
  } else {
    asm volatile("{\n.reg .pred p;\nsetp.ne.b32 p, 0, 0;\n"
    "wgmma.mma_async.sync.aligned.m64n72k16.f32.bf16.bf16 {%0,%1,%2,%3,%4,%5,%6,%7,%8,%9,%10,%11,%12,%13,%14,%15,%16,%17,%18,%19,%20,%21,%22,%23,%24,%25,%26,%27,%28,%29,%30,%31,%32,%33,%34,%35}, %36, %37, p, 1, 1, 0, 1;\n}"
    : "+f"(d[0]),"+f"(d[1]),"+f"(d[2]),"+f"(d[3]),"+f"(d[4]),"+f"(d[5]),"+f"(d[6]),"+f"(d[7]),"+f"(d[8]),"+f"(d[9]),"+f"(d[10]),"+f"(d[11]),"+f"(d[12]),"+f"(d[13]),"+f"(d[14]),"+f"(d[15]),"+f"(d[16]),"+f"(d[17]),"+f"(d[18]),"+f"(d[19]),"+f"(d[20]),"+f"(d[21]),"+f"(d[22]),"+f"(d[23]),"+f"(d[24]),"+f"(d[25]),"+f"(d[26]),"+f"(d[27]),"+f"(d[28]),"+f"(d[29]),"+f"(d[30]),"+f"(d[31]),"+f"(d[32]),"+f"(d[33]),"+f"(d[34]),"+f"(d[35])
    : "l"(ad), "l"(bd));
  }
}
template<int SD> __device__ __forceinline__ void wg_tt64(float* d, uint64_t ad, uint64_t bd) {
  if constexpr (SD) {
    asm volatile("{\n.reg .pred p;\nsetp.eq.b32 p, 0, 0;\n"
    "wgmma.mma_async.sync.aligned.m64n64k16.f32.bf16.bf16 {%0,%1,%2,%3,%4,%5,%6,%7,%8,%9,%10,%11,%12,%13,%14,%15,%16,%17,%18,%19,%20,%21,%22,%23,%24,%25,%26,%27,%28,%29,%30,%31}, %32, %33, p, 1, 1, 1, 1;\n}"
    : "+f"(d[0]),"+f"(d[1]),"+f"(d[2]),"+f"(d[3]),"+f"(d[4]),"+f"(d[5]),"+f"(d[6]),"+f"(d[7]),"+f"(d[8]),"+f"(d[9]),"+f"(d[10]),"+f"(d[11]),"+f"(d[12]),"+f"(d[13]),"+f"(d[14]),"+f"(d[15]),"+f"(d[16]),"+f"(d[17]),"+f"(d[18]),"+f"(d[19]),"+f"(d[20]),"+f"(d[21]),"+f"(d[22]),"+f"(d[23]),"+f"(d[24]),"+f"(d[25]),"+f"(d[26]),"+f"(d[27]),"+f"(d[28]),"+f"(d[29]),"+f"(d[30]),"+f"(d[31])
    : "l"(ad), "l"(bd));
  } else {
    asm volatile("{\n.reg .pred p;\nsetp.ne.b32 p, 0, 0;\n"
    "wgmma.mma_async.sync.aligned.m64n64k16.f32.bf16.bf16 {%0,%1,%2,%3,%4,%5,%6,%7,%8,%9,%10,%11,%12,%13,%14,%15,%16,%17,%18,%19,%20,%21,%22,%23,%24,%25,%26,%27,%28,%29,%30,%31}, %32, %33, p, 1, 1, 1, 1;\n}"
    : "+f"(d[0]),"+f"(d[1]),"+f"(d[2]),"+f"(d[3]),"+f"(d[4]),"+f"(d[5]),"+f"(d[6]),"+f"(d[7]),"+f"(d[8]),"+f"(d[9]),"+f"(d[10]),"+f"(d[11]),"+f"(d[12]),"+f"(d[13]),"+f"(d[14]),"+f"(d[15]),"+f"(d[16]),"+f"(d[17]),"+f"(d[18]),"+f"(d[19]),"+f"(d[20]),"+f"(d[21]),"+f"(d[22]),"+f"(d[23]),"+f"(d[24]),"+f"(d[25]),"+f"(d[26]),"+f"(d[27]),"+f"(d[28]),"+f"(d[29]),"+f"(d[30]),"+f"(d[31])
    : "l"(ad), "l"(bd));
  }
}

template<int V> struct IC { static constexpr int v = V; };
template<int I, int N, class F> __device__ __forceinline__ void sfor(F&& f) {
    if constexpr (I < N) { f(IC<I>{}); sfor<I + 1, N>(f); }
}

enum { K_QKV = 0, K_H = 1 };

struct Ctx {
    uint32_t tph;
    uint32_t tid;
    bool pf = false;
};
__device__ __forceinline__ void release_slot(const Ctx& c, int slot) { if ((c.tid & 31) == 0) mbar_arrive(bar(B_EMPTY + slot)); }

__device__ __forceinline__ void turn_wait(const Ctx& c) { asm volatile("bar.sync %0, 256;" :: "r"(4 + (c.tid >> 7)) : "memory"); }
__device__ __forceinline__ void turn_pass(const Ctx& c) { asm volatile("bar.arrive %0, 256;" :: "r"(5 - (c.tid >> 7)) : "memory"); }

template<int KIND, class PART, class POST>
__device__ __forceinline__ void run_step(Ctx& c, float* acc, const uint32_t* a, PART&& part, POST&& post, bool last = false) {
    constexpr int NST = (KIND == K_QKV) ? 6 : 3;
    constexpr int KPS = 36 / NST;
    sfor<0, NST>([&](auto ST) {
        constexpr int st = decltype(ST)::v;
        constexpr int slot = st % 3;
        mbar_wait(bar(B_FULL + slot), c.tph);
        uint32_t wgo = 0;
        if constexpr (st == NST - 1) wgo = (c.tid >> 7) * 512;
        if (KIND == K_H && c.pf) prof(44 + st * 5);
        turn_wait(c);
        if (KIND == K_H && c.pf) prof(45 + st * 5);
        wg_fence();
        sfor<0, KPS>([&](auto KK) {
            constexpr int kk = decltype(KK)::v;
            constexpr int ks = st * KPS + kk;
            constexpr int SD = ks ? 1 : 0;
            if constexpr (KIND == K_QKV) {
                constexpr uint64_t bd = mkdesc(RING + slot * SLOT + kk * 2048, 12288, 1024, 1);
                if constexpr (ks < 32) wg_rs72<SD>(acc, a + ks * 4, bd);
                else wg_ss72<SD>(acc, mkdesc(XB + (ks - 32) * 32, 16, 1024, 1) + wgo, bd);
            } else {
                constexpr uint64_t bd = mkdesc(RING + slot * SLOT + kk * 2048, 16, 1024, 1);
                if constexpr (ks < 32) wg_rs64<SD>(acc, a + ks * 4, bd);
                else wg_ss64<SD>(acc, mkdesc(XB + (ks - 32) * 32, 16, 1024, 1) + wgo, bd);
            }
        });
        wg_commit();
        if (st < NST - 1 || !last || c.tid < 128) turn_pass(c);
        if (KIND == K_H && c.pf) prof(46 + st * 5);
        part(ST);
        if (KIND == K_H && c.pf) prof(47 + st * 5);
        wg_wait<0>();
        if (KIND == K_H && c.pf) prof(48 + st * 5);
        release_slot(c, slot);
        if constexpr (slot == 2) c.tph ^= 1;
        post(ST);
    });
    if constexpr (KIND == K_QKV) reg_fence<36>(acc); else reg_fence<32>(acc);
}

__device__ __forceinline__ float phi(float t) {
    float e = ex2(t * 1.4426950408889634f);
    return (t > 0.f ? t + 1.0f : e) + 1e-6f;
}
__device__ __forceinline__ float gelu_h(float hx) {
    float u = hx * fmaf(hx * hx, 0.2854192650f, 1.5957691216f);
    return fmaf(hx, tanh_ap(u), hx);
}

struct Params {
    const __nv_bfloat16* x;
    const __nv_bfloat16* wqkv;
    const __nv_bfloat16* wo;
    const __nv_bfloat16* w1;
    const __nv_bfloat16* b1;
    const __nv_bfloat16* w2;
    const __nv_bfloat16* b2;
    __nv_bfloat16* out;
};

__global__ void __launch_bounds__(384, 1)
fused_kernel(const __grid_constant__ CUtensorMap tm_x, const __grid_constant__ CUtensorMap tm_w1,
             const __grid_constant__ CUtensorMap tm_w2, const __grid_constant__ CUtensorMap tm_wo,
             const __grid_constant__ CUtensorMap tm_o, const __grid_constant__ CUtensorMap tm_qkv,
             const __grid_constant__ CUtensorMap tm_qkve, const Params p) {
    extern __shared__ __align__(1024) unsigned char smem_raw[];
    const int tid = threadIdx.x;
    const int bid = blockIdx.x;
    const bool is_main = bid < NMAIN;
    const int j = bid & 7;
    const int m = bid >> 3;

    if (tid == 0) {
        if ((uint32_t)__cvta_generic_to_shared(smem_raw) != SB) __trap();
        for (int i = 0; i < 3; i++) {
            mbar_init(bar(B_FULL + i), 1); mbar_init(bar(B_EMPTY + i), 8);
            mbar_init(bar(B_XFULL + i), 1);
        }
        mbar_init(bar(B_KVB), is_main ? 2 : 8); mbar_init(bar(B_YRDY), 1);
        mbar_init(bar(B_OFULL), 1); mbar_init(bar(B_O8FULL), 1); mbar_init(bar(B_OFREE), 8); mbar_init(bar(B_O8FREE), 8);
        asm volatile("fence.mbarrier_init.release.cluster;" ::: "memory");
        if (is_main) {
            for (int g = 0; g < 3; g++) {
                mbar_expect_tx(bar(B_XFULL + g), 49152);
                for (int kb = 3 * g; kb < 3 * g + 3; kb++) tma_2d(HA + kb * 16384, &tm_x, bar(B_XFULL + g), kb * 64, m * 128);
            }
            for (int st = 0; st < 3; st++) {
                mbar_expect_tx(bar(B_FULL + st), 96 * 144);
                tma_2d(RING + st * SLOT, &tm_qkv, bar(B_FULL + st), 576 + j * 72, st * 96);
                tma_2d(RING + st * SLOT + 12288, &tm_qkve, bar(B_FULL + st), 576 + j * 72 + 64, st * 96);
            }
        }
    }
    if (tid == 32) sts32(EPO, g_epoch[bid]);
    if (tid >= 40 && tid < 48) sts32(EVC + (tid - 40) * 4, 0);
    if (tid >= 64 && tid < 64 + 288 && is_main) {
        int i = tid - 64;
        uint32_t v = *reinterpret_cast<const uint32_t*>(p.b1 + j * 576 + 2 * i);
        sts32(B1S + 8 * i, __float_as_uint(0.5f * bf_lo(v))); sts32(B1S + 8 * i + 4, __float_as_uint(0.5f * bf_hi(v)));
    }
    if (tid >= 352) {
        int i = tid - 352;
        uint32_t v = *reinterpret_cast<const uint32_t*>(p.b2 + (is_main ? j : 8) * 64 + 2 * i);
        sts32(B2S + 8 * i, v << 16); sts32(B2S + 8 * i + 4, v & 0xffff0000u);
    }
    fence_async_smem();
    __syncthreads();
    uint32_t epoch;
    asm volatile("ld.shared.u32 %0, [%1];" : "=r"(epoch) : "r"(EPO));
    const uint32_t par = epoch & 1;

    if (tid >= 256) {
        asm volatile("setmaxnreg.dec.sync.aligned.u32 24;");
        const int hw = (tid >> 5) - 8, lane = tid & 31;
        if (hw == 0) {
            if (lane == 0) {
                uint32_t n = 0;
                if (is_main) {
                    n = 1;
                    #pragma unroll 1
                    for (int u = 3; u < 18; u++) {
                        const int st = u % 3, step = u / 6;
                        const int col = ((step == 2) ? 0 : (step + 1) * 576) + j * 72, row = (u % 6) * 96;
                        mbar_wait(bar(B_EMPTY + st), (n & 1) ^ 1);
                        mbar_expect_tx(bar(B_FULL + st), 96 * 144);
                        tma_2d(RING + st * SLOT, &tm_qkv, bar(B_FULL + st), col, row);
                        tma_2d(RING + st * SLOT + 12288, &tm_qkve, bar(B_FULL + st), col + 64, row);
                        if (st == 2) n++;
                    }
                }
                const int nsteps = is_main ? 19 : 1;
                #pragma unroll 1
                for (int s = 0; s < nsteps; s++, n++) {
                    const CUtensorMap* tm; int col, row;
                    if (!is_main) { tm = &tm_wo; col = 512; row = 0; }
                    else if (s < 9) { tm = &tm_w1; col = j * 576 + s * 64; row = 0; }
                    else if (s < 18) { tm = &tm_w2; col = (s == 9) ? 512 : (((j + s - 9) & 7) * 64); row = j * 576; }
                    else { tm = &tm_wo; col = j * 64; row = 0; }
                    #pragma unroll 1
                    for (int st = 0; st < 3; st++) {
                        mbar_wait(bar(B_EMPTY + st), (n & 1) ^ 1);
                        mbar_expect_tx(bar(B_FULL + st), SLOT);
                        tma_2d(RING + st * SLOT, tm, bar(B_FULL + st), col, row + st * 192);
                    }
                }
            }
        } else {
            if (is_main) {
                const int t = tid - 288;
                #pragma unroll 1
                for (int i = t; i < 36 * 6; i += 96) {
                    int r = i / 6, q = i - r * 6;
                    prefetch_l2(reinterpret_cast<const char*>(p.wqkv) + (36 * m + r) * 3456 + (q >> 1) * 1152 + j * 144 + (q & 1) * 128);
                }
                __nanosleep(PF1_NS);
                #pragma unroll 1
                for (int i = t; i < 36 * 9; i += 96) {
                    int r = i / 9, q = i - r * 9;
                    prefetch_l2(reinterpret_cast<const char*>(p.w1) + (36 * m + r) * 9216 + j * 1152 + q * 128);
                    __nanosleep(PF3_NS);
                }
                __nanosleep(PF2_NS);
                #pragma unroll 1
                for (int i = t; i < 36 * 9; i += 96)
                    prefetch_l2(reinterpret_cast<const char*>(p.w2) + (576 * j + 36 * m) * 1152 + i * 128);
                if (t < 41 && (bid * 41 + t) < 5184) prefetch_l2(reinterpret_cast<const char*>(p.wo) + (bid * 41 + t) * 128);
                if (hw != 2) {
                    if (lane == 0) wait_cnt(cnt_kv(j), (epoch + 1) * 16);
                    __syncwarp();
                    const float4* kv = reinterpret_cast<const float4*>(g_kv + (par * 8 + j) * 1440);
                    #pragma unroll 2
                    for (int i = lane + (hw == 1 ? 0 : 32); i < 360; i += 64) {
                        const float4 v = __ldcg(kv + i);
                        const int d = i / 5, e = (i - d * 5) * 4, h = d / 18;
                        const uint32_t base = KVB + (d >> 3) * 128 + (d & 7) * 16;
                        const int n0 = 8 + h * 18 + e;
                        sts32(base + (n0 >> 3) * 1280 + (n0 & 7) * 2, pack_bf16(v.x, v.y));
                        if (e < 16) sts32(base + ((n0 + 2) >> 3) * 1280 + ((n0 + 2) & 7) * 2, pack_bf16(v.z, v.w));
                        else asm volatile("st.shared.u16 [%0], %1;" :: "r"(base + h * 2), "h"((unsigned short)pack_bf16(v.z, 0.f)) : "memory");
                    }
                    fence_async_smem();
                    __syncwarp();
                    if (lane == 0) mbar_arrive(bar(B_KVB));
                }
            }
            if (hw == 1) {
                if (lane == 0) {
                    const int nit = is_main ? 1 : 4;
                    for (int it = 0; it < nit; it++) {
                        const int mt = is_main ? m : ((bid - NMAIN) * 4 + it);
                        const bool wf = is_main || it > 0;
                        const uint32_t fp = is_main ? 0 : ((it - 1) & 1);
                        wait_cnt(cnt_o(mt), (epoch + 1) * 8);
                        fence_async_all();
                        if (wf) mbar_wait(bar(B_OFREE), fp);
                        mbar_expect_tx(bar(B_OFULL), 131072);
                        #pragma unroll 1
                        for (int kb = 0; kb < 8; kb++) tma_2d(HA + kb * 16384, &tm_o, bar(B_OFULL), kb * 64, mt * 128);
                        if (wf) mbar_wait(bar(B_O8FREE), fp);
                        mbar_expect_tx(bar(B_O8FULL), 16384);
                        tma_2d(XB, &tm_o, bar(B_O8FULL), 512, mt * 128);
                    }
                    if (is_main) { wait_cnt(cnt_y(m, j), (epoch + 1) * 7); mbar_arrive(bar(B_YRDY)); }
                }
            } else if (hw == 2) {
                if (!is_main) {
                    if (lane == 0) {
                        #pragma unroll 1
                        for (int it = 0; it < 4; it++) {
                            if (it > 0) mbar_wait(bar(B_KVB), (it - 1) & 1);
                            wait_cnt(cnt_y((bid - NMAIN) * 4 + it, 8), (epoch + 1) * 8);
                            mbar_arrive(bar(B_YRDY));
                        }
                    }
                } else {
                    #pragma unroll 1
                    for (int e = 0; e < 10; e++) {
                        int spin = 0;
                        while (true) {
                            uint32_t v;
                            asm volatile("ld.acquire.cta.shared.u32 %0, [%1];" : "=r"(v) : "r"(EVC + (lane & 7) * 4) : "memory");
                            if (__all_sync(0xffffffffu, v > (uint32_t)e)) break;
                            if (++spin > 20000000) __trap();
                            __nanosleep(20);
                        }
                        if (lane == 0) {
                            unsigned int* cp = (e == 0) ? cnt_kv(j) : (e == 1) ? cnt_o(m) : cnt_y(m, e == 2 ? 8 : ((j + e - 2) & 7));
                            if (e == 1) fence_async_all();
                            __threadfence();
                            asm volatile("red.relaxed.gpu.global.add.u32 [%0], 1;" :: "l"(cp) : "memory");
                        }
                        __syncwarp();
                    }
                }
            } else {
                {
                    const int t0 = is_main ? (m * 9 + j) : ((bid - NMAIN) * 4 * 9 + 8);
                    const int nt = is_main ? 1 : 4;
                    for (int t = 0; t < nt; t++) {
                        uint4* z = reinterpret_cast<uint4*>(g_yacc + (size_t)((par ^ 1) * 144 + t0 + t * 9) * YT_BYTES);
                        for (int i = lane; i < YT_BYTES / 16; i += 32) z[i] = make_uint4(0, 0, 0, 0);
                    }
                    if (is_main && m == 0) {
                        float* z = g_kv + ((par ^ 1) * 8 + j) * 1440;
                        for (int i = lane; i < 1440; i += 32) z[i] = 0.f;
                    }
                }
            }
        }
    } else {
        asm volatile("setmaxnreg.inc.sync.aligned.u32 240;");
        prof(0);
        Ctx c; c.tph = 0; c.tid = v_tid();
        float hc[32], pv[36];
        if (tid >> 7) turn_pass(c);
        auto event = [&](uint32_t ev) {
            __syncwarp();
            if (((c.tid & 31) == 0)) asm volatile("st.release.cta.shared.u32 [%0], %1;" :: "r"(EVC + (c.tid >> 3)), "r"(ev) : "memory");
        };
        auto warp_arrive = [&](uint32_t b) { __syncwarp(); if (((c.tid & 31) == 0)) mbar_arrive(b); };

        uint32_t a[128];
        float rs0 = 0.f, rs1 = 0.f;
        auto lrow_off = [&]() { uint32_t t_ = c.tid; return HA + ((t_ >> 5) * 16 + (t_ & 15)) * 128 + ((((t_ >> 4) & 1) ^ (t_ & 7)) << 4); };
        auto tail_off = [&]() { uint32_t t_ = c.tid, g = (t_ >> 2) & 7; return XB + ((t_ >> 5) * 16 + g) * 128 + (g << 4) + (t_ & 3) * 4; };
        if (!is_main) {
            #pragma unroll
            for (int i = 0; i < 128; i++) a[i] = 0;
            #pragma unroll
            for (int i = 0; i < 32; i++) { hc[i] = 0.f; pv[i] = 0.f; }
        } else {
            uint32_t m00, m11;
            {
                uint32_t tl[16];
                const uint32_t lrow = lrow_off();
                float cs[2][4] = {{0.f, 0.f, 0.f, 0.f}, {0.f, 0.f, 0.f, 0.f}};
                sfor<0, 36>([&](auto KS) {
                    constexpr int ks = decltype(KS)::v;
                    if constexpr (ks % 12 == 0) mbar_wait(bar(B_XFULL + ks / 12), 0);
                    uint32_t* dst = (ks < 32) ? (a + (ks & 31) * 4) : (tl + (ks & 3) * 4);
                    ldsm4((lrow ^ ((ks % 4) << 5)) + (ks / 4) * 16384, dst);
                    mma_ones(cs[ks & 1], dst);
                });
                prof(2);
                float mean0 = (cs[0][0] + cs[1][0]) * (1.0f / 576.0f), mean1 = (cs[0][2] + cs[1][2]) * (1.0f / 576.0f);
                m00 = pack_bf16(mean0, mean0); m11 = pack_bf16(mean1, mean1);
                rs0 = mean0 - bf_lo(m00); rs1 = mean1 - bf_lo(m11);
                rs0 = -144.0f * rs0 * rs0; rs1 = -144.0f * rs1 * rs1;
                const uint32_t tb = tail_off();
                #pragma unroll
                for (int i = 0; i < 16; i++) {
                    const uint32_t w = sub_bf16x2(tl[i], (i & 1) ? m11 : m00);
                    sts32((tb ^ ((i >> 1) << 4)) + (i & 1) * 1024, w);
                    float lo = bf_lo(w), hi = bf_hi(w);
                    if (i & 1) rs1 = fmaf(lo, lo, fmaf(hi, hi, rs1)); else rs0 = fmaf(lo, lo, fmaf(hi, hi, rs0));
                }
                fence_async_smem();
                #pragma unroll
                for (int i = 0; i < 128; i++) a[i] = sub_bf16x2(a[i], (i & 1) ? m11 : m00);
                named_bar(2 + (tid >> 7), 128);
            }
            prof(3);
            auto cm_off = [&]() { uint32_t t_ = c.tid; return (t_ >> 5) * 256 + (t_ & 31) * 4; };
            {
                float qc[36];
                #pragma unroll
                for (int i = 0; i < 36; i++) { qc[i] = 0.f; pv[i] = 0.f; }
                #pragma unroll 1
                for (int s = 0; s < 3; s++) {
                    run_step<K_QKV>(c, qc, a, [&](auto ST) {
                        constexpr int st = decltype(ST)::v;
                        if (s == 0) {
                            const uint32_t lrow = lrow_off();
                            sfor<(st * 32) / 6, ((st + 1) * 32) / 6>([&](auto I) {
                                constexpr int ks = decltype(I)::v;
                                uint32_t v[4];
                                ldsm4((lrow ^ ((ks % 4) << 5)) + (ks / 4) * 16384, v);
                                #pragma unroll
                                for (int r = 0; r < 4; r++) {
                                    uint32_t w = sub_bf16x2(v[r], (r & 1) ? m11 : m00);
                                    float lo = bf_lo(w), hi = bf_hi(w);
                                    if (r & 1) rs1 = fmaf(lo, lo, fmaf(hi, hi, rs1)); else rs0 = fmaf(lo, lo, fmaf(hi, hi, rs0));
                                }
                            });
                            if constexpr (st == 5) {
                                rs0 += __shfl_xor_sync(0xffffffffu, rs0, 1); rs1 += __shfl_xor_sync(0xffffffffu, rs1, 1);
                                rs0 += __shfl_xor_sync(0xffffffffu, rs0, 2); rs1 += __shfl_xor_sync(0xffffffffu, rs1, 2);
                                rs0 = rsqrtf(fmaxf(rs0 * (1.0f / 576.0f), 0.f) + 1e-5f);
                                rs1 = rsqrtf(fmaxf(rs1 * (1.0f / 576.0f), 0.f) + 1e-5f);
                                named_bar(1, 256);
                            }
                        } else {
                            const uint32_t cm = cm_off();
                            sfor<0, 9>([&](auto B) {
                                constexpr int b = decltype(B)::v;
                                if constexpr ((b * 6) / 9 == st) {
                                    const float v0 = pv[4 * b] * rs0, v1 = pv[4 * b + 1] * rs0, v2 = pv[4 * b + 2] * rs1, v3 = pv[4 * b + 3] * rs1;
                                    if (s == 1) {
                                        sts32(PKT + b * 2048 + cm, pack_bf16(phi(v0), phi(v1)));
                                        sts32(PKT + b * 2048 + cm + 128, pack_bf16(phi(v2), phi(v3)));
                                    } else {
                                        const uint32_t w0 = pack_bf16(v0, v1), w1 = pack_bf16(v2, v3);
                                        if constexpr (b <= 4) { sts32(VT + b * 2048 + cm, w0); sts32(VT + b * 2048 + cm + 128, w1); }
                                        if constexpr (b >= 4) { sts32(VT + (b + 2) * 2048 + cm, w0); sts32(VT + (b + 2) * 2048 + cm + 128, w1); }
                                        if constexpr (b == 0) {
                                            const uint32_t one = (cm & 12) ? 0u : 0x00003F80u;
                                            sts32(VT + 5 * 2048 + cm, one); sts32(VT + 5 * 2048 + cm + 128, one);
                                        }
                                        if constexpr (b == 8) {
                                            const uint32_t z = KVB + c.tid * 16;
                                            sts128(z, 0, 0, 0, 0); sts128(z + 4096, 0, 0, 0, 0); sts128(z + 8192, 0, 0, 0, 0);
                                            if (z < KVB + 512) sts128(z + 12288, 0, 0, 0, 0);
                                            fence_async_smem();
                                        }
                                    }
                                }
                            });
                        }
                    }, [](auto) {});
                    reg_copy<36>(pv, qc);
                    prof(4 + s);
                }
            }
            {
                #pragma unroll
                for (int i = 0; i < 32; i++) hc[i] = 0.f;
                named_bar(1, 256);
                const uint32_t wgo = ((c.tid >> 7) * 512);
                wg_fence();
                sfor<0, 8>([&](auto KS) {
                    constexpr int ks = decltype(KS)::v;
                    wg_tt64<(ks ? 1 : 0)>(hc, mkdesc(PKT + ks * 256, 128, 2048, 0) + wgo,
                                          mkdesc(VT + ks * 256, 128, 2048, 0) + wgo + (wgo >> 2));
                });
                wg_commit();
                const uint32_t pq = PQT + cm_off() + ((c.tid >> 7) * 512) * 16;
                sfor<0, 9>([&](auto B) {
                    constexpr int b = decltype(B)::v;
                    sts32(pq + b * 1024, pack_bf16(phi(pv[4 * b] * rs0), phi(pv[4 * b + 1] * rs0)));
                    sts32(pq + b * 1024 + 128, pack_bf16(phi(pv[4 * b + 2] * rs1), phi(pv[4 * b + 3] * rs1)));
                });
                fence_async_smem();
                wg_wait<0>();
                reg_fence<32>(hc);
                reg_copy<24>(pv, hc);
            }
            prof(7);
            rs0 *= 0.5f; rs1 *= 0.5f;
        }
        {
            auto gelun = [&](auto B0, auto B1, uint32_t bofs, uint32_t* w) {
                constexpr int b0 = decltype(B0)::v, nb = decltype(B1)::v - b0;
                float2 bv[nb];
                #pragma unroll
                for (int i = 0; i < nb; i++) bv[i] = lds64f(bofs + (b0 + i) * 32);
                #pragma unroll
                for (int i = 0; i < nb; i++) {
                    const int b = b0 + i;
                    w[2 * i]     = pack_bf16(gelu_h(fmaf(pv[4 * b], rs0, bv[i].x)), gelu_h(fmaf(pv[4 * b + 1], rs0, bv[i].y)));
                    w[2 * i + 1] = pack_bf16(gelu_h(fmaf(pv[4 * b + 2], rs1, bv[i].x)), gelu_h(fmaf(pv[4 * b + 3], rs1, bv[i].y)));
                }
            };
            auto spill_off = [&]() { uint32_t t_ = c.tid; return HA + (t_ >> 7) * 8192 + (t_ & 127) * 8; };
            auto reload = [&](auto S0, auto S1) {
                const uint32_t spill = spill_off();
                sfor<decltype(S0)::v * 8, decltype(S1)::v * 8>([&](auto Q) {
                    constexpr int q = decltype(Q)::v;
                    lds64(spill + (q / 8) * 16384 + (q % 8) * 1024, a + q * 2);
                });
            };
            const int it_end = is_main ? 19 : 4;
            #pragma unroll 1
            for (int it = 0; it < it_end; it++) {
                const uint32_t b_ = v_bid();
                const bool mainf = b_ < NMAIN;
                const int idx = mainf ? it : 18;
                const uint32_t jpar = mainf ? 0 : (it & 1);
                const int ftile = mainf ? ((b_ >> 3) * 9 + (b_ & 7)) : (((b_ - NMAIN) * 4 + it) * 9 + 8);
                uint32_t xr[16];
                uint4 yv[4];
                auto out_off = [&]() {
                    const int mt = ftile / 9, ch = ftile - mt * 9;
                    return (size_t)(mt * 128 + (c.tid >> 5) * 16 + ((c.tid >> 2) & 7)) * DM + ch * 64 + 2 * (c.tid & 3);
                };
                if (idx == 18) {
                    mbar_wait(bar(B_OFULL), jpar);
                    const uint32_t lrow = lrow_off();
                    sfor<0, 32>([&](auto KS) {
                        constexpr int ks = decltype(KS)::v;
                        ldsm4((lrow ^ ((ks % 4) << 5)) + (ks / 4) * 16384, a + ks * 4);
                    });
                    warp_arrive(bar(B_OFREE));
                    if (!mainf) c.tph = 0;
                }
                run_step<K_H>(c, hc, a, [&](auto ST) {
                    constexpr int st = decltype(ST)::v;
                    if (idx == 18) {
                        if constexpr (st == 0) {
                            #pragma unroll
                            for (int b = 0; b < 8; b++) {
                                float2 bv = lds64f(B2S + b * 32 + (c.tid & 3) * 8);
                                pv[4 * b] += bv.x; pv[4 * b + 1] += bv.y; pv[4 * b + 2] += bv.x; pv[4 * b + 3] += bv.y;
                            }
                        } else if constexpr (st == 1) {
                            prof(26);
                            mbar_wait(bar(B_YRDY), jpar);
                            prof(27);
                            const unsigned char* yp = g_yacc + ((v_epoch() & 1) * 144 + ftile) * YT_BYTES + c.tid * 16;
                            #pragma unroll
                            for (int q = 0; q < 4; q++) yv[q] = __ldcg(reinterpret_cast<const uint4*>(yp + q * 4096));
                            if (!mainf) warp_arrive(bar(B_KVB));
                            mbar_wait(bar(B_O8FULL), jpar);
                        } else {
                            prof(28);
                            #pragma unroll
                            for (int q = 0; q < 4; q++) {
                                const uint4 u = yv[q];
                                pv[8 * q] += bf_lo(u.x); pv[8 * q + 1] += bf_hi(u.x); pv[8 * q + 2] += bf_lo(u.y); pv[8 * q + 3] += bf_hi(u.y);
                                pv[8 * q + 4] += bf_lo(u.z); pv[8 * q + 5] += bf_hi(u.z); pv[8 * q + 6] += bf_lo(u.w); pv[8 * q + 7] += bf_hi(u.w);
                            }
                            reg_fence<32>(pv);
                            const __nv_bfloat16* xp = p.x + out_off();
                            #pragma unroll
                            for (int i = 0; i < 8; i++) {
                                xr[2 * i] = __ldg(reinterpret_cast<const uint32_t*>(xp + i * 8));
                                xr[2 * i + 1] = __ldg(reinterpret_cast<const uint32_t*>(xp + 8 * DM + i * 8));
                            }
                            #pragma unroll
                            for (int i = 0; i < 32; i++) pv[i] = pv[i] * rcp(1.0f + ex2(pv[i] * -1.4426950408889634f));
                            prof(29);
                        }
                    } else
                    if (idx >= 10) {
                        if constexpr (st < 2) {
                            const uint32_t chunk = (idx == 10) ? 8 : ((b_ + idx - 10) & 7);
                            unsigned char* yp = g_yacc + ((v_epoch() & 1) * 144 + (b_ >> 3) * 9 + chunk) * YT_BYTES + c.tid * 16;
                            sfor<2 * st, 2 * st + 2>([&](auto Q) {
                                constexpr int q = decltype(Q)::v;
                                asm volatile("red.global.add.noftz.v4.bf16x2 [%0], {%1,%2,%3,%4};" :: "l"(yp + q * 4096),
                                             "r"(pack_bf16(pv[8 * q], pv[8 * q + 1])), "r"(pack_bf16(pv[8 * q + 2], pv[8 * q + 3])),
                                             "r"(pack_bf16(pv[8 * q + 4], pv[8 * q + 5])), "r"(pack_bf16(pv[8 * q + 6], pv[8 * q + 7])) : "memory");
                            });
                            if constexpr (st == 1) event(idx - 7);
                        }
                    } else if (idx >= 1) {
                        const uint32_t bofs = B1S + (idx - 1) * 256 + (c.tid & 3) * 8;
                        if (idx < 9) {
                            if constexpr (st == 0) { if (idx == OSTEP_AT + 1) event(2); }
                            const uint32_t spill = spill_off() + (idx - 1) * 16384;
                            constexpr int b0 = st * 3, b1 = (st == 2 ? 8 : st * 3 + 3);
                            uint32_t w[6];
                            gelun(IC<b0>{}, IC<b1>{}, bofs, w);
                            #pragma unroll
                            for (int b = b0; b < b1; b++) sts64(spill + b * 1024, w[2 * (b - b0)], w[2 * (b - b0) + 1]);
                        } else {
                            if constexpr (st < 2) {
                                const uint32_t tb = tail_off();
                                uint32_t w[8];
                                gelun(IC<st * 4>{}, IC<st * 4 + 4>{}, bofs, w);
                                #pragma unroll
                                for (int i = 0; i < 4; i++) { sts32(tb ^ ((st * 4 + i) << 4), w[2 * i]); sts32((tb ^ ((st * 4 + i) << 4)) + 1024, w[2 * i + 1]); }
                            }
                            if constexpr (st == 1) { fence_async_smem(); named_bar(2 + (c.tid >> 7), 128); }
                        }
                    } else {
                        if constexpr (st < 2) {
                            constexpr int hf = st;
                            const int t_ = c.tid, wg = t_ >> 7, t = t_ & 3;
                            float* dst = g_kv + ((v_epoch() & 1) * 8 + (v_bid() & 7)) * 1440;
                            const int d = wg * 32 + ((t_ >> 5) & 3) * 16 + ((t_ >> 2) & 7) + hf * 8;
                            const bool dv = wg ? (d >= 36 && d < 72) : (d < 36);
                            const int e00 = wg * 24 + 2 * t - (d / 18) * 18;
                            float* dp = dst + d * 20 + e00;
                            #pragma unroll
                            for (int i = 0; i < 6; i++) {
                                const int e = e00 + i * 8;
                                const bool blk = wg ? (i >= 1) : (i <= 4);
                                if (dv && blk && e >= 0 && e < 18)
                                    asm volatile("red.global.add.v2.f32 [%0], {%1,%2};" :: "l"(dp + i * 8), "f"(pv[4 * i + 2 * hf]), "f"(pv[4 * i + 2 * hf + 1]) : "memory");
                            }
                            if (dv && t == 0) atomicAdd(dst + d * 20 + 18, wg ? pv[2 * hf] : pv[20 + 2 * hf]);
                            if constexpr (st == 1) event(1);
                        }
                    }
                }, [&](auto ST) {
                    constexpr int st = decltype(ST)::v;
                    if (idx == 8) {
                        reload(IC<3 * st>{}, IC<(st == 2 ? 8 : 3 * st + 3)>{});
                        if constexpr (st == 2) warp_arrive(bar(B_OFREE));
                    }
                }, it == it_end - 1);
                if (idx >= 17) warp_arrive(bar(B_O8FREE));
                if (idx == 18) {
                    prof(30);
                    __nv_bfloat16* op = p.out + out_off();
                    #pragma unroll
                    for (int b = 0; b < 8; b++) {
                        *reinterpret_cast<uint32_t*>(op + b * 8) =
                            pack_bf16(fmaf(hc[4 * b], pv[4 * b], bf_lo(xr[2 * b])), fmaf(hc[4 * b + 1], pv[4 * b + 1], bf_hi(xr[2 * b])));
                        *reinterpret_cast<uint32_t*>(op + 8 * DM + b * 8) =
                            pack_bf16(fmaf(hc[4 * b + 2], pv[4 * b + 2], bf_lo(xr[2 * b + 1])), fmaf(hc[4 * b + 3], pv[4 * b + 3], bf_hi(xr[2 * b + 1])));
                    }
                    #pragma unroll
                    for (int i = 0; i < 32; i++) pv[i] = 0.f;
                    if (!mainf) prof(8 + it);
                } else {
                    reg_copy<32>(pv, hc);
                    prof(8 + idx);
                }
                if (idx == OSTEP_AT) {
                    mbar_wait(bar(B_KVB), 0);
                    prof(34);
                    const uint32_t pqo = (c.tid >> 7) * 576;
                    const int t_ = c.tid, t = t_ & 3, l4 = t_ & 28;
                    __nv_bfloat16* op = g_o + (size_t)((b_ >> 3) * 128 + (t_ >> 5) * 16 + ((t_ >> 2) & 7)) * DM + (b_ & 7) * 72 + 2 * t;
                    float r3[2];
                    sfor<0, 2>([&](auto PS) {
                        constexpr int ps = decltype(PS)::v;
                        wg_fence();
                        sfor<0, 5>([&](auto KS) {
                            constexpr int ks = decltype(KS)::v;
                            wg_ss64<(ks ? 1 : 0)>(hc, mkdesc(PQT + ks * 2048, ks == 4 ? 0 : 1024, 128, 0) + pqo, mkdesc(KVB + ps * 8 * 1280 + ks * 256, 128, 1280, 0));
                        });
                        wg_commit();
                        wg_wait<0>();
                        reg_fence<32>(hc);
                        #pragma unroll
                        for (int hf = 0; hf < 2; hf++) {
                            if constexpr (ps == 0) {
                                float r[4];
                                r[0] = rcp(__shfl_sync(0xffffffffu, hc[2 * hf], l4) + 1e-6f);
                                r[1] = rcp(__shfl_sync(0xffffffffu, hc[1 + 2 * hf], l4) + 1e-6f);
                                r[2] = rcp(__shfl_sync(0xffffffffu, hc[2 * hf], l4 + 1) + 1e-6f);
                                r[3] = rcp(__shfl_sync(0xffffffffu, hc[1 + 2 * hf], l4 + 1) + 1e-6f);
                                r3[hf] = r[3];
                                #pragma unroll
                                for (int i = 0; i < 7; i++) {
                                    float rr = (i < 2) ? r[0] : (i == 2) ? (t < 1 ? r[0] : r[1]) : (i == 3) ? r[1] : (i == 4) ? (t < 2 ? r[1] : r[2])
                                             : (i == 5) ? r[2] : (t < 3 ? r[2] : r[3]);
                                    *reinterpret_cast<uint32_t*>(op + hf * 8 * DM + i * 8) = pack_bf16(hc[4 * i + 4 + 2 * hf] * rr, hc[4 * i + 5 + 2 * hf] * rr);
                                }
                            } else {
                                #pragma unroll
                                for (int i = 0; i < 2; i++)
                                    *reinterpret_cast<uint32_t*>(op + hf * 8 * DM + 56 + i * 8) = pack_bf16(hc[4 * i + 2 * hf] * r3[hf], hc[4 * i + 1 + 2 * hf] * r3[hf]);
                            }
                        }
                    });
                }
            }
        }
        prof(40);
        if (c.tid == 0) g_epoch[v_bid()] = v_epoch() + 1;
    }
}

typedef CUresult (*EncodeFn)(CUtensorMap*, CUtensorMapDataType, cuuint32_t, void*, const cuuint64_t*, const cuuint64_t*,
                             const cuuint32_t*, const cuuint32_t*, CUtensorMapInterleave, CUtensorMapSwizzle,
                             CUtensorMapL2promotion, CUtensorMapFloatOOBfill);

void make_map(EncodeFn enc, CUtensorMap* tm, const void* base, int rows, int cols, int box_rows, int box_cols = 64) {
    cuuint64_t gdim[2] = {(cuuint64_t)cols, (cuuint64_t)rows};
    cuuint64_t gstr[1] = {(cuuint64_t)cols * 2};
    cuuint32_t box[2] = {(cuuint32_t)box_cols, (cuuint32_t)box_rows};
    cuuint32_t estr[2] = {1, 1};
    enc(tm, CU_TENSOR_MAP_DATA_TYPE_BFLOAT16, 2, const_cast<void*>(base), gdim, gstr, box, estr, CU_TENSOR_MAP_INTERLEAVE_NONE,
        CU_TENSOR_MAP_SWIZZLE_128B, CU_TENSOR_MAP_L2_PROMOTION_L2_128B, CU_TENSOR_MAP_FLOAT_OOB_FILL_NONE);
}

}

extern "C" void kernel_launch(void* const* d_in, const int* in_sizes, int n_in, void* d_out, int out_size) {
    static EncodeFn enc = nullptr;
    static void* o_ptr = nullptr;
    if (!enc) {
        void* fn = nullptr;
        cudaDriverEntryPointQueryResult qr;
        cudaGetDriverEntryPoint("cuTensorMapEncodeTiled", &fn, cudaEnableDefault, &qr);
        enc = (EncodeFn)fn;
        cudaGetSymbolAddress(&o_ptr, g_o);
        cudaFuncSetAttribute(fused_kernel, cudaFuncAttributeMaxDynamicSharedMemorySize, SMEM_BYTES);
    }
    Params p;
    p.x = (const __nv_bfloat16*)d_in[0];
    p.wqkv = (const __nv_bfloat16*)d_in[1];
    p.wo = (const __nv_bfloat16*)d_in[2];
    p.w1 = (const __nv_bfloat16*)d_in[4];
    p.b1 = (const __nv_bfloat16*)d_in[5];
    p.w2 = (const __nv_bfloat16*)d_in[6];
    p.b2 = (const __nv_bfloat16*)d_in[7];
    p.out = (__nv_bfloat16*)d_out;
    CUtensorMap tm_x, tm_w1, tm_w2, tm_wo, tm_o, tm_qkv, tm_qkve;
    make_map(enc, &tm_qkv, p.wqkv, DM, 3 * DM, 96);
    make_map(enc, &tm_qkve, p.wqkv, DM, 3 * DM, 96, 8);
    make_map(enc, &tm_x, p.x, SEQ, DM, 128);
    make_map(enc, &tm_w1, p.w1, DM, FF, 192);
    make_map(enc, &tm_w2, p.w2, FF, DM, 192);
    make_map(enc, &tm_wo, p.wo, DM, DM, 192);
    make_map(enc, &tm_o, o_ptr, SEQ, DM, 128);
    fused_kernel<<<NMAIN + NAUX, 384, SMEM_BYTES>>>(tm_x, tm_w1, tm_w2, tm_wo, tm_o, tm_qkv, tm_qkve, p);
}
```

```cpp
#include <cuda_runtime.h>
#include <cuda.h>
#include <cuda_bf16.h>
#include <stdint.h>

#define OSTEP_AT 4
#define KNOB_A 1
#define KNOB_B 0
#define PF1_NS 1000
#define PF2_NS 2000
#define PFIDX 3
#define PF3_NS 800
#define YF32 0

namespace {
constexpr int WAIT_ITERS = 3000000;

constexpr int SEQ = 2048, DM = 576, FF = 4608;
constexpr int NMAIN = 128, NAUX = 4;

constexpr uint32_t SB    = 0x400;
constexpr uint32_t HA    = SB;
constexpr uint32_t XB    = SB + 131072;
constexpr uint32_t RING  = SB + 147456;
constexpr uint32_t SLOT  = 24576;
constexpr uint32_t MISC  = SB + 221184;
constexpr uint32_t BARS  = MISC;
constexpr uint32_t B1S   = MISC + 512;
constexpr uint32_t B2S   = MISC + 2816;
constexpr uint32_t EPO   = MISC + 3072;
constexpr uint32_t EVC   = MISC + 3104;
constexpr uint32_t SMEM_BYTES = 221184 + 3200 + 512;
constexpr uint32_t PKT   = HA + 32768;
constexpr uint32_t VT    = HA + 51200;
constexpr uint32_t PQT   = HA + 98304;
constexpr uint32_t KVB   = HA + 116736;

enum { B_FULL = 0, B_EMPTY = 3, B_XFULL = 6, B_OFULL = 9, B_O8FULL = 10, B_OFREE = 11, B_O8FREE = 12, B_KVB = 13, B_YRDY = 14, B_COUNT = 15 };
__device__ __forceinline__ constexpr uint32_t bar(int i) { return BARS + 8u * i; }

constexpr int YT_BYTES = YF32 ? 32768 : 16384;
__device__ __align__(1024) __nv_bfloat16 g_o[SEQ * DM];
__device__ __align__(1024) unsigned char g_yacc[2 * 16 * 9 * YT_BYTES];
__device__ __align__(128) float g_kv[2 * 8 * 72 * 20];
__device__ __align__(128) unsigned int g_cnt[(8 + 16 + 16 * 9) * 8];
__device__ unsigned int g_epoch[NMAIN + NAUX];
__device__ __forceinline__ unsigned int* cnt_kv(int j) { return g_cnt + j * 8; }
__device__ __forceinline__ unsigned int* cnt_o(int m) { return g_cnt + (8 + m) * 8; }
__device__ __forceinline__ unsigned int* cnt_y(int m, int c) { return g_cnt + (24 + m * 9 + c) * 8; }

__device__ __forceinline__ void mbar_init(uint32_t b, uint32_t cnt) { asm volatile("mbarrier.init.shared::cta.b64 [%0], %1;" :: "r"(b), "r"(cnt)); }
__device__ __forceinline__ void mbar_expect_tx(uint32_t b, uint32_t bytes) { asm volatile("mbarrier.arrive.expect_tx.shared::cta.b64 _, [%0], %1;" :: "r"(b), "r"(bytes) : "memory"); }
__device__ __forceinline__ void mbar_arrive(uint32_t b) { asm volatile("mbarrier.arrive.shared::cta.b64 _, [%0];" :: "r"(b) : "memory"); }
__device__ __forceinline__ void prof(int) {}
__device__ __forceinline__ void mbar_wait(uint32_t b, uint32_t parity) {
    asm volatile("{\n.reg .pred p;\n.reg .u32 c;\nmov.u32 c, 0;\n"
                 "WAIT_LOOP:\nmbarrier.try_wait.parity.shared::cta.b64 p, [%0], %1;\n@p bra WAIT_DONE;\n"
                 "add.u32 c, c, 1;\nsetp.lt.u32 p, c, 4000000;\n@p bra WAIT_LOOP;\ntrap;\nWAIT_DONE:\n}"
                 :: "r"(b), "r"(parity) : "memory");
}
__device__ __forceinline__ void tma_2d(uint32_t dst, const CUtensorMap* tm, uint32_t b, int c0, int c1) {
    asm volatile("cp.async.bulk.tensor.2d.shared::cluster.global.mbarrier::complete_tx::bytes [%0], [%1, {%3, %4}], [%2];"
                 :: "r"(dst), "l"(tm), "r"(b), "r"(c0), "r"(c1) : "memory");
}
__device__ __forceinline__ void fence_async_smem() { asm volatile("fence.proxy.async.shared::cta;" ::: "memory"); }
__device__ __forceinline__ void fence_async_all() { asm volatile("fence.proxy.async;" ::: "memory"); }
__device__ __forceinline__ void named_bar(int id, int n) { asm volatile("bar.sync %0, %1;" :: "r"(id), "r"(n) : "memory"); }
__device__ __forceinline__ void wg_fence() { asm volatile("wgmma.fence.sync.aligned;" ::: "memory"); }
__device__ __forceinline__ void wg_commit() { asm volatile("wgmma.commit_group.sync.aligned;" ::: "memory"); }
template<int N> __device__ __forceinline__ void wg_wait() { asm volatile("wgmma.wait_group.sync.aligned %0;" :: "n"(N) : "memory"); }
template<int N> __device__ __forceinline__ void reg_fence(float* d) {
    #pragma unroll
    for (int i = 0; i < N; i++) asm volatile("" : "+f"(d[i]) :: "memory");
}
template<int N> __device__ __forceinline__ void reg_copy(float* d, const float* s) {
    #pragma unroll
    for (int i = 0; i < N; i++) asm volatile("mov.b32 %0, %1;" : "=f"(d[i]) : "f"(s[i]));
}
__device__ __forceinline__ uint32_t pack_bf16(float lo, float hi) { uint32_t r; asm("cvt.rn.bf16x2.f32 %0, %1, %2;" : "=r"(r) : "f"(hi), "f"(lo)); return r; }
__device__ __forceinline__ float bf_lo(uint32_t v) { return __uint_as_float(v << 16); }
__device__ __forceinline__ float bf_hi(uint32_t v) { return __uint_as_float(v & 0xffff0000u); }
__device__ __forceinline__ uint32_t sub_bf16x2(uint32_t a, uint32_t b) { uint32_t r; asm("sub.rn.bf16x2 %0, %1, %2;" : "=r"(r) : "r"(a), "r"(b)); return r; }
__device__ __forceinline__ float ex2(float x) { float r; asm("ex2.approx.ftz.f32 %0, %1;" : "=f"(r) : "f"(x)); return r; }
__device__ __forceinline__ float rcp(float x) { float r; asm("rcp.approx.ftz.f32 %0, %1;" : "=f"(r) : "f"(x)); return r; }
__device__ __forceinline__ float tanh_ap(float x) { float r; asm("tanh.approx.f32 %0, %1;" : "=f"(r) : "f"(x)); return r; }
__device__ __forceinline__ void sts32(uint32_t a, uint32_t v) { asm volatile("st.shared.b32 [%0], %1;" :: "r"(a), "r"(v)); }
__device__ __forceinline__ void sts128(uint32_t a, uint32_t x, uint32_t y, uint32_t z, uint32_t w) { asm volatile("st.shared.v4.b32 [%0], {%1,%2,%3,%4};" :: "r"(a), "r"(x), "r"(y), "r"(z), "r"(w)); }
__device__ __forceinline__ void sts64(uint32_t a, uint32_t x, uint32_t y) { asm volatile("st.shared.v2.b32 [%0], {%1,%2};" :: "r"(a), "r"(x), "r"(y)); }
__device__ __forceinline__ void lds64(uint32_t a, uint32_t* v) { asm volatile("ld.shared.v2.b32 {%0,%1}, [%2];" : "=r"(v[0]), "=r"(v[1]) : "r"(a)); }
__device__ __forceinline__ void lds128(uint32_t a, uint32_t* v) { asm volatile("ld.shared.v4.b32 {%0,%1,%2,%3}, [%4];" : "=r"(v[0]), "=r"(v[1]), "=r"(v[2]), "=r"(v[3]) : "r"(a) : "memory"); }
__device__ __forceinline__ float2 lds64f(uint32_t a) { float2 v; asm("ld.shared.v2.f32 {%0,%1}, [%2];" : "=f"(v.x), "=f"(v.y) : "r"(a)); return v; }
__device__ __forceinline__ void ldsm4(uint32_t a, uint32_t* v) {
    asm volatile("ldmatrix.sync.aligned.m8n8.x4.shared.b16 {%0,%1,%2,%3}, [%4];" : "=r"(v[0]), "=r"(v[1]), "=r"(v[2]), "=r"(v[3]) : "r"(a));
}
__device__ __forceinline__ void mma_ones(float* c, const uint32_t* a) {
    const uint32_t one2 = 0x3F803F80u;
    asm volatile("mma.sync.aligned.m16n8k16.row.col.f32.bf16.bf16.f32 {%0,%1,%2,%3}, {%4,%5,%6,%7}, {%8,%8}, {%0,%1,%2,%3};"
                 : "+f"(c[0]), "+f"(c[1]), "+f"(c[2]), "+f"(c[3]) : "r"(a[0]), "r"(a[1]), "r"(a[2]), "r"(a[3]), "r"(one2));
}
__device__ __forceinline__ unsigned int ld_acquire(const unsigned int* p) { unsigned int v; asm volatile("ld.acquire.gpu.global.u32 %0, [%1];" : "=r"(v) : "l"(p) : "memory"); return v; }
__device__ __forceinline__ void wait_cnt(const unsigned int* p, unsigned int target) {
    for (int i = 0; i < WAIT_ITERS; i++) {
        if ((int)(ld_acquire(p) - target) >= 0) return;
        __nanosleep(40);
    }
    __trap();
}
__device__ __forceinline__ uint32_t v_tid() { uint32_t r; asm volatile("mov.u32 %0, %%tid.x;" : "=r"(r)); return r; }
__device__ __forceinline__ uint32_t v_bid() { uint32_t r; asm volatile("mov.u32 %0, %%ctaid.x;" : "=r"(r)); return r; }
__device__ __forceinline__ uint32_t v_epoch() { uint32_t r; asm volatile("ld.shared.u32 %0, [%1];" : "=r"(r) : "r"(EPO)); return r; }
__device__ __forceinline__ void prefetch_l2(const void* p) { asm volatile("prefetch.global.L2 [%0];" :: "l"(p)); }

__host__ __device__ constexpr uint64_t mkdesc(uint32_t addr, uint32_t lbo, uint32_t sbo, uint32_t swz) {
    return (uint64_t)((addr & 0x3FFFF) >> 4) | ((uint64_t)((lbo >> 4) & 0x3FFF) << 16) | ((uint64_t)((sbo >> 4) & 0x3FFF) << 32) | ((uint64_t)swz << 62);
}

template<int SD> __device__ __forceinline__ void wg_rs64(float* d, const uint32_t* a, uint64_t bd) {
  if constexpr (SD) {
    asm volatile("{\n.reg .pred p;\nsetp.eq.b32 p, 0, 0;\n"
    "wgmma.mma_async.sync.aligned.m64n64k16.f32.bf16.bf16 {%0,%1,%2,%3,%4,%5,%6,%7,%8,%9,%10,%11,%12,%13,%14,%15,%16,%17,%18,%19,%20,%21,%22,%23,%24,%25,%26,%27,%28,%29,%30,%31}, {%32,%33,%34,%35}, %36, p, 1, 1, 1;\n}"
    : "+f"(d[0]),"+f"(d[1]),"+f"(d[2]),"+f"(d[3]),"+f"(d[4]),"+f"(d[5]),"+f"(d[6]),"+f"(d[7]),"+f"(d[8]),"+f"(d[9]),"+f"(d[10]),"+f"(d[11]),"+f"(d[12]),"+f"(d[13]),"+f"(d[14]),"+f"(d[15]),"+f"(d[16]),"+f"(d[17]),"+f"(d[18]),"+f"(d[19]),"+f"(d[20]),"+f"(d[21]),"+f"(d[22]),"+f"(d[23]),"+f"(d[24]),"+f"(d[25]),"+f"(d[26]),"+f"(d[27]),"+f"(d[28]),"+f"(d[29]),"+f"(d[30]),"+f"(d[31])
    : "r"(a[0]),"r"(a[1]),"r"(a[2]),"r"(a[3]), "l"(bd));
  } else {
    asm volatile("{\n.reg .pred p;\nsetp.ne.b32 p, 0, 0;\n"
    "wgmma.mma_async.sync.aligned.m64n64k16.f32.bf16.bf16 {%0,%1,%2,%3,%4,%5,%6,%7,%8,%9,%10,%11,%12,%13,%14,%15,%16,%17,%18,%19,%20,%21,%22,%23,%24,%25,%26,%27,%28,%29,%30,%31}, {%32,%33,%34,%35}, %36, p, 1, 1, 1;\n}"
    : "+f"(d[0]),"+f"(d[1]),"+f"(d[2]),"+f"(d[3]),"+f"(d[4]),"+f"(d[5]),"+f"(d[6]),"+f"(d[7]),"+f"(d[8]),"+f"(d[9]),"+f"(d[10]),"+f"(d[11]),"+f"(d[12]),"+f"(d[13]),"+f"(d[14]),"+f"(d[15]),"+f"(d[16]),"+f"(d[17]),"+f"(d[18]),"+f"(d[19]),"+f"(d[20]),"+f"(d[21]),"+f"(d[22]),"+f"(d[23]),"+f"(d[24]),"+f"(d[25]),"+f"(d[26]),"+f"(d[27]),"+f"(d[28]),"+f"(d[29]),"+f"(d[30]),"+f"(d[31])
    : "r"(a[0]),"r"(a[1]),"r"(a[2]),"r"(a[3]), "l"(bd));
  }
}
template<int SD> __device__ __forceinline__ void wg_ss64(float* d, uint64_t ad, uint64_t bd) {
  if constexpr (SD) {
    asm volatile("{\n.reg .pred p;\nsetp.eq.b32 p, 0, 0;\n"
    "wgmma.mma_async.sync.aligned.m64n64k16.f32.bf16.bf16 {%0,%1,%2,%3,%4,%5,%6,%7,%8,%9,%10,%11,%12,%13,%14,%15,%16,%17,%18,%19,%20,%21,%22,%23,%24,%25,%26,%27,%28,%29,%30,%31}, %32, %33, p, 1, 1, 0, 1;\n}"
    : "+f"(d[0]),"+f"(d[1]),"+f"(d[2]),"+f"(d[3]),"+f"(d[4]),"+f"(d[5]),"+f"(d[6]),"+f"(d[7]),"+f"(d[8]),"+f"(d[9]),"+f"(d[10]),"+f"(d[11]),"+f"(d[12]),"+f"(d[13]),"+f"(d[14]),"+f"(d[15]),"+f"(d[16]),"+f"(d[17]),"+f"(d[18]),"+f"(d[19]),"+f"(d[20]),"+f"(d[21]),"+f"(d[22]),"+f"(d[23]),"+f"(d[24]),"+f"(d[25]),"+f"(d[26]),"+f"(d[27]),"+f"(d[28]),"+f"(d[29]),"+f"(d[30]),"+f"(d[31])
    : "l"(ad), "l"(bd));
  } else {
    asm volatile("{\n.reg .pred p;\nsetp.ne.b32 p, 0, 0;\n"
    "wgmma.mma_async.sync.aligned.m64n64k16.f32.bf16.bf16 {%0,%1,%2,%3,%4,%5,%6,%7,%8,%9,%10,%11,%12,%13,%14,%15,%16,%17,%18,%19,%20,%21,%22,%23,%24,%25,%26,%27,%28,%29,%30,%31}, %32, %33, p, 1, 1, 0, 1;\n}"
    : "+f"(d[0]),"+f"(d[1]),"+f"(d[2]),"+f"(d[3]),"+f"(d[4]),"+f"(d[5]),"+f"(d[6]),"+f"(d[7]),"+f"(d[8]),"+f"(d[9]),"+f"(d[10]),"+f"(d[11]),"+f"(d[12]),"+f"(d[13]),"+f"(d[14]),"+f"(d[15]),"+f"(d[16]),"+f"(d[17]),"+f"(d[18]),"+f"(d[19]),"+f"(d[20]),"+f"(d[21]),"+f"(d[22]),"+f"(d[23]),"+f"(d[24]),"+f"(d[25]),"+f"(d[26]),"+f"(d[27]),"+f"(d[28]),"+f"(d[29]),"+f"(d[30]),"+f"(d[31])
    : "l"(ad), "l"(bd));
  }
}
template<int SD> __device__ __forceinline__ void wg_rs72(float* d, const uint32_t* a, uint64_t bd) {
  if constexpr (SD) {
    asm volatile("{\n.reg .pred p;\nsetp.eq.b32 p, 0, 0;\n"
    "wgmma.mma_async.sync.aligned.m64n72k16.f32.bf16.bf16 {%0,%1,%2,%3,%4,%5,%6,%7,%8,%9,%10,%11,%12,%13,%14,%15,%16,%17,%18,%19,%20,%21,%22,%23,%24,%25,%26,%27,%28,%29,%30,%31,%32,%33,%34,%35}, {%36,%37,%38,%39}, %40, p, 1, 1, 1;\n}"
    : "+f"(d[0]),"+f"(d[1]),"+f"(d[2]),"+f"(d[3]),"+f"(d[4]),"+f"(d[5]),"+f"(d[6]),"+f"(d[7]),"+f"(d[8]),"+f"(d[9]),"+f"(d[10]),"+f"(d[11]),"+f"(d[12]),"+f"(d[13]),"+f"(d[14]),"+f"(d[15]),"+f"(d[16]),"+f"(d[17]),"+f"(d[18]),"+f"(d[19]),"+f"(d[20]),"+f"(d[21]),"+f"(d[22]),"+f"(d[23]),"+f"(d[24]),"+f"(d[25]),"+f"(d[26]),"+f"(d[27]),"+f"(d[28]),"+f"(d[29]),"+f"(d[30]),"+f"(d[31]),"+f"(d[32]),"+f"(d[33]),"+f"(d[34]),"+f"(d[35])
    : "r"(a[0]),"r"(a[1]),"r"(a[2]),"r"(a[3]), "l"(bd));
  } else {
    asm volatile("{\n.reg .pred p;\nsetp.ne.b32 p, 0, 0;\n"
    "wgmma.mma_async.sync.aligned.m64n72k16.f32.bf16.bf16 {%0,%1,%2,%3,%4,%5,%6,%7,%8,%9,%10,%11,%12,%13,%14,%15,%16,%17,%18,%19,%20,%21,%22,%23,%24,%25,%26,%27,%28,%29,%30,%31,%32,%33,%34,%35}, {%36,%37,%38,%39}, %40, p, 1, 1, 1;\n}"
    : "+f"(d[0]),"+f"(d[1]),"+f"(d[2]),"+f"(d[3]),"+f"(d[4]),"+f"(d[5]),"+f"(d[6]),"+f"(d[7]),"+f"(d[8]),"+f"(d[9]),"+f"(d[10]),"+f"(d[11]),"+f"(d[12]),"+f"(d[13]),"+f"(d[14]),"+f"(d[15]),"+f"(d[16]),"+f"(d[17]),"+f"(d[18]),"+f"(d[19]),"+f"(d[20]),"+f"(d[21]),"+f"(d[22]),"+f"(d[23]),"+f"(d[24]),"+f"(d[25]),"+f"(d[26]),"+f"(d[27]),"+f"(d[28]),"+f"(d[29]),"+f"(d[30]),"+f"(d[31]),"+f"(d[32]),"+f"(d[33]),"+f"(d[34]),"+f"(d[35])
    : "r"(a[0]),"r"(a[1]),"r"(a[2]),"r"(a[3]), "l"(bd));
  }
}
template<int SD> __device__ __forceinline__ void wg_ss72(float* d, uint64_t ad, uint64_t bd) {
  if constexpr (SD) {
    asm volatile("{\n.reg .pred p;\nsetp.eq.b32 p, 0, 0;\n"
    "wgmma.mma_async.sync.aligned.m64n72k16.f32.bf16.bf16 {%0,%1,%2,%3,%4,%5,%6,%7,%8,%9,%10,%11,%12,%13,%14,%15,%16,%17,%18,%19,%20,%21,%22,%23,%24,%25,%26,%27,%28,%29,%30,%31,%32,%33,%34,%35}, %36, %37, p, 1, 1, 0, 1;\n}"
    : "+f"(d[0]),"+f"(d[1]),"+f"(d[2]),"+f"(d[3]),"+f"(d[4]),"+f"(d[5]),"+f"(d[6]),"+f"(d[7]),"+f"(d[8]),"+f"(d[9]),"+f"(d[10]),"+f"(d[11]),"+f"(d[12]),"+f"(d[13]),"+f"(d[14]),"+f"(d[15]),"+f"(d[16]),"+f"(d[17]),"+f"(d[18]),"+f"(d[19]),"+f"(d[20]),"+f"(d[21]),"+f"(d[22]),"+f"(d[23]),"+f"(d[24]),"+f"(d[25]),"+f"(d[26]),"+f"(d[27]),"+f"(d[28]),"+f"(d[29]),"+f"(d[30]),"+f"(d[31]),"+f"(d[32]),"+f"(d[33]),"+f"(d[34]),"+f"(d[35])
    : "l"(ad), "l"(bd));
  } else {
    asm volatile("{\n.reg .pred p;\nsetp.ne.b32 p, 0, 0;\n"
    "wgmma.mma_async.sync.aligned.m64n72k16.f32.bf16.bf16 {%0,%1,%2,%3,%4,%5,%6,%7,%8,%9,%10,%11,%12,%13,%14,%15,%16,%17,%18,%19,%20,%21,%22,%23,%24,%25,%26,%27,%28,%29,%30,%31,%32,%33,%34,%35}, %36, %37, p, 1, 1, 0, 1;\n}"
    : "+f"(d[0]),"+f"(d[1]),"+f"(d[2]),"+f"(d[3]),"+f"(d[4]),"+f"(d[5]),"+f"(d[6]),"+f"(d[7]),"+f"(d[8]),"+f"(d[9]),"+f"(d[10]),"+f"(d[11]),"+f"(d[12]),"+f"(d[13]),"+f"(d[14]),"+f"(d[15]),"+f"(d[16]),"+f"(d[17]),"+f"(d[18]),"+f"(d[19]),"+f"(d[20]),"+f"(d[21]),"+f"(d[22]),"+f"(d[23]),"+f"(d[24]),"+f"(d[25]),"+f"(d[26]),"+f"(d[27]),"+f"(d[28]),"+f"(d[29]),"+f"(d[30]),"+f"(d[31]),"+f"(d[32]),"+f"(d[33]),"+f"(d[34]),"+f"(d[35])
    : "l"(ad), "l"(bd));
  }
}
template<int SD> __device__ __forceinline__ void wg_tt64(float* d, uint64_t ad, uint64_t bd) {
  if constexpr (SD) {
    asm volatile("{\n.reg .pred p;\nsetp.eq.b32 p, 0, 0;\n"
    "wgmma.mma_async.sync.aligned.m64n64k16.f32.bf16.bf16 {%0,%1,%2,%3,%4,%5,%6,%7,%8,%9,%10,%11,%12,%13,%14,%15,%16,%17,%18,%19,%20,%21,%22,%23,%24,%25,%26,%27,%28,%29,%30,%31}, %32, %33, p, 1, 1, 1, 1;\n}"
    : "+f"(d[0]),"+f"(d[1]),"+f"(d[2]),"+f"(d[3]),"+f"(d[4]),"+f"(d[5]),"+f"(d[6]),"+f"(d[7]),"+f"(d[8]),"+f"(d[9]),"+f"(d[10]),"+f"(d[11]),"+f"(d[12]),"+f"(d[13]),"+f"(d[14]),"+f"(d[15]),"+f"(d[16]),"+f"(d[17]),"+f"(d[18]),"+f"(d[19]),"+f"(d[20]),"+f"(d[21]),"+f"(d[22]),"+f"(d[23]),"+f"(d[24]),"+f"(d[25]),"+f"(d[26]),"+f"(d[27]),"+f"(d[28]),"+f"(d[29]),"+f"(d[30]),"+f"(d[31])
    : "l"(ad), "l"(bd));
  } else {
    asm volatile("{\n.reg .pred p;\nsetp.ne.b32 p, 0, 0;\n"
    "wgmma.mma_async.sync.aligned.m64n64k16.f32.bf16.bf16 {%0,%1,%2,%3,%4,%5,%6,%7,%8,%9,%10,%11,%12,%13,%14,%15,%16,%17,%18,%19,%20,%21,%22,%23,%24,%25,%26,%27,%28,%29,%30,%31}, %32, %33, p, 1, 1, 1, 1;\n}"
    : "+f"(d[0]),"+f"(d[1]),"+f"(d[2]),"+f"(d[3]),"+f"(d[4]),"+f"(d[5]),"+f"(d[6]),"+f"(d[7]),"+f"(d[8]),"+f"(d[9]),"+f"(d[10]),"+f"(d[11]),"+f"(d[12]),"+f"(d[13]),"+f"(d[14]),"+f"(d[15]),"+f"(d[16]),"+f"(d[17]),"+f"(d[18]),"+f"(d[19]),"+f"(d[20]),"+f"(d[21]),"+f"(d[22]),"+f"(d[23]),"+f"(d[24]),"+f"(d[25]),"+f"(d[26]),"+f"(d[27]),"+f"(d[28]),"+f"(d[29]),"+f"(d[30]),"+f"(d[31])
    : "l"(ad), "l"(bd));
  }
}

template<int V> struct IC { static constexpr int v = V; };
template<int I, int N, class F> __device__ __forceinline__ void sfor(F&& f) {
    if constexpr (I < N) { f(IC<I>{}); sfor<I + 1, N>(f); }
}

enum { K_QKV = 0, K_H = 1 };

struct Ctx {
    uint32_t tph;
    uint32_t tid_;
    bool pf = false;
    __device__ __forceinline__ uint32_t tid() const { uint32_t r; asm volatile("mov.u32 %0, %1;" : "=r"(r) : "r"(tid_)); return r; }
};
__device__ __forceinline__ void release_slot(const Ctx& c, int slot) { if ((c.tid() & 31) == 0) mbar_arrive(bar(B_EMPTY + slot)); }

__device__ __forceinline__ void turn_wait(const Ctx& c) { asm volatile("bar.sync %0, 256;" :: "r"(4 + (c.tid() >> 7)) : "memory"); }
__device__ __forceinline__ void turn_pass(const Ctx& c) { asm volatile("bar.arrive %0, 256;" :: "r"(5 - (c.tid() >> 7)) : "memory"); }

template<int KIND, class PART, class POST>
__device__ __forceinline__ void run_step(Ctx& c, float* acc, const uint32_t* a, PART&& part, POST&& post, bool last = false) {
    constexpr int NST = (KIND == K_QKV) ? 6 : 3;
    constexpr int KPS = 36 / NST;
    sfor<0, NST>([&](auto ST) {
        constexpr int st = decltype(ST)::v;
        constexpr int slot = st % 3;
        mbar_wait(bar(B_FULL + slot), c.tph);
        uint32_t wgo = 0;
        if constexpr (st == NST - 1) wgo = (c.tid() >> 7) * 512;
        if (KIND == K_H && c.pf) prof(44 + st * 5);
        turn_wait(c);
        if (KIND == K_H && c.pf) prof(45 + st * 5);
        wg_fence();
        sfor<0, KPS>([&](auto KK) {
            constexpr int kk = decltype(KK)::v;
            constexpr int ks = st * KPS + kk;
            constexpr int SD = ks ? 1 : 0;
            if constexpr (KIND == K_QKV) {
                constexpr uint64_t bd = mkdesc(RING + slot * SLOT + kk * 2048, 12288, 1024, 1);
                if constexpr (ks < 32) wg_rs72<SD>(acc, a + ks * 4, bd);
                else wg_ss72<SD>(acc, mkdesc(XB + (ks - 32) * 32, 16, 1024, 1) + wgo, bd);
            } else {
                constexpr uint64_t bd = mkdesc(RING + slot * SLOT + kk * 2048, 16, 1024, 1);
                if constexpr (ks < 32) wg_rs64<SD>(acc, a + ks * 4, bd);
                else wg_ss64<SD>(acc, mkdesc(XB + (ks - 32) * 32, 16, 1024, 1) + wgo, bd);
            }
        });
        wg_commit();
        if (st < NST - 1 || !last || c.tid() < 128) turn_pass(c);
        if (KIND == K_H && c.pf) prof(46 + st * 5);
        part(ST);
        if (KIND == K_H && c.pf) prof(47 + st * 5);
        wg_wait<0>();
        if (KIND == K_H && c.pf) prof(48 + st * 5);
        release_slot(c, slot);
        if constexpr (slot == 2) c.tph ^= 1;
        post(ST);
    });
    if constexpr (KIND == K_QKV) reg_fence<36>(acc); else reg_fence<32>(acc);
}

__device__ __forceinline__ float phi(float t) {
    float e = ex2(t * 1.4426950408889634f);
    return (t > 0.f ? t + 1.0f : e) + 1e-6f;
}
__device__ __forceinline__ float gelu_h(float hx) {
    float u = hx * fmaf(hx * hx, 0.2854192650f, 1.5957691216f);
    return fmaf(hx, tanh_ap(u), hx);
}

struct Params {
    const __nv_bfloat16* x;
    const __nv_bfloat16* wqkv;
    const __nv_bfloat16* wo;
    const __nv_bfloat16* w1;
    const __nv_bfloat16* b1;
    const __nv_bfloat16* w2;
    const __nv_bfloat16* b2;
    __nv_bfloat16* out;
};

__global__ void __launch_bounds__(384, 1)
fused_kernel(const __grid_constant__ CUtensorMap tm_x, const __grid_constant__ CUtensorMap tm_w1,
             const __grid_constant__ CUtensorMap tm_w2, const __grid_constant__ CUtensorMap tm_wo,
             const __grid_constant__ CUtensorMap tm_o, const __grid_constant__ CUtensorMap tm_qkv,
             const __grid_constant__ CUtensorMap tm_qkve, const Params p) {
    extern __shared__ __align__(1024) unsigned char smem_raw[];
    const int tid = threadIdx.x;
    const int bid = blockIdx.x;
    const bool is_main = bid < NMAIN;
    const int j = bid & 7;
    const int m = bid >> 3;

    if (tid == 0) {
        if ((uint32_t)__cvta_generic_to_shared(smem_raw) != SB) __trap();
        for (int i = 0; i < 3; i++) {
            mbar_init(bar(B_FULL + i), 1); mbar_init(bar(B_EMPTY + i), 8);
            mbar_init(bar(B_XFULL + i), 1);
        }
        mbar_init(bar(B_KVB), is_main ? 2 : 8); mbar_init(bar(B_YRDY), 1);
        mbar_init(bar(B_OFULL), 1); mbar_init(bar(B_O8FULL), 1); mbar_init(bar(B_OFREE), 8); mbar_init(bar(B_O8FREE), 8);
        asm volatile("fence.mbarrier_init.release.cluster;" ::: "memory");
        if (is_main) {
            for (int g = 0; g < 3; g++) {
                mbar_expect_tx(bar(B_XFULL + g), 49152);
                for (int kb = 3 * g; kb < 3 * g + 3; kb++) tma_2d(HA + kb * 16384, &tm_x, bar(B_XFULL + g), kb * 64, m * 128);
            }
            for (int st = 0; st < 3; st++) {
                mbar_expect_tx(bar(B_FULL + st), 96 * 144);
                tma_2d(RING + st * SLOT, &tm_qkv, bar(B_FULL + st), 576 + j * 72, st * 96);
                tma_2d(RING + st * SLOT + 12288, &tm_qkve, bar(B_FULL + st), 576 + j * 72 + 64, st * 96);
            }
        }
    }
    if (tid == 32) sts32(EPO, g_epoch[bid]);
    if (tid >= 40 && tid < 48) sts32(EVC + (tid - 40) * 4, 0);
    if (tid >= 64 && tid < 64 + 288 && is_main) {
        int i = tid - 64;
        uint32_t v = *reinterpret_cast<const uint32_t*>(p.b1 + j * 576 + 2 * i);
        sts32(B1S + 8 * i, __float_as_uint(0.5f * bf_lo(v))); sts32(B1S + 8 * i + 4, __float_as_uint(0.5f * bf_hi(v)));
    }
    if (tid >= 352) {
        int i = tid - 352;
        uint32_t v = *reinterpret_cast<const uint32_t*>(p.b2 + (is_main ? j : 8) * 64 + 2 * i);
        sts32(B2S + 8 * i, v << 16); sts32(B2S + 8 * i + 4, v & 0xffff0000u);
    }
    fence_async_smem();
    __syncthreads();
    uint32_t epoch;
    asm volatile("ld.shared.u32 %0, [%1];" : "=r"(epoch) : "r"(EPO));
    const uint32_t par = epoch & 1;

    if (tid >= 256) {
        asm volatile("setmaxnreg.dec.sync.aligned.u32 24;");
        const int hw = (tid >> 5) - 8, lane = tid & 31;
        if (hw == 0) {
            if (lane == 0) {
                uint32_t n = 0;
                if (is_main) {
                    n = 1;
                    #pragma unroll 1
                    for (int u = 3; u < 18; u++) {
                        const int st = u % 3, step = u / 6;
                        const int col = ((step == 2) ? 0 : (step + 1) * 576) + j * 72, row = (u % 6) * 96;
                        mbar_wait(bar(B_EMPTY + st), (n & 1) ^ 1);
                        mbar_expect_tx(bar(B_FULL + st), 96 * 144);
                        tma_2d(RING + st * SLOT, &tm_qkv, bar(B_FULL + st), col, row);
                        tma_2d(RING + st * SLOT + 12288, &tm_qkve, bar(B_FULL + st), col + 64, row);
                        if (st == 2) n++;
                    }
                }
                const int nsteps = is_main ? 19 : 1;
                #pragma unroll 1
                for (int s = 0; s < nsteps; s++, n++) {
                    const CUtensorMap* tm; int col, row;
                    if (!is_main) { tm = &tm_wo; col = 512; row = 0; }
                    else if (s < 9) { tm = &tm_w1; col = j * 576 + s * 64; row = 0; }
                    else if (s < 18) { tm = &tm_w2; col = (s == 9) ? 512 : (((j + s - 9) & 7) * 64); row = j * 576; }
                    else { tm = &tm_wo; col = j * 64; row = 0; }
                    #pragma unroll 1
                    for (int st = 0; st < 3; st++) {
                        mbar_wait(bar(B_EMPTY + st), (n & 1) ^ 1);
                        mbar_expect_tx(bar(B_FULL + st), SLOT);
                        tma_2d(RING + st * SLOT, tm, bar(B_FULL + st), col, row + st * 192);
                    }
                }
            }
        } else {
            if (is_main) {
                const int t = tid - 288;
                #pragma unroll 1
                for (int i = t; i < 36 * 6; i += 96) {
                    int r = i / 6, q = i - r * 6;
                    prefetch_l2(reinterpret_cast<const char*>(p.wqkv) + (36 * m + r) * 3456 + (q >> 1) * 1152 + j * 144 + (q & 1) * 128);
                }
                __nanosleep(PF1_NS);
                #pragma unroll 1
                for (int i = t; i < 36 * 9; i += 96) {
                    int r = i / 9, q = i - r * 9;
                    prefetch_l2(reinterpret_cast<const char*>(p.w1) + (36 * m + r) * 9216 + j * 1152 + q * 128);
                    __nanosleep(PF3_NS);
                }
                __nanosleep(PF2_NS);
                #pragma unroll 1
                for (int i = t; i < 36 * 9; i += 96)
                    prefetch_l2(reinterpret_cast<const char*>(p.w2) + (576 * j + 36 * m) * 1152 + i * 128);
                if (t < 41 && (bid * 41 + t) < 5184) prefetch_l2(reinterpret_cast<const char*>(p.wo) + (bid * 41 + t) * 128);
                if (hw != 2) {
                    if (lane == 0) wait_cnt(cnt_kv(j), (epoch + 1) * 16);
                    __syncwarp();
                    const float4* kv = reinterpret_cast<const float4*>(g_kv + (par * 8 + j) * 1440);
                    #pragma unroll 2
                    for (int i = lane + (hw == 1 ? 0 : 32); i < 360; i += 64) {
                        const float4 v = __ldcg(kv + i);
                        const int d = i / 5, e = (i - d * 5) * 4, h = d / 18;
                        const uint32_t base = KVB + (d >> 3) * 128 + (d & 7) * 16;
                        const int n0 = 8 + h * 18 + e;
                        sts32(base + (n0 >> 3) * 1280 + (n0 & 7) * 2, pack_bf16(v.x, v.y));
                        if (e < 16) sts32(base + ((n0 + 2) >> 3) * 1280 + ((n0 + 2) & 7) * 2, pack_bf16(v.z, v.w));
                        else asm volatile("st.shared.u16 [%0], %1;" :: "r"(base + h * 2), "h"((unsigned short)pack_bf16(v.z, 0.f)) : "memory");
                    }
                    fence_async_smem();
                    __syncwarp();
                    if (lane == 0) mbar_arrive(bar(B_KVB));
                }
            }
            if (hw == 1) {
                if (lane == 0) {
                    const int nit = is_main ? 1 : 4;
                    for (int it = 0; it < nit; it++) {
                        const int mt = is_main ? m : ((bid - NMAIN) * 4 + it);
                        const bool wf = is_main || it > 0;
                        const uint32_t fp = is_main ? 0 : ((it - 1) & 1);
                        wait_cnt(cnt_o(mt), (epoch + 1) * 8);
                        fence_async_all();
                        if (wf) mbar_wait(bar(B_OFREE), fp);
                        mbar_expect_tx(bar(B_OFULL), 131072);
                        #pragma unroll 1
                        for (int kb = 0; kb < 8; kb++) tma_2d(HA + kb * 16384, &tm_o, bar(B_OFULL), kb * 64, mt * 128);
                        if (wf) mbar_wait(bar(B_O8FREE), fp);
                        mbar_expect_tx(bar(B_O8FULL), 16384);
                        tma_2d(XB, &tm_o, bar(B_O8FULL), 512, mt * 128);
                    }
                    if (is_main) { wait_cnt(cnt_y(m, j), (epoch + 1) * 7); mbar_arrive(bar(B_YRDY)); }
                }
            } else if (hw == 2) {
                if (!is_main) {
                    if (lane == 0) {
                        #pragma unroll 1
                        for (int it = 0; it < 4; it++) {
                            if (it > 0) mbar_wait(bar(B_KVB), (it - 1) & 1);
                            wait_cnt(cnt_y((bid - NMAIN) * 4 + it, 8), (epoch + 1) * 8);
                            mbar_arrive(bar(B_YRDY));
                        }
                    }
                } else {
                    #pragma unroll 1
                    for (int e = 0; e < 10; e++) {
                        int spin = 0;
                        while (true) {
                            uint32_t v;
                            asm volatile("ld.acquire.cta.shared.u32 %0, [%1];" : "=r"(v) : "r"(EVC + (lane & 7) * 4) : "memory");
                            if (__all_sync(0xffffffffu, v > (uint32_t)e)) break;
                            if (++spin > 20000000) __trap();
                            __nanosleep(20);
                        }
                        if (lane == 0) {
                            unsigned int* cp = (e == 0) ? cnt_kv(j) : (e == 1) ? cnt_o(m) : cnt_y(m, e == 2 ? 8 : ((j + e - 2) & 7));
                            if (e == 1) fence_async_all();
                            __threadfence();
                            asm volatile("red.relaxed.gpu.global.add.u32 [%0], 1;" :: "l"(cp) : "memory");
                        }
                        __syncwarp();
                    }
                }
            } else {
                {
                    const int t0 = is_main ? (m * 9 + j) : ((bid - NMAIN) * 4 * 9 + 8);
                    const int nt = is_main ? 1 : 4;
                    for (int t = 0; t < nt; t++) {
                        uint4* z = reinterpret_cast<uint4*>(g_yacc + (size_t)((par ^ 1) * 144 + t0 + t * 9) * YT_BYTES);
                        for (int i = lane; i < YT_BYTES / 16; i += 32) z[i] = make_uint4(0, 0, 0, 0);
                    }
                    if (is_main && m == 0) {
                        float* z = g_kv + ((par ^ 1) * 8 + j) * 1440;
                        for (int i = lane; i < 1440; i += 32) z[i] = 0.f;
                    }
                }
            }
        }
    } else {
        asm volatile("setmaxnreg.inc.sync.aligned.u32 240;");
        prof(0);
        Ctx c; c.tph = 0; c.tid_ = v_tid();
        float hc[32], pv[36];
        if (tid >> 7) turn_pass(c);
        auto event = [&](uint32_t ev) {
            __syncwarp();
            if (((c.tid() & 31) == 0)) asm volatile("st.release.cta.shared.u32 [%0], %1;" :: "r"(EVC + (c.tid() >> 3)), "r"(ev) : "memory");
        };
        auto warp_arrive = [&](uint32_t b) { __syncwarp(); if (((c.tid() & 31) == 0)) mbar_arrive(b); };

        uint32_t a[128];
        float rs0 = 0.f, rs1 = 0.f;
        auto lrow_off = [&]() { uint32_t t_ = c.tid(); return HA + ((t_ >> 5) * 16 + (t_ & 15)) * 128 + ((((t_ >> 4) & 1) ^ (t_ & 7)) << 4); };
        auto tail_off = [&]() { uint32_t t_ = c.tid(), g = (t_ >> 2) & 7; return XB + ((t_ >> 5) * 16 + g) * 128 + (g << 4) + (t_ & 3) * 4; };
        if (!is_main) {
            #pragma unroll
            for (int i = 0; i < 128; i++) a[i] = 0;
            #pragma unroll
            for (int i = 0; i < 32; i++) { hc[i] = 0.f; pv[i] = 0.f; }
        } else {
            uint32_t m00, m11;
            {
                uint32_t tl[16];
                const uint32_t lrow = lrow_off();
                float cs[2][4] = {{0.f, 0.f, 0.f, 0.f}, {0.f, 0.f, 0.f, 0.f}};
                sfor<0, 36>([&](auto KS) {
                    constexpr int ks = decltype(KS)::v;
                    if constexpr (ks % 12 == 0) mbar_wait(bar(B_XFULL + ks / 12), 0);
                    uint32_t* dst = (ks < 32) ? (a + (ks & 31) * 4) : (tl + (ks & 3) * 4);
                    ldsm4((lrow ^ ((ks % 4) << 5)) + (ks / 4) * 16384, dst);
                    mma_ones(cs[ks & 1], dst);
                });
                prof(2);
                float mean0 = (cs[0][0] + cs[1][0]) * (1.0f / 576.0f), mean1 = (cs[0][2] + cs[1][2]) * (1.0f / 576.0f);
                m00 = pack_bf16(mean0, mean0); m11 = pack_bf16(mean1, mean1);
                rs0 = mean0 - bf_lo(m00); rs1 = mean1 - bf_lo(m11);
                rs0 = -144.0f * rs0 * rs0; rs1 = -144.0f * rs1 * rs1;
                const uint32_t tb = tail_off();
                #pragma unroll
                for (int i = 0; i < 16; i++) {
                    const uint32_t w = sub_bf16x2(tl[i], (i & 1) ? m11 : m00);
                    sts32((tb ^ ((i >> 1) << 4)) + (i & 1) * 1024, w);
                    float lo = bf_lo(w), hi = bf_hi(w);
                    if (i & 1) rs1 = fmaf(lo, lo, fmaf(hi, hi, rs1)); else rs0 = fmaf(lo, lo, fmaf(hi, hi, rs0));
                }
                fence_async_smem();
                #pragma unroll
                for (int i = 0; i < 128; i++) a[i] = sub_bf16x2(a[i], (i & 1) ? m11 : m00);
                named_bar(2 + (tid >> 7), 128);
            }
            prof(3);
            auto cm_off = [&]() { uint32_t t_ = c.tid(); return (t_ >> 5) * 256 + (t_ & 31) * 4; };
            {
                float qc[36];
                #pragma unroll
                for (int i = 0; i < 36; i++) { qc[i] = 0.f; pv[i] = 0.f; }
                #pragma unroll 1
                for (int s = 0; s < 3; s++) {
                    run_step<K_QKV>(c, qc, a, [&](auto ST) {
                        constexpr int st = decltype(ST)::v;
                        if (s == 0) {
                            const uint32_t lrow = lrow_off();
                            sfor<(st * 32) / 6, ((st + 1) * 32) / 6>([&](auto I) {
                                constexpr int ks = decltype(I)::v;
                                uint32_t v[4];
                                ldsm4((lrow ^ ((ks % 4) << 5)) + (ks / 4) * 16384, v);
                                #pragma unroll
                                for (int r = 0; r < 4; r++) {
                                    uint32_t w = sub_bf16x2(v[r], (r & 1) ? m11 : m00);
                                    float lo = bf_lo(w), hi = bf_hi(w);
                                    if (r & 1) rs1 = fmaf(lo, lo, fmaf(hi, hi, rs1)); else rs0 = fmaf(lo, lo, fmaf(hi, hi, rs0));
                                }
                            });
                            if constexpr (st == 5) {
                                rs0 += __shfl_xor_sync(0xffffffffu, rs0, 1); rs1 += __shfl_xor_sync(0xffffffffu, rs1, 1);
                                rs0 += __shfl_xor_sync(0xffffffffu, rs0, 2); rs1 += __shfl_xor_sync(0xffffffffu, rs1, 2);
                                rs0 = rsqrtf(fmaxf(rs0 * (1.0f / 576.0f), 0.f) + 1e-5f);
                                rs1 = rsqrtf(fmaxf(rs1 * (1.0f / 576.0f), 0.f) + 1e-5f);
                                named_bar(1, 256);
                            }
                        } else {
                            const uint32_t cm = cm_off();
                            sfor<0, 9>([&](auto B) {
                                constexpr int b = decltype(B)::v;
                                if constexpr ((b * 6) / 9 == st) {
                                    const float v0 = pv[4 * b] * rs0, v1 = pv[4 * b + 1] * rs0, v2 = pv[4 * b + 2] * rs1, v3 = pv[4 * b + 3] * rs1;
                                    if (s == 1) {
                                        sts32(PKT + b * 2048 + cm, pack_bf16(phi(v0), phi(v1)));
                                        sts32(PKT + b * 2048 + cm + 128, pack_bf16(phi(v2), phi(v3)));
                                    } else {
                                        const uint32_t w0 = pack_bf16(v0, v1), w1 = pack_bf16(v2, v3);
                                        if constexpr (b <= 4) { sts32(VT + b * 2048 + cm, w0); sts32(VT + b * 2048 + cm + 128, w1); }
                                        if constexpr (b >= 4) { sts32(VT + (b + 2) * 2048 + cm, w0); sts32(VT + (b + 2) * 2048 + cm + 128, w1); }
                                        if constexpr (b == 0) {
                                            const uint32_t one = (cm & 12) ? 0u : 0x00003F80u;
                                            sts32(VT + 5 * 2048 + cm, one); sts32(VT + 5 * 2048 + cm + 128, one);
                                        }
                                        if constexpr (b == 8) {
                                            const uint32_t z = KVB + c.tid() * 16;
                                            sts128(z, 0, 0, 0, 0); sts128(z + 4096, 0, 0, 0, 0); sts128(z + 8192, 0, 0, 0, 0);
                                            if (z < KVB + 512) sts128(z + 12288, 0, 0, 0, 0);
                                            fence_async_smem();
                                        }
                                    }
                                }
                            });
                        }
                    }, [](auto) {});
                    reg_copy<36>(pv, qc);
                    prof(4 + s);
                }
            }
            {
                #pragma unroll
                for (int i = 0; i < 32; i++) hc[i] = 0.f;
                named_bar(1, 256);
                const uint32_t wgo = ((c.tid() >> 7) * 512);
                wg_fence();
                sfor<0, 8>([&](auto KS) {
                    constexpr int ks = decltype(KS)::v;
                    wg_tt64<(ks ? 1 : 0)>(hc, mkdesc(PKT + ks * 256, 128, 2048, 0) + wgo,
                                          mkdesc(VT + ks * 256, 128, 2048, 0) + wgo + (wgo >> 2));
                });
                wg_commit();
                const uint32_t pq = PQT + cm_off() + ((c.tid() >> 7) * 512) * 16;
                sfor<0, 9>([&](auto B) {
                    constexpr int b = decltype(B)::v;
                    sts32(pq + b * 1024, pack_bf16(phi(pv[4 * b] * rs0), phi(pv[4 * b + 1] * rs0)));
                    sts32(pq + b * 1024 + 128, pack_bf16(phi(pv[4 * b + 2] * rs1), phi(pv[4 * b + 3] * rs1)));
                });
                fence_async_smem();
                wg_wait<0>();
                reg_fence<32>(hc);
                reg_copy<24>(pv, hc);
            }
            prof(7);
            rs0 *= 0.5f; rs1 *= 0.5f;
        }
        {
            auto gelun = [&](auto B0, auto B1, uint32_t bofs, uint32_t* w) {
                constexpr int b0 = decltype(B0)::v, nb = decltype(B1)::v - b0;
                float2 bv[nb];
                #pragma unroll
                for (int i = 0; i < nb; i++) bv[i] = lds64f(bofs + (b0 + i) * 32);
                #pragma unroll
                for (int i = 0; i < nb; i++) {
                    const int b = b0 + i;
                    w[2 * i]     = pack_bf16(gelu_h(fmaf(pv[4 * b], rs0, bv[i].x)), gelu_h(fmaf(pv[4 * b + 1], rs0, bv[i].y)));
                    w[2 * i + 1] = pack_bf16(gelu_h(fmaf(pv[4 * b + 2], rs1, bv[i].x)), gelu_h(fmaf(pv[4 * b + 3], rs1, bv[i].y)));
                }
            };
            auto spill_off = [&]() { uint32_t t_ = c.tid(); return HA + (t_ >> 7) * 8192 + (t_ & 127) * 8; };
            auto reload = [&](auto S0, auto S1) {
                const uint32_t spill = spill_off();
                sfor<decltype(S0)::v * 8, decltype(S1)::v * 8>([&](auto Q) {
                    constexpr int q = decltype(Q)::v;
                    lds64(spill + (q / 8) * 16384 + (q % 8) * 1024, a + q * 2);
                });
            };
            #pragma unroll 1
            for (int it = is_main ? 0 : 19; it != 23; it = (it == 18) ? 23 : it + 1) {
                const int idx = min(it, 18);
                auto jpar = [&]() { return (uint32_t)(it > 18 ? ((it - 19) & 1) : 0); };
                auto ftile = [&]() {
                    const uint32_t b_ = v_bid();
                    return (int)(it == 18 ? ((b_ >> 3) * 9 + (b_ & 7)) : (((b_ - NMAIN) * 4 + it - 19) * 9 + 8));
                };
                uint32_t* const xr = a;
                uint32_t* const yv = a + 16;
                auto out_off = [&]() {
                    const int ft = ftile(), mt = ft / 9, ch = ft - mt * 9;
                    return (size_t)(mt * 128 + (c.tid() >> 5) * 16 + ((c.tid() >> 2) & 7)) * DM + ch * 64 + 2 * (c.tid() & 3);
                };
                if (idx == 18) {
                    mbar_wait(bar(B_OFULL), jpar());
                    const uint32_t lrow = lrow_off();
                    sfor<0, 32>([&](auto KS) {
                        constexpr int ks = decltype(KS)::v;
                        ldsm4((lrow ^ ((ks % 4) << 5)) + (ks / 4) * 16384, a + ks * 4);
                    });
                    warp_arrive(bar(B_OFREE));
                    if (it > 18) c.tph = 0;
                }
                run_step<K_H>(c, hc, a, [&](auto ST) {
                    constexpr int st = decltype(ST)::v;
                    if (idx == 18) {
                        if constexpr (st == 0) {
                            #pragma unroll
                            for (int b = 0; b < 8; b++) {
                                float2 bv = lds64f(B2S + b * 32 + (c.tid() & 3) * 8);
                                pv[4 * b] += bv.x; pv[4 * b + 1] += bv.y; pv[4 * b + 2] += bv.x; pv[4 * b + 3] += bv.y;
                            }
                        } else if constexpr (st == 1) {
                            prof(26);
                            mbar_wait(bar(B_YRDY), jpar());
                            prof(27);
                            const unsigned char* yp = g_yacc + ((v_epoch() & 1) * 144 + ftile()) * YT_BYTES + c.tid() * 16;
                            #pragma unroll
                            for (int q = 0; q < YT_BYTES / 4096; q++)
                                asm volatile("ld.global.cg.v4.u32 {%0,%1,%2,%3}, [%4];" : "=r"(yv[4 * q]), "=r"(yv[4 * q + 1]), "=r"(yv[4 * q + 2]), "=r"(yv[4 * q + 3]) : "l"(yp + q * 4096) : "memory");
                            const __nv_bfloat16* xp = p.x + out_off();
                            #pragma unroll
                            for (int i = 0; i < 8; i++) {
                                asm volatile("ld.global.nc.u32 %0, [%1];" : "=r"(xr[2 * i]) : "l"(xp + i * 8));
                                asm volatile("ld.global.nc.u32 %0, [%1];" : "=r"(xr[2 * i + 1]) : "l"(xp + 8 * DM + i * 8));
                            }
                            if (it > 18) warp_arrive(bar(B_KVB));
                            mbar_wait(bar(B_O8FULL), jpar());
                        } else {
                            prof(28);
                            #pragma unroll
                            for (int i = 0; i < 16; i++) { pv[2 * i] += bf_lo(yv[i]); pv[2 * i + 1] += bf_hi(yv[i]); }
                            #pragma unroll
                            for (int i = 0; i < 32; i++) pv[i] = pv[i] * rcp(1.0f + ex2(pv[i] * -1.4426950408889634f));
                            prof(29);
                        }
                    } else
                    if (idx >= 10) {
                        if constexpr (st < 2) {
                            const uint32_t b_ = v_bid();
                            const uint32_t chunk = (idx == 10) ? 8 : ((b_ + idx - 10) & 7);
                            unsigned char* yp = g_yacc + ((v_epoch() & 1) * 144 + (b_ >> 3) * 9 + chunk) * YT_BYTES + c.tid() * 16;
                            sfor<2 * st, 2 * st + 2>([&](auto Q) {
                                constexpr int q = decltype(Q)::v;
                                asm volatile("red.global.add.noftz.v4.bf16x2 [%0], {%1,%2,%3,%4};" :: "l"(yp + q * 4096),
                                             "r"(pack_bf16(pv[8 * q], pv[8 * q + 1])), "r"(pack_bf16(pv[8 * q + 2], pv[8 * q + 3])),
                                             "r"(pack_bf16(pv[8 * q + 4], pv[8 * q + 5])), "r"(pack_bf16(pv[8 * q + 6], pv[8 * q + 7])) : "memory");
                            });
                            if constexpr (st == 1) event(idx - 7);
                        }
                    } else if (idx >= 1) {
                        const uint32_t bofs = B1S + (idx - 1) * 256 + (c.tid() & 3) * 8;
                        if (idx < 9) {
                            if constexpr (st == 0) { if (idx == OSTEP_AT + 1) event(2); }
                            const uint32_t spill = spill_off() + (idx - 1) * 16384;
                            constexpr int b0 = st * 3, b1 = (st == 2 ? 8 : st * 3 + 3);
                            uint32_t w[6];
                            gelun(IC<b0>{}, IC<b1>{}, bofs, w);
                            #pragma unroll
                            for (int b = b0; b < b1; b++) sts64(spill + b * 1024, w[2 * (b - b0)], w[2 * (b - b0) + 1]);
                        } else {
                            if constexpr (st < 2) {
                                const uint32_t tb = tail_off();
                                uint32_t w[8];
                                gelun(IC<st * 4>{}, IC<st * 4 + 4>{}, bofs, w);
                                #pragma unroll
                                for (int i = 0; i < 4; i++) { sts32(tb ^ ((st * 4 + i) << 4), w[2 * i]); sts32((tb ^ ((st * 4 + i) << 4)) + 1024, w[2 * i + 1]); }
                            }
                            if constexpr (st == 1) { fence_async_smem(); named_bar(2 + (c.tid() >> 7), 128); }
                        }
                    } else {
                        if constexpr (st < 2) {
                            constexpr int hf = st;
                            const int t_ = c.tid(), wg = t_ >> 7, t = t_ & 3;
                            float* dst = g_kv + ((v_epoch() & 1) * 8 + (v_bid() & 7)) * 1440;
                            const int d = wg * 32 + ((t_ >> 5) & 3) * 16 + ((t_ >> 2) & 7) + hf * 8;
                            const bool dv = wg ? (d >= 36 && d < 72) : (d < 36);
                            const int e00 = wg * 24 + 2 * t - (d / 18) * 18;
                            float* dp = dst + d * 20 + e00;
                            #pragma unroll
                            for (int i = 0; i < 6; i++) {
                                const int e = e00 + i * 8;
                                const bool blk = wg ? (i >= 1) : (i <= 4);
                                if (dv && blk && e >= 0 && e < 18)
                                    asm volatile("red.global.add.v2.f32 [%0], {%1,%2};" :: "l"(dp + i * 8), "f"(pv[4 * i + 2 * hf]), "f"(pv[4 * i + 2 * hf + 1]) : "memory");
                            }
                            if (dv && t == 0) atomicAdd(dst + d * 20 + 18, wg ? pv[2 * hf] : pv[20 + 2 * hf]);
                            if constexpr (st == 1) event(1);
                        }
                    }
                }, [&](auto ST) {
                    constexpr int st = decltype(ST)::v;
                    if (idx == 8) {
                        reload(IC<3 * st>{}, IC<(st == 2 ? 8 : 3 * st + 3)>{});
                        if constexpr (st == 2) warp_arrive(bar(B_OFREE));
                    }
                }, it == 18 || it == 22);
                if (idx >= 17) warp_arrive(bar(B_O8FREE));
                if (idx == 18) {
                    prof(30);
                    __nv_bfloat16* op = p.out + out_off();
                    #pragma unroll
                    for (int b = 0; b < 8; b++) {
                        *reinterpret_cast<uint32_t*>(op + b * 8) =
                            pack_bf16(fmaf(hc[4 * b], pv[4 * b], bf_lo(xr[2 * b])), fmaf(hc[4 * b + 1], pv[4 * b + 1], bf_hi(xr[2 * b])));
                        *reinterpret_cast<uint32_t*>(op + 8 * DM + b * 8) =
                            pack_bf16(fmaf(hc[4 * b + 2], pv[4 * b + 2], bf_lo(xr[2 * b + 1])), fmaf(hc[4 * b + 3], pv[4 * b + 3], bf_hi(xr[2 * b + 1])));
                    }
                    #pragma unroll
                    for (int i = 0; i < 32; i++) pv[i] = 0.f;
                    if (it > 18) prof(it - 11);
                } else {
                    reg_copy<32>(pv, hc);
                    prof(8 + idx);
                }
                if (idx == OSTEP_AT) {
                    mbar_wait(bar(B_KVB), 0);
                    prof(34);
                    const uint32_t pqo = (c.tid() >> 7) * 576;
                    const int t_ = c.tid(), b_ = v_bid(), t = t_ & 3, l4 = t_ & 28;
                    __nv_bfloat16* op = g_o + (size_t)((b_ >> 3) * 128 + (t_ >> 5) * 16 + ((t_ >> 2) & 7)) * DM + (b_ & 7) * 72 + 2 * t;
                    float r3[2];
                    sfor<0, 2>([&](auto PS) {
                        constexpr int ps = decltype(PS)::v;
                        wg_fence();
                        sfor<0, 5>([&](auto KS) {
                            constexpr int ks = decltype(KS)::v;
                            wg_ss64<(ks ? 1 : 0)>(hc, mkdesc(PQT + ks * 2048, ks == 4 ? 0 : 1024, 128, 0) + pqo, mkdesc(KVB + ps * 8 * 1280 + ks * 256, 128, 1280, 0));
                        });
                        wg_commit();
                        wg_wait<0>();
                        reg_fence<32>(hc);
                        #pragma unroll
                        for (int hf = 0; hf < 2; hf++) {
                            if constexpr (ps == 0) {
                                float r[4];
                                r[0] = rcp(__shfl_sync(0xffffffffu, hc[2 * hf], l4) + 1e-6f);
                                r[1] = rcp(__shfl_sync(0xffffffffu, hc[1 + 2 * hf], l4) + 1e-6f);
                                r[2] = rcp(__shfl_sync(0xffffffffu, hc[2 * hf], l4 + 1) + 1e-6f);
                                r[3] = rcp(__shfl_sync(0xffffffffu, hc[1 + 2 * hf], l4 + 1) + 1e-6f);
                                r3[hf] = r[3];
                                #pragma unroll
                                for (int i = 0; i < 7; i++) {
                                    float rr = (i < 2) ? r[0] : (i == 2) ? (t < 1 ? r[0] : r[1]) : (i == 3) ? r[1] : (i == 4) ? (t < 2 ? r[1] : r[2])
                                             : (i == 5) ? r[2] : (t < 3 ? r[2] : r[3]);
                                    *reinterpret_cast<uint32_t*>(op + hf * 8 * DM + i * 8) = pack_bf16(hc[4 * i + 4 + 2 * hf] * rr, hc[4 * i + 5 + 2 * hf] * rr);
                                }
                            } else {
                                #pragma unroll
                                for (int i = 0; i < 2; i++)
                                    *reinterpret_cast<uint32_t*>(op + hf * 8 * DM + 56 + i * 8) = pack_bf16(hc[4 * i + 2 * hf] * r3[hf], hc[4 * i + 1 + 2 * hf] * r3[hf]);
                            }
                        }
                    });
                }
            }
        }
        prof(40);
        if (c.tid() == 0) g_epoch[v_bid()] = v_epoch() + 1;
    }
}

typedef CUresult (*EncodeFn)(CUtensorMap*, CUtensorMapDataType, cuuint32_t, void*, const cuuint64_t*, const cuuint64_t*,
                             const cuuint32_t*, const cuuint32_t*, CUtensorMapInterleave, CUtensorMapSwizzle,
                             CUtensorMapL2promotion, CUtensorMapFloatOOBfill);

void make_map(EncodeFn enc, CUtensorMap* tm, const void* base, int rows, int cols, int box_rows, int box_cols = 64) {
    cuuint64_t gdim[2] = {(cuuint64_t)cols, (cuuint64_t)rows};
    cuuint64_t gstr[1] = {(cuuint64_t)cols * 2};
    cuuint32_t box[2] = {(cuuint32_t)box_cols, (cuuint32_t)box_rows};
    cuuint32_t estr[2] = {1, 1};
    enc(tm, CU_TENSOR_MAP_DATA_TYPE_BFLOAT16, 2, const_cast<void*>(base), gdim, gstr, box, estr, CU_TENSOR_MAP_INTERLEAVE_NONE,
        CU_TENSOR_MAP_SWIZZLE_128B, CU_TENSOR_MAP_L2_PROMOTION_L2_128B, CU_TENSOR_MAP_FLOAT_OOB_FILL_NONE);
}

}

extern "C" void kernel_launch(void* const* d_in, const int* in_sizes, int n_in, void* d_out, int out_size) {
    static EncodeFn enc = nullptr;
    static void* o_ptr = nullptr;
    if (!enc) {
        void* fn = nullptr;
        cudaDriverEntryPointQueryResult qr;
        cudaGetDriverEntryPoint("cuTensorMapEncodeTiled", &fn, cudaEnableDefault, &qr);
        enc = (EncodeFn)fn;
        cudaGetSymbolAddress(&o_ptr, g_o);
        cudaFuncSetAttribute(fused_kernel, cudaFuncAttributeMaxDynamicSharedMemorySize, SMEM_BYTES);
    }
    Params p;
    p.x = (const __nv_bfloat16*)d_in[0];
    p.wqkv = (const __nv_bfloat16*)d_in[1];
    p.wo = (const __nv_bfloat16*)d_in[2];
    p.w1 = (const __nv_bfloat16*)d_in[4];
    p.b1 = (const __nv_bfloat16*)d_in[5];
    p.w2 = (const __nv_bfloat16*)d_in[6];
    p.b2 = (const __nv_bfloat16*)d_in[7];
    p.out = (__nv_bfloat16*)d_out;
    CUtensorMap tm_x, tm_w1, tm_w2, tm_wo, tm_o, tm_qkv, tm_qkve;
    make_map(enc, &tm_qkv, p.wqkv, DM, 3 * DM, 96);
    make_map(enc, &tm_qkve, p.wqkv, DM, 3 * DM, 96, 8);
    make_map(enc, &tm_x, p.x, SEQ, DM, 128);
    make_map(enc, &tm_w1, p.w1, DM, FF, 192);
    make_map(enc, &tm_w2, p.w2, FF, DM, 192);
    make_map(enc, &tm_wo, p.wo, DM, DM, 192);
    make_map(enc, &tm_o, o_ptr, SEQ, DM, 128);
    fused_kernel<<<NMAIN + NAUX, 384, SMEM_BYTES>>>(tm_x, tm_w1, tm_w2, tm_wo, tm_o, tm_qkv, tm_qkve, p);
}
```

```cpp
#include <cuda_runtime.h>
#include <cuda.h>
#include <cuda_bf16.h>
#include <stdint.h>

#define OSTEP_AT 4
#define KNOB_A 1
#define KNOB_B 0
#define PF1_NS 1000
#define PF2_NS 2000
#define PFIDX 3
#define PF3_NS 800
#define YF32 0

namespace {
constexpr int WAIT_ITERS = 3000000;

constexpr int SEQ = 2048, DM = 576, FF = 4608;
constexpr int NMAIN = 128, NAUX = 4;

constexpr uint32_t SB    = 0x400;
constexpr uint32_t HA    = SB;
constexpr uint32_t XB    = SB + 131072;
constexpr uint32_t RING  = SB + 147456;
constexpr uint32_t SLOT  = 24576;
constexpr uint32_t MISC  = SB + 221184;
constexpr uint32_t BARS  = MISC;
constexpr uint32_t B1S   = MISC + 512;
constexpr uint32_t B2S   = MISC + 2816;
constexpr uint32_t EPO   = MISC + 3072;
constexpr uint32_t EVC   = MISC + 3104;
constexpr uint32_t SMEM_BYTES = 221184 + 3200 + 512;
constexpr uint32_t PKT   = HA + 32768;
constexpr uint32_t VT    = HA + 51200;
constexpr uint32_t PQT   = HA + 98304;
constexpr uint32_t KVB   = HA + 116736;

enum { B_FULL = 0, B_EMPTY = 3, B_XFULL = 6, B_OFULL = 9, B_O8FULL = 10, B_OFREE = 11, B_O8FREE = 12, B_KVB = 13, B_YRDY = 14, B_COUNT = 15 };
__device__ __forceinline__ constexpr uint32_t bar(int i) { return BARS + 8u * i; }

constexpr int YT_BYTES = YF32 ? 32768 : 16384;
__device__ __align__(1024) __nv_bfloat16 g_o[SEQ * DM];
__device__ __align__(1024) unsigned char g_yacc[2 * 16 * 9 * YT_BYTES];
__device__ __align__(128) float g_kv[2 * 8 * 72 * 20];
__device__ __align__(128) unsigned int g_cnt[(8 + 16 + 16 * 9) * 8];
__device__ unsigned int g_epoch[NMAIN + NAUX];
__device__ __forceinline__ unsigned int* cnt_kv(int j) { return g_cnt + j * 8; }
__device__ __forceinline__ unsigned int* cnt_o(int m) { return g_cnt + (8 + m) * 8; }
__device__ __forceinline__ unsigned int* cnt_y(int m, int c) { return g_cnt + (24 + m * 9 + c) * 8; }

__device__ __forceinline__ void mbar_init(uint32_t b, uint32_t cnt) { asm volatile("mbarrier.init.shared::cta.b64 [%0], %1;" :: "r"(b), "r"(cnt)); }
__device__ __forceinline__ void mbar_expect_tx(uint32_t b, uint32_t bytes) { asm volatile("mbarrier.arrive.expect_tx.shared::cta.b64 _, [%0], %1;" :: "r"(b), "r"(bytes) : "memory"); }
__device__ __forceinline__ void mbar_arrive(uint32_t b) { asm volatile("mbarrier.arrive.shared::cta.b64 _, [%0];" :: "r"(b) : "memory"); }
__device__ __forceinline__ void prof(int) {}
__device__ __forceinline__ void mbar_wait(uint32_t b, uint32_t parity) {
    asm volatile("{\n.reg .pred p;\n.reg .u32 c;\nmov.u32 c, 0;\n"
                 "WAIT_LOOP:\nmbarrier.try_wait.parity.shared::cta.b64 p, [%0], %1;\n@p bra WAIT_DONE;\n"
                 "add.u32 c, c, 1;\nsetp.lt.u32 p, c, 4000000;\n@p bra WAIT_LOOP;\ntrap;\nWAIT_DONE:\n}"
                 :: "r"(b), "r"(parity) : "memory");
}
__device__ __forceinline__ void tma_2d(uint32_t dst, const CUtensorMap* tm, uint32_t b, int c0, int c1) {
    asm volatile("cp.async.bulk.tensor.2d.shared::cluster.global.mbarrier::complete_tx::bytes [%0], [%1, {%3, %4}], [%2];"
                 :: "r"(dst), "l"(tm), "r"(b), "r"(c0), "r"(c1) : "memory");
}
__device__ __forceinline__ void fence_async_smem() { asm volatile("fence.proxy.async.shared::cta;" ::: "memory"); }
__device__ __forceinline__ void fence_async_all() { asm volatile("fence.proxy.async;" ::: "memory"); }
__device__ __forceinline__ void named_bar(int id, int n) { asm volatile("bar.sync %0, %1;" :: "r"(id), "r"(n) : "memory"); }
__device__ __forceinline__ void wg_fence() { asm volatile("wgmma.fence.sync.aligned;" ::: "memory"); }
__device__ __forceinline__ void wg_commit() { asm volatile("wgmma.commit_group.sync.aligned;" ::: "memory"); }
template<int N> __device__ __forceinline__ void wg_wait() { asm volatile("wgmma.wait_group.sync.aligned %0;" :: "n"(N) : "memory"); }
template<int N> __device__ __forceinline__ void reg_fence(float* d) {
    #pragma unroll
    for (int i = 0; i < N; i++) asm volatile("" : "+f"(d[i]) :: "memory");
}
template<int N> __device__ __forceinline__ void reg_copy(float* d, const float* s) {
    #pragma unroll
    for (int i = 0; i < N; i++) asm volatile("mov.b32 %0, %1;" : "=f"(d[i]) : "f"(s[i]));
}
__device__ __forceinline__ uint32_t pack_bf16(float lo, float hi) { uint32_t r; asm("cvt.rn.bf16x2.f32 %0, %1, %2;" : "=r"(r) : "f"(hi), "f"(lo)); return r; }
__device__ __forceinline__ float bf_lo(uint32_t v) { return __uint_as_float(v << 16); }
__device__ __forceinline__ float bf_hi(uint32_t v) { return __uint_as_float(v & 0xffff0000u); }
__device__ __forceinline__ uint32_t sub_bf16x2(uint32_t a, uint32_t b) { uint32_t r; asm("sub.rn.bf16x2 %0, %1, %2;" : "=r"(r) : "r"(a), "r"(b)); return r; }
__device__ __forceinline__ float ex2(float x) { float r; asm("ex2.approx.ftz.f32 %0, %1;" : "=f"(r) : "f"(x)); return r; }
__device__ __forceinline__ float rcp(float x) { float r; asm("rcp.approx.ftz.f32 %0, %1;" : "=f"(r) : "f"(x)); return r; }
__device__ __forceinline__ float tanh_ap(float x) { float r; asm("tanh.approx.f32 %0, %1;" : "=f"(r) : "f"(x)); return r; }
__device__ __forceinline__ void sts32(uint32_t a, uint32_t v) { asm volatile("st.shared.b32 [%0], %1;" :: "r"(a), "r"(v)); }
__device__ __forceinline__ void sts128(uint32_t a, uint32_t x, uint32_t y, uint32_t z, uint32_t w) { asm volatile("st.shared.v4.b32 [%0], {%1,%2,%3,%4};" :: "r"(a), "r"(x), "r"(y), "r"(z), "r"(w)); }
__device__ __forceinline__ void sts64(uint32_t a, uint32_t x, uint32_t y) { asm volatile("st.shared.v2.b32 [%0], {%1,%2};" :: "r"(a), "r"(x), "r"(y)); }
__device__ __forceinline__ void lds64(uint32_t a, uint32_t* v) { asm volatile("ld.shared.v2.b32 {%0,%1}, [%2];" : "=r"(v[0]), "=r"(v[1]) : "r"(a)); }
__device__ __forceinline__ void lds128(uint32_t a, uint32_t* v) { asm volatile("ld.shared.v4.b32 {%0,%1,%2,%3}, [%4];" : "=r"(v[0]), "=r"(v[1]), "=r"(v[2]), "=r"(v[3]) : "r"(a) : "memory"); }
__device__ __forceinline__ float2 lds64f(uint32_t a) { float2 v; asm("ld.shared.v2.f32 {%0,%1}, [%2];" : "=f"(v.x), "=f"(v.y) : "r"(a)); return v; }
__device__ __forceinline__ void ldsm4(uint32_t a, uint32_t* v) {
    asm volatile("ldmatrix.sync.aligned.m8n8.x4.shared.b16 {%0,%1,%2,%3}, [%4];" : "=r"(v[0]), "=r"(v[1]), "=r"(v[2]), "=r"(v[3]) : "r"(a));
}
__device__ __forceinline__ void mma_ones(float* c, const uint32_t* a) {
    const uint32_t one2 = 0x3F803F80u;
    asm volatile("mma.sync.aligned.m16n8k16.row.col.f32.bf16.bf16.f32 {%0,%1,%2,%3}, {%4,%5,%6,%7}, {%8,%8}, {%0,%1,%2,%3};"
                 : "+f"(c[0]), "+f"(c[1]), "+f"(c[2]), "+f"(c[3]) : "r"(a[0]), "r"(a[1]), "r"(a[2]), "r"(a[3]), "r"(one2));
}
__device__ __forceinline__ unsigned int ld_acquire(const unsigned int* p) { unsigned int v; asm volatile("ld.acquire.gpu.global.u32 %0, [%1];" : "=r"(v) : "l"(p) : "memory"); return v; }
__device__ __forceinline__ void wait_cnt(const unsigned int* p, unsigned int target) {
    for (int i = 0; i < WAIT_ITERS; i++) {
        if ((int)(ld_acquire(p) - target) >= 0) return;
        __nanosleep(40);
    }
    __trap();
}
__device__ __forceinline__ uint32_t v_tid() { uint32_t r; asm volatile("mov.u32 %0, %%tid.x;" : "=r"(r)); return r; }
__device__ __forceinline__ uint32_t v_bid() { uint32_t r; asm volatile("mov.u32 %0, %%ctaid.x;" : "=r"(r)); return r; }
__device__ __forceinline__ uint32_t v_epoch() { uint32_t r; asm volatile("ld.shared.u32 %0, [%1];" : "=r"(r) : "r"(EPO)); return r; }
__device__ __forceinline__ void prefetch_l2(const void* p) { asm volatile("prefetch.global.L2 [%0];" :: "l"(p)); }

__host__ __device__ constexpr uint64_t mkdesc(uint32_t addr, uint32_t lbo, uint32_t sbo, uint32_t swz) {
    return (uint64_t)((addr & 0x3FFFF) >> 4) | ((uint64_t)((lbo >> 4) & 0x3FFF) << 16) | ((uint64_t)((sbo >> 4) & 0x3FFF) << 32) | ((uint64_t)swz << 62);
}

template<int SD> __device__ __forceinline__ void wg_rs64(float* d, const uint32_t* a, uint64_t bd) {
  if constexpr (SD) {
    asm volatile("{\n.reg .pred p;\nsetp.eq.b32 p, 0, 0;\n"
    "wgmma.mma_async.sync.aligned.m64n64k16.f32.bf16.bf16 {%0,%1,%2,%3,%4,%5,%6,%7,%8,%9,%10,%11,%12,%13,%14,%15,%16,%17,%18,%19,%20,%21,%22,%23,%24,%25,%26,%27,%28,%29,%30,%31}, {%32,%33,%34,%35}, %36, p, 1, 1, 1;\n}"
    : "+f"(d[0]),"+f"(d[1]),"+f"(d[2]),"+f"(d[3]),"+f"(d[4]),"+f"(d[5]),"+f"(d[6]),"+f"(d[7]),"+f"(d[8]),"+f"(d[9]),"+f"(d[10]),"+f"(d[11]),"+f"(d[12]),"+f"(d[13]),"+f"(d[14]),"+f"(d[15]),"+f"(d[16]),"+f"(d[17]),"+f"(d[18]),"+f"(d[19]),"+f"(d[20]),"+f"(d[21]),"+f"(d[22]),"+f"(d[23]),"+f"(d[24]),"+f"(d[25]),"+f"(d[26]),"+f"(d[27]),"+f"(d[28]),"+f"(d[29]),"+f"(d[30]),"+f"(d[31])
    : "r"(a[0]),"r"(a[1]),"r"(a[2]),"r"(a[3]), "l"(bd));
  } else {
    asm volatile("{\n.reg .pred p;\nsetp.ne.b32 p, 0, 0;\n"
    "wgmma.mma_async.sync.aligned.m64n64k16.f32.bf16.bf16 {%0,%1,%2,%3,%4,%5,%6,%7,%8,%9,%10,%11,%12,%13,%14,%15,%16,%17,%18,%19,%20,%21,%22,%23,%24,%25,%26,%27,%28,%29,%30,%31}, {%32,%33,%34,%35}, %36, p, 1, 1, 1;\n}"
    : "+f"(d[0]),"+f"(d[1]),"+f"(d[2]),"+f"(d[3]),"+f"(d[4]),"+f"(d[5]),"+f"(d[6]),"+f"(d[7]),"+f"(d[8]),"+f"(d[9]),"+f"(d[10]),"+f"(d[11]),"+f"(d[12]),"+f"(d[13]),"+f"(d[14]),"+f"(d[15]),"+f"(d[16]),"+f"(d[17]),"+f"(d[18]),"+f"(d[19]),"+f"(d[20]),"+f"(d[21]),"+f"(d[22]),"+f"(d[23]),"+f"(d[24]),"+f"(d[25]),"+f"(d[26]),"+f"(d[27]),"+f"(d[28]),"+f"(d[29]),"+f"(d[30]),"+f"(d[31])
    : "r"(a[0]),"r"(a[1]),"r"(a[2]),"r"(a[3]), "l"(bd));
  }
}
template<int SD> __device__ __forceinline__ void wg_ss64(float* d, uint64_t ad, uint64_t bd) {
  if constexpr (SD) {
    asm volatile("{\n.reg .pred p;\nsetp.eq.b32 p, 0, 0;\n"
    "wgmma.mma_async.sync.aligned.m64n64k16.f32.bf16.bf16 {%0,%1,%2,%3,%4,%5,%6,%7,%8,%9,%10,%11,%12,%13,%14,%15,%16,%17,%18,%19,%20,%21,%22,%23,%24,%25,%26,%27,%28,%29,%30,%31}, %32, %33, p, 1, 1, 0, 1;\n}"
    : "+f"(d[0]),"+f"(d[1]),"+f"(d[2]),"+f"(d[3]),"+f"(d[4]),"+f"(d[5]),"+f"(d[6]),"+f"(d[7]),"+f"(d[8]),"+f"(d[9]),"+f"(d[10]),"+f"(d[11]),"+f"(d[12]),"+f"(d[13]),"+f"(d[14]),"+f"(d[15]),"+f"(d[16]),"+f"(d[17]),"+f"(d[18]),"+f"(d[19]),"+f"(d[20]),"+f"(d[21]),"+f"(d[22]),"+f"(d[23]),"+f"(d[24]),"+f"(d[25]),"+f"(d[26]),"+f"(d[27]),"+f"(d[28]),"+f"(d[29]),"+f"(d[30]),"+f"(d[31])
    : "l"(ad), "l"(bd));
  } else {
    asm volatile("{\n.reg .pred p;\nsetp.ne.b32 p, 0, 0;\n"
    "wgmma.mma_async.sync.aligned.m64n64k16.f32.bf16.bf16 {%0,%1,%2,%3,%4,%5,%6,%7,%8,%9,%10,%11,%12,%13,%14,%15,%16,%17,%18,%19,%20,%21,%22,%23,%24,%25,%26,%27,%28,%29,%30,%31}, %32, %33, p, 1, 1, 0, 1;\n}"
    : "+f"(d[0]),"+f"(d[1]),"+f"(d[2]),"+f"(d[3]),"+f"(d[4]),"+f"(d[5]),"+f"(d[6]),"+f"(d[7]),"+f"(d[8]),"+f"(d[9]),"+f"(d[10]),"+f"(d[11]),"+f"(d[12]),"+f"(d[13]),"+f"(d[14]),"+f"(d[15]),"+f"(d[16]),"+f"(d[17]),"+f"(d[18]),"+f"(d[19]),"+f"(d[20]),"+f"(d[21]),"+f"(d[22]),"+f"(d[23]),"+f"(d[24]),"+f"(d[25]),"+f"(d[26]),"+f"(d[27]),"+f"(d[28]),"+f"(d[29]),"+f"(d[30]),"+f"(d[31])
    : "l"(ad), "l"(bd));
  }
}
template<int SD> __device__ __forceinline__ void wg_rs72(float* d, const uint32_t* a, uint64_t bd) {
  if constexpr (SD) {
    asm volatile("{\n.reg .pred p;\nsetp.eq.b32 p, 0, 0;\n"
    "wgmma.mma_async.sync.aligned.m64n72k16.f32.bf16.bf16 {%0,%1,%2,%3,%4,%5,%6,%7,%8,%9,%10,%11,%12,%13,%14,%15,%16,%17,%18,%19,%20,%21,%22,%23,%24,%25,%26,%27,%28,%29,%30,%31,%32,%33,%34,%35}, {%36,%37,%38,%39}, %40, p, 1, 1, 1;\n}"
    : "+f"(d[0]),"+f"(d[1]),"+f"(d[2]),"+f"(d[3]),"+f"(d[4]),"+f"(d[5]),"+f"(d[6]),"+f"(d[7]),"+f"(d[8]),"+f"(d[9]),"+f"(d[10]),"+f"(d[11]),"+f"(d[12]),"+f"(d[13]),"+f"(d[14]),"+f"(d[15]),"+f"(d[16]),"+f"(d[17]),"+f"(d[18]),"+f"(d[19]),"+f"(d[20]),"+f"(d[21]),"+f"(d[22]),"+f"(d[23]),"+f"(d[24]),"+f"(d[25]),"+f"(d[26]),"+f"(d[27]),"+f"(d[28]),"+f"(d[29]),"+f"(d[30]),"+f"(d[31]),"+f"(d[32]),"+f"(d[33]),"+f"(d[34]),"+f"(d[35])
    : "r"(a[0]),"r"(a[1]),"r"(a[2]),"r"(a[3]), "l"(bd));
  } else {
    asm volatile("{\n.reg .pred p;\nsetp.ne.b32 p, 0, 0;\n"
    "wgmma.mma_async.sync.aligned.m64n72k16.f32.bf16.bf16 {%0,%1,%2,%3,%4,%5,%6,%7,%8,%9,%10,%11,%12,%13,%14,%15,%16,%17,%18,%19,%20,%21,%22,%23,%24,%25,%26,%27,%28,%29,%30,%31,%32,%33,%34,%35}, {%36,%37,%38,%39}, %40, p, 1, 1, 1;\n}"
    : "+f"(d[0]),"+f"(d[1]),"+f"(d[2]),"+f"(d[3]),"+f"(d[4]),"+f"(d[5]),"+f"(d[6]),"+f"(d[7]),"+f"(d[8]),"+f"(d[9]),"+f"(d[10]),"+f"(d[11]),"+f"(d[12]),"+f"(d[13]),"+f"(d[14]),"+f"(d[15]),"+f"(d[16]),"+f"(d[17]),"+f"(d[18]),"+f"(d[19]),"+f"(d[20]),"+f"(d[21]),"+f"(d[22]),"+f"(d[23]),"+f"(d[24]),"+f"(d[25]),"+f"(d[26]),"+f"(d[27]),"+f"(d[28]),"+f"(d[29]),"+f"(d[30]),"+f"(d[31]),"+f"(d[32]),"+f"(d[33]),"+f"(d[34]),"+f"(d[35])
    : "r"(a[0]),"r"(a[1]),"r"(a[2]),"r"(a[3]), "l"(bd));
  }
}
template<int SD> __device__ __forceinline__ void wg_ss72(float* d, uint64_t ad, uint64_t bd) {
  if constexpr (SD) {
    asm volatile("{\n.reg .pred p;\nsetp.eq.b32 p, 0, 0;\n"
    "wgmma.mma_async.sync.aligned.m64n72k16.f32.bf16.bf16 {%0,%1,%2,%3,%4,%5,%6,%7,%8,%9,%10,%11,%12,%13,%14,%15,%16,%17,%18,%19,%20,%21,%22,%23,%24,%25,%26,%27,%28,%29,%30,%31,%32,%33,%34,%35}, %36, %37, p, 1, 1, 0, 1;\n}"
    : "+f"(d[0]),"+f"(d[1]),"+f"(d[2]),"+f"(d[3]),"+f"(d[4]),"+f"(d[5]),"+f"(d[6]),"+f"(d[7]),"+f"(d[8]),"+f"(d[9]),"+f"(d[10]),"+f"(d[11]),"+f"(d[12]),"+f"(d[13]),"+f"(d[14]),"+f"(d[15]),"+f"(d[16]),"+f"(d[17]),"+f"(d[18]),"+f"(d[19]),"+f"(d[20]),"+f"(d[21]),"+f"(d[22]),"+f"(d[23]),"+f"(d[24]),"+f"(d[25]),"+f"(d[26]),"+f"(d[27]),"+f"(d[28]),"+f"(d[29]),"+f"(d[30]),"+f"(d[31]),"+f"(d[32]),"+f"(d[33]),"+f"(d[34]),"+f"(d[35])
    : "l"(ad), "l"(bd));
  } else {
    asm volatile("{\n.reg .pred p;\nsetp.ne.b32 p, 0, 0;\n"
    "wgmma.mma_async.sync.aligned.m64n72k16.f32.bf16.bf16 {%0,%1,%2,%3,%4,%5,%6,%7,%8,%9,%10,%11,%12,%13,%14,%15,%16,%17,%18,%19,%20,%21,%22,%23,%24,%25,%26,%27,%28,%29,%30,%31,%32,%33,%34,%35}, %36, %37, p, 1, 1, 0, 1;\n}"
    : "+f"(d[0]),"+f"(d[1]),"+f"(d[2]),"+f"(d[3]),"+f"(d[4]),"+f"(d[5]),"+f"(d[6]),"+f"(d[7]),"+f"(d[8]),"+f"(d[9]),"+f"(d[10]),"+f"(d[11]),"+f"(d[12]),"+f"(d[13]),"+f"(d[14]),"+f"(d[15]),"+f"(d[16]),"+f"(d[17]),"+f"(d[18]),"+f"(d[19]),"+f"(d[20]),"+f"(d[21]),"+f"(d[22]),"+f"(d[23]),"+f"(d[24]),"+f"(d[25]),"+f"(d[26]),"+f"(d[27]),"+f"(d[28]),"+f"(d[29]),"+f"(d[30]),"+f"(d[31]),"+f"(d[32]),"+f"(d[33]),"+f"(d[34]),"+f"(d[35])
    : "l"(ad), "l"(bd));
  }
}
template<int SD> __device__ __forceinline__ void wg_tt64(float* d, uint64_t ad, uint64_t bd) {
  if constexpr (SD) {
    asm volatile("{\n.reg .pred p;\nsetp.eq.b32 p, 0, 0;\n"
    "wgmma.mma_async.sync.aligned.m64n64k16.f32.bf16.bf16 {%0,%1,%2,%3,%4,%5,%6,%7,%8,%9,%10,%11,%12,%13,%14,%15,%16,%17,%18,%19,%20,%21,%22,%23,%24,%25,%26,%27,%28,%29,%30,%31}, %32, %33, p, 1, 1, 1, 1;\n}"
    : "+f"(d[0]),"+f"(d[1]),"+f"(d[2]),"+f"(d[3]),"+f"(d[4]),"+f"(d[5]),"+f"(d[6]),"+f"(d[7]),"+f"(d[8]),"+f"(d[9]),"+f"(d[10]),"+f"(d[11]),"+f"(d[12]),"+f"(d[13]),"+f"(d[14]),"+f"(d[15]),"+f"(d[16]),"+f"(d[17]),"+f"(d[18]),"+f"(d[19]),"+f"(d[20]),"+f"(d[21]),"+f"(d[22]),"+f"(d[23]),"+f"(d[24]),"+f"(d[25]),"+f"(d[26]),"+f"(d[27]),"+f"(d[28]),"+f"(d[29]),"+f"(d[30]),"+f"(d[31])
    : "l"(ad), "l"(bd));
  } else {
    asm volatile("{\n.reg .pred p;\nsetp.ne.b32 p, 0, 0;\n"
    "wgmma.mma_async.sync.aligned.m64n64k16.f32.bf16.bf16 {%0,%1,%2,%3,%4,%5,%6,%7,%8,%9,%10,%11,%12,%13,%14,%15,%16,%17,%18,%19,%20,%21,%22,%23,%24,%25,%26,%27,%28,%29,%30,%31}, %32, %33, p, 1, 1, 1, 1;\n}"
    : "+f"(d[0]),"+f"(d[1]),"+f"(d[2]),"+f"(d[3]),"+f"(d[4]),"+f"(d[5]),"+f"(d[6]),"+f"(d[7]),"+f"(d[8]),"+f"(d[9]),"+f"(d[10]),"+f"(d[11]),"+f"(d[12]),"+f"(d[13]),"+f"(d[14]),"+f"(d[15]),"+f"(d[16]),"+f"(d[17]),"+f"(d[18]),"+f"(d[19]),"+f"(d[20]),"+f"(d[21]),"+f"(d[22]),"+f"(d[23]),"+f"(d[24]),"+f"(d[25]),"+f"(d[26]),"+f"(d[27]),"+f"(d[28]),"+f"(d[29]),"+f"(d[30]),"+f"(d[31])
    : "l"(ad), "l"(bd));
  }
}

template<int V> struct IC { static constexpr int v = V; };
template<int I, int N, class F> __device__ __forceinline__ void sfor(F&& f) {
    if constexpr (I < N) { f(IC<I>{}); sfor<I + 1, N>(f); }
}

enum { K_QKV = 0, K_H = 1 };

struct Ctx {
    uint32_t tph;
    uint32_t tid_;
    bool pf = false;
    __device__ __forceinline__ uint32_t tid() const { uint32_t r; asm volatile("mov.u32 %0, %1;" : "=r"(r) : "r"(tid_)); return r; }
};
__device__ __forceinline__ void release_slot(const Ctx& c, int slot) { if ((c.tid() & 31) == 0) mbar_arrive(bar(B_EMPTY + slot)); }

__device__ __forceinline__ void turn_wait(const Ctx& c) { asm volatile("bar.sync %0, 256;" :: "r"(4 + (c.tid() >> 7)) : "memory"); }
__device__ __forceinline__ void turn_pass(const Ctx& c) { asm volatile("bar.arrive %0, 256;" :: "r"(5 - (c.tid() >> 7)) : "memory"); }

template<int KIND, class PART, class POST>
__device__ __forceinline__ void run_step(Ctx& c, float* acc, const uint32_t* a, PART&& part, POST&& post, bool last = false) {
    constexpr int NST = (KIND == K_QKV) ? 6 : 3;
    constexpr int KPS = 36 / NST;
    sfor<0, NST>([&](auto ST) {
        constexpr int st = decltype(ST)::v;
        constexpr int slot = st % 3;
        mbar_wait(bar(B_FULL + slot), c.tph);
        uint32_t wgo = 0;
        if constexpr (st == NST - 1) wgo = (c.tid() >> 7) * 512;
        if (KIND == K_H && c.pf) prof(44 + st * 5);
        turn_wait(c);
        if (KIND == K_H && c.pf) prof(45 + st * 5);
        wg_fence();
        sfor<0, KPS>([&](auto KK) {
            constexpr int kk = decltype(KK)::v;
            constexpr int ks = st * KPS + kk;
            constexpr int SD = ks ? 1 : 0;
            if constexpr (KIND == K_QKV) {
                constexpr uint64_t bd = mkdesc(RING + slot * SLOT + kk * 2048, 12288, 1024, 1);
                if constexpr (ks < 32) wg_rs72<SD>(acc, a + ks * 4, bd);
                else wg_ss72<SD>(acc, mkdesc(XB + (ks - 32) * 32, 16, 1024, 1) + wgo, bd);
            } else {
                constexpr uint64_t bd = mkdesc(RING + slot * SLOT + kk * 2048, 16, 1024, 1);
                if constexpr (ks < 32) wg_rs64<SD>(acc, a + ks * 4, bd);
                else wg_ss64<SD>(acc, mkdesc(XB + (ks - 32) * 32, 16, 1024, 1) + wgo, bd);
            }
        });
        wg_commit();
        if (st < NST - 1 || !last || c.tid() < 128) turn_pass(c);
        if (KIND == K_H && c.pf) prof(46 + st * 5);
        part(ST);
        if (KIND == K_H && c.pf) prof(47 + st * 5);
        wg_wait<0>();
        if (KIND == K_H && c.pf) prof(48 + st * 5);
        release_slot(c, slot);
        if constexpr (slot == 2) c.tph ^= 1;
        post(ST);
    });
    if constexpr (KIND == K_QKV) reg_fence<36>(acc); else reg_fence<32>(acc);
}

__device__ __forceinline__ float phi(float t) {
    float e = ex2(t * 1.4426950408889634f);
    return (t > 0.f ? t + 1.0f : e) + 1e-6f;
}
__device__ __forceinline__ float gelu_h(float hx) {
    float u = hx * fmaf(hx * hx, 0.2854192650f, 1.5957691216f);
    return fmaf(hx, tanh_ap(u), hx);
}

struct Params {
    const __nv_bfloat16* x;
    const __nv_bfloat16* wqkv;
    const __nv_bfloat16* wo;
    const __nv_bfloat16* w1;
    const __nv_bfloat16* b1;
    const __nv_bfloat16* w2;
    const __nv_bfloat16* b2;
    __nv_bfloat16* out;
};

__global__ void __launch_bounds__(384, 1)
fused_kernel(const __grid_constant__ CUtensorMap tm_x, const __grid_constant__ CUtensorMap tm_w1,
             const __grid_constant__ CUtensorMap tm_w2, const __grid_constant__ CUtensorMap tm_wo,
             const __grid_constant__ CUtensorMap tm_o, const __grid_constant__ CUtensorMap tm_qkv,
             const __grid_constant__ CUtensorMap tm_qkve, const Params p) {
    extern __shared__ __align__(1024) unsigned char smem_raw[];
    const int tid = threadIdx.x;
    const int bid = blockIdx.x;
    const bool is_main = bid < NMAIN;
    const int j = bid & 7;
    const int m = bid >> 3;

    if (tid == 0) {
        if ((uint32_t)__cvta_generic_to_shared(smem_raw) != SB) __trap();
        for (int i = 0; i < 3; i++) {
            mbar_init(bar(B_FULL + i), 1); mbar_init(bar(B_EMPTY + i), 8);
            mbar_init(bar(B_XFULL + i), 1);
        }
        mbar_init(bar(B_KVB), is_main ? 2 : 8); mbar_init(bar(B_YRDY), 1);
        mbar_init(bar(B_OFULL), 1); mbar_init(bar(B_O8FULL), 1); mbar_init(bar(B_OFREE), 8); mbar_init(bar(B_O8FREE), 8);
        asm volatile("fence.mbarrier_init.release.cluster;" ::: "memory");
        if (is_main) {
            for (int g = 0; g < 3; g++) {
                mbar_expect_tx(bar(B_XFULL + g), 49152);
                for (int kb = 3 * g; kb < 3 * g + 3; kb++) tma_2d(HA + kb * 16384, &tm_x, bar(B_XFULL + g), kb * 64, m * 128);
            }
            for (int st = 0; st < 3; st++) {
                mbar_expect_tx(bar(B_FULL + st), 96 * 144);
                tma_2d(RING + st * SLOT, &tm_qkv, bar(B_FULL + st), 576 + j * 72, st * 96);
                tma_2d(RING + st * SLOT + 12288, &tm_qkve, bar(B_FULL + st), 576 + j * 72 + 64, st * 96);
            }
        }
    }
    if (tid == 32) sts32(EPO, g_epoch[bid]);
    if (tid >= 40 && tid < 48) sts32(EVC + (tid - 40) * 4, 0);
    if (tid >= 64 && tid < 64 + 288 && is_main) {
        int i = tid - 64;
        uint32_t v = *reinterpret_cast<const uint32_t*>(p.b1 + j * 576 + 2 * i);
        sts32(B1S + 8 * i, __float_as_uint(0.5f * bf_lo(v))); sts32(B1S + 8 * i + 4, __float_as_uint(0.5f * bf_hi(v)));
    }
    if (tid >= 352) {
        int i = tid - 352;
        uint32_t v = *reinterpret_cast<const uint32_t*>(p.b2 + (is_main ? j : 8) * 64 + 2 * i);
        sts32(B2S + 8 * i, v << 16); sts32(B2S + 8 * i + 4, v & 0xffff0000u);
    }
    fence_async_smem();
    __syncthreads();
    uint32_t epoch;
    asm volatile("ld.shared.u32 %0, [%1];" : "=r"(epoch) : "r"(EPO));
    const uint32_t par = epoch & 1;

    if (tid >= 256) {
        asm volatile("setmaxnreg.dec.sync.aligned.u32 24;");
        const int hw = (tid >> 5) - 8, lane = tid & 31;
        if (hw == 0) {
            if (lane == 0) {
                uint32_t n = 0;
                if (is_main) {
                    n = 1;
                    #pragma unroll 1
                    for (int u = 3; u < 18; u++) {
                        const int st = u % 3, step = u / 6;
                        const int col = ((step == 2) ? 0 : (step + 1) * 576) + j * 72, row = (u % 6) * 96;
                        mbar_wait(bar(B_EMPTY + st), (n & 1) ^ 1);
                        mbar_expect_tx(bar(B_FULL + st), 96 * 144);
                        tma_2d(RING + st * SLOT, &tm_qkv, bar(B_FULL + st), col, row);
                        tma_2d(RING + st * SLOT + 12288, &tm_qkve, bar(B_FULL + st), col + 64, row);
                        if (st == 2) n++;
                    }
                }
                const int nsteps = is_main ? 19 : 1;
                #pragma unroll 1
                for (int s = 0; s < nsteps; s++, n++) {
                    const CUtensorMap* tm; int col, row;
                    if (!is_main) { tm = &tm_wo; col = 512; row = 0; }
                    else if (s < 9) { tm = &tm_w1; col = j * 576 + s * 64; row = 0; }
                    else if (s < 18) { tm = &tm_w2; col = (s == 9) ? 512 : (((j + s - 9) & 7) * 64); row = j * 576; }
                    else { tm = &tm_wo; col = j * 64; row = 0; }
                    #pragma unroll 1
                    for (int st = 0; st < 3; st++) {
                        mbar_wait(bar(B_EMPTY + st), (n & 1) ^ 1);
                        mbar_expect_tx(bar(B_FULL + st), SLOT);
                        tma_2d(RING + st * SLOT, tm, bar(B_FULL + st), col, row + st * 192);
                    }
                }
            }
        } else {
            if (is_main) {
                const int t = tid - 288;
                #pragma unroll 1
                for (int i = t; i < 36 * 6; i += 96) {
                    int r = i / 6, q = i - r * 6;
                    prefetch_l2(reinterpret_cast<const char*>(p.wqkv) + (36 * m + r) * 3456 + (q >> 1) * 1152 + j * 144 + (q & 1) * 128);
                }
                __nanosleep(PF1_NS);
                #pragma unroll 1
                for (int i = t; i < 36 * 9; i += 96) {
                    int r = i / 9, q = i - r * 9;
                    prefetch_l2(reinterpret_cast<const char*>(p.w1) + (36 * m + r) * 9216 + j * 1152 + q * 128);
                    __nanosleep(PF3_NS);
                }
                __nanosleep(PF2_NS);
                #pragma unroll 1
                for (int i = t; i < 36 * 9; i += 96)
                    prefetch_l2(reinterpret_cast<const char*>(p.w2) + (576 * j + 36 * m) * 1152 + i * 128);
                if (t < 41 && (bid * 41 + t) < 5184) prefetch_l2(reinterpret_cast<const char*>(p.wo) + (bid * 41 + t) * 128);
                if (hw != 2) {
                    if (lane == 0) wait_cnt(cnt_kv(j), (epoch + 1) * 16);
                    __syncwarp();
                    const float4* kv = reinterpret_cast<const float4*>(g_kv + (par * 8 + j) * 1440);
                    #pragma unroll 2
                    for (int i = lane + (hw == 1 ? 0 : 32); i < 360; i += 64) {
                        const float4 v = __ldcg(kv + i);
                        const int d = i / 5, e = (i - d * 5) * 4, h = d / 18;
                        const uint32_t base = KVB + (d >> 3) * 128 + (d & 7) * 16;
                        const int n0 = 8 + h * 18 + e;
                        sts32(base + (n0 >> 3) * 1280 + (n0 & 7) * 2, pack_bf16(v.x, v.y));
                        if (e < 16) sts32(base + ((n0 + 2) >> 3) * 1280 + ((n0 + 2) & 7) * 2, pack_bf16(v.z, v.w));
                        else asm volatile("st.shared.u16 [%0], %1;" :: "r"(base + h * 2), "h"((unsigned short)pack_bf16(v.z, 0.f)) : "memory");
                    }
                    fence_async_smem();
                    __syncwarp();
                    if (lane == 0) mbar_arrive(bar(B_KVB));
                }
            }
            if (hw == 1) {
                if (lane == 0) {
                    const int nit = is_main ? 1 : 4;
                    for (int it = 0; it < nit; it++) {
                        const int mt = is_main ? m : ((bid - NMAIN) * 4 + it);
                        const bool wf = is_main || it > 0;
                        const uint32_t fp = is_main ? 0 : ((it - 1) & 1);
                        wait_cnt(cnt_o(mt), (epoch + 1) * 8);
                        fence_async_all();
                        if (wf) mbar_wait(bar(B_OFREE), fp);
                        mbar_expect_tx(bar(B_OFULL), 131072);
                        #pragma unroll 1
                        for (int kb = 0; kb < 8; kb++) tma_2d(HA + kb * 16384, &tm_o, bar(B_OFULL), kb * 64, mt * 128);
                        if (wf) mbar_wait(bar(B_O8FREE), fp);
                        mbar_expect_tx(bar(B_O8FULL), 16384);
                        tma_2d(XB, &tm_o, bar(B_O8FULL), 512, mt * 128);
                    }
                    if (is_main) { wait_cnt(cnt_y(m, j), (epoch + 1) * 7); mbar_arrive(bar(B_YRDY)); }
                }
            } else if (hw == 2) {
                if (!is_main) {
                    if (lane == 0) {
                        #pragma unroll 1
                        for (int it = 0; it < 4; it++) {
                            if (it > 0) mbar_wait(bar(B_KVB), (it - 1) & 1);
                            wait_cnt(cnt_y((bid - NMAIN) * 4 + it, 8), (epoch + 1) * 8);
                            mbar_arrive(bar(B_YRDY));
                        }
                    }
                } else {
                    #pragma unroll 1
                    for (int e = 0; e < 10; e++) {
                        int spin = 0;
                        while (true) {
                            uint32_t v;
                            asm volatile("ld.acquire.cta.shared.u32 %0, [%1];" : "=r"(v) : "r"(EVC + (lane & 7) * 4) : "memory");
                            if (__all_sync(0xffffffffu, v > (uint32_t)e)) break;
                            if (++spin > 20000000) __trap();
                            __nanosleep(20);
                        }
                        if (lane == 0) {
                            unsigned int* cp = (e == 0) ? cnt_kv(j) : (e == 1) ? cnt_o(m) : cnt_y(m, e == 2 ? 8 : ((j + e - 2) & 7));
                            if (e == 1) fence_async_all();
                            __threadfence();
                            asm volatile("red.relaxed.gpu.global.add.u32 [%0], 1;" :: "l"(cp) : "memory");
                        }
                        __syncwarp();
                    }
                }
            } else {
                {
                    const int t0 = is_main ? (m * 9 + j) : ((bid - NMAIN) * 4 * 9 + 8);
                    const int nt = is_main ? 1 : 4;
                    for (int t = 0; t < nt; t++) {
                        uint4* z = reinterpret_cast<uint4*>(g_yacc + (size_t)((par ^ 1) * 144 + t0 + t * 9) * YT_BYTES);
                        for (int i = lane; i < YT_BYTES / 16; i += 32) z[i] = make_uint4(0, 0, 0, 0);
                    }
                    if (is_main && m == 0) {
                        float* z = g_kv + ((par ^ 1) * 8 + j) * 1440;
                        for (int i = lane; i < 1440; i += 32) z[i] = 0.f;
                    }
                }
            }
        }
    } else {
        asm volatile("setmaxnreg.inc.sync.aligned.u32 240;");
        prof(0);
        Ctx c; c.tph = 0; c.tid_ = v_tid();
        float hc[32], pv[36];
        if (tid >> 7) turn_pass(c);
        auto event = [&](uint32_t ev) {
            __syncwarp();
            if (((c.tid() & 31) == 0)) asm volatile("st.release.cta.shared.u32 [%0], %1;" :: "r"(EVC + (c.tid() >> 3)), "r"(ev) : "memory");
        };
        auto warp_arrive = [&](uint32_t b) { __syncwarp(); if (((c.tid() & 31) == 0)) mbar_arrive(b); };

        uint32_t a[128];
        float rs0 = 0.f, rs1 = 0.f;
        auto lrow_off = [&]() { uint32_t t_ = c.tid(); return HA + ((t_ >> 5) * 16 + (t_ & 15)) * 128 + ((((t_ >> 4) & 1) ^ (t_ & 7)) << 4); };
        auto tail_off = [&]() { uint32_t t_ = c.tid(), g = (t_ >> 2) & 7; return XB + ((t_ >> 5) * 16 + g) * 128 + (g << 4) + (t_ & 3) * 4; };
        if (!is_main) {
            #pragma unroll
            for (int i = 0; i < 128; i++) a[i] = 0;
            #pragma unroll
            for (int i = 0; i < 32; i++) { hc[i] = 0.f; pv[i] = 0.f; }
        } else {
            uint32_t m00, m11;
            {
                uint32_t tl[16];
                const uint32_t lrow = lrow_off();
                float cs[2][4] = {{0.f, 0.f, 0.f, 0.f}, {0.f, 0.f, 0.f, 0.f}};
                sfor<0, 36>([&](auto KS) {
                    constexpr int ks = decltype(KS)::v;
                    if constexpr (ks % 12 == 0) mbar_wait(bar(B_XFULL + ks / 12), 0);
                    uint32_t* dst = (ks < 32) ? (a + (ks & 31) * 4) : (tl + (ks & 3) * 4);
                    ldsm4((lrow ^ ((ks % 4) << 5)) + (ks / 4) * 16384, dst);
                    mma_ones(cs[ks & 1], dst);
                });
                prof(2);
                float mean0 = (cs[0][0] + cs[1][0]) * (1.0f / 576.0f), mean1 = (cs[0][2] + cs[1][2]) * (1.0f / 576.0f);
                m00 = pack_bf16(mean0, mean0); m11 = pack_bf16(mean1, mean1);
                rs0 = mean0 - bf_lo(m00); rs1 = mean1 - bf_lo(m11);
                rs0 = -144.0f * rs0 * rs0; rs1 = -144.0f * rs1 * rs1;
                const uint32_t tb = tail_off();
                #pragma unroll
                for (int i = 0; i < 16; i++) {
                    const uint32_t w = sub_bf16x2(tl[i], (i & 1) ? m11 : m00);
                    sts32((tb ^ ((i >> 1) << 4)) + (i & 1) * 1024, w);
                    float lo = bf_lo(w), hi = bf_hi(w);
                    if (i & 1) rs1 = fmaf(lo, lo, fmaf(hi, hi, rs1)); else rs0 = fmaf(lo, lo, fmaf(hi, hi, rs0));
                }
                fence_async_smem();
                #pragma unroll
                for (int i = 0; i < 128; i++) a[i] = sub_bf16x2(a[i], (i & 1) ? m11 : m00);
                named_bar(2 + (tid >> 7), 128);
            }
            prof(3);
            auto cm_off = [&]() { uint32_t t_ = c.tid(); return (t_ >> 5) * 256 + (t_ & 31) * 4; };
            {
                float qc[36];
                #pragma unroll
                for (int i = 0; i < 36; i++) { qc[i] = 0.f; pv[i] = 0.f; }
                #pragma unroll 1
                for (int s = 0; s < 3; s++) {
                    run_step<K_QKV>(c, qc, a, [&](auto ST) {
                        constexpr int st = decltype(ST)::v;
                        if (s == 0) {
                            const uint32_t lrow = lrow_off();
                            sfor<(st * 32) / 6, ((st + 1) * 32) / 6>([&](auto I) {
                                constexpr int ks = decltype(I)::v;
                                uint32_t v[4];
                                ldsm4((lrow ^ ((ks % 4) << 5)) + (ks / 4) * 16384, v);
                                #pragma unroll
                                for (int r = 0; r < 4; r++) {
                                    uint32_t w = sub_bf16x2(v[r], (r & 1) ? m11 : m00);
                                    float lo = bf_lo(w), hi = bf_hi(w);
                                    if (r & 1) rs1 = fmaf(lo, lo, fmaf(hi, hi, rs1)); else rs0 = fmaf(lo, lo, fmaf(hi, hi, rs0));
                                }
                            });
                            if constexpr (st == 5) {
                                rs0 += __shfl_xor_sync(0xffffffffu, rs0, 1); rs1 += __shfl_xor_sync(0xffffffffu, rs1, 1);
                                rs0 += __shfl_xor_sync(0xffffffffu, rs0, 2); rs1 += __shfl_xor_sync(0xffffffffu, rs1, 2);
                                rs0 = rsqrtf(fmaxf(rs0 * (1.0f / 576.0f), 0.f) + 1e-5f);
                                rs1 = rsqrtf(fmaxf(rs1 * (1.0f / 576.0f), 0.f) + 1e-5f);
                                named_bar(1, 256);
                            }
                        } else {
                            const uint32_t cm = cm_off();
                            sfor<0, 9>([&](auto B) {
                                constexpr int b = decltype(B)::v;
                                if constexpr ((b * 6) / 9 == st) {
                                    const float v0 = pv[4 * b] * rs0, v1 = pv[4 * b + 1] * rs0, v2 = pv[4 * b + 2] * rs1, v3 = pv[4 * b + 3] * rs1;
                                    if (s == 1) {
                                        sts32(PKT + b * 2048 + cm, pack_bf16(phi(v0), phi(v1)));
                                        sts32(PKT + b * 2048 + cm + 128, pack_bf16(phi(v2), phi(v3)));
                                    } else {
                                        const uint32_t w0 = pack_bf16(v0, v1), w1 = pack_bf16(v2, v3);
                                        if constexpr (b <= 4) { sts32(VT + b * 2048 + cm, w0); sts32(VT + b * 2048 + cm + 128, w1); }
                                        if constexpr (b >= 4) { sts32(VT + (b + 2) * 2048 + cm, w0); sts32(VT + (b + 2) * 2048 + cm + 128, w1); }
                                        if constexpr (b == 0) {
                                            const uint32_t one = (cm & 12) ? 0u : 0x00003F80u;
                                            sts32(VT + 5 * 2048 + cm, one); sts32(VT + 5 * 2048 + cm + 128, one);
                                        }
                                        if constexpr (b == 8) {
                                            const uint32_t z = KVB + c.tid() * 16;
                                            sts128(z, 0, 0, 0, 0); sts128(z + 4096, 0, 0, 0, 0); sts128(z + 8192, 0, 0, 0, 0);
                                            if (z < KVB + 512) sts128(z + 12288, 0, 0, 0, 0);
                                            fence_async_smem();
                                        }
                                    }
                                }
                            });
                        }
                    }, [](auto) {});
                    reg_copy<36>(pv, qc);
                    prof(4 + s);
                }
            }
            {
                #pragma unroll
                for (int i = 0; i < 32; i++) hc[i] = 0.f;
                named_bar(1, 256);
                const uint32_t wgo = ((c.tid() >> 7) * 512);
                wg_fence();
                sfor<0, 8>([&](auto KS) {
                    constexpr int ks = decltype(KS)::v;
                    wg_tt64<(ks ? 1 : 0)>(hc, mkdesc(PKT + ks * 256, 128, 2048, 0) + wgo,
                                          mkdesc(VT + ks * 256, 128, 2048, 0) + wgo + (wgo >> 2));
                });
                wg_commit();
                const uint32_t pq = PQT + cm_off() + ((c.tid() >> 7) * 512) * 16;
                sfor<0, 9>([&](auto B) {
                    constexpr int b = decltype(B)::v;
                    sts32(pq + b * 1024, pack_bf16(phi(pv[4 * b] * rs0), phi(pv[4 * b + 1] * rs0)));
                    sts32(pq + b * 1024 + 128, pack_bf16(phi(pv[4 * b + 2] * rs1), phi(pv[4 * b + 3] * rs1)));
                });
                fence_async_smem();
                wg_wait<0>();
                reg_fence<32>(hc);
                reg_copy<24>(pv, hc);
            }
            prof(7);
            rs0 *= 0.5f; rs1 *= 0.5f;
        }
        {
            auto gelun = [&](auto B0, auto B1, uint32_t bofs, uint32_t* w) {
                constexpr int b0 = decltype(B0)::v, nb = decltype(B1)::v - b0;
                float2 bv[nb];
                #pragma unroll
                for (int i = 0; i < nb; i++) bv[i] = lds64f(bofs + (b0 + i) * 32);
                #pragma unroll
                for (int i = 0; i < nb; i++) {
                    const int b = b0 + i;
                    w[2 * i]     = pack_bf16(gelu_h(fmaf(pv[4 * b], rs0, bv[i].x)), gelu_h(fmaf(pv[4 * b + 1], rs0, bv[i].y)));
                    w[2 * i + 1] = pack_bf16(gelu_h(fmaf(pv[4 * b + 2], rs1, bv[i].x)), gelu_h(fmaf(pv[4 * b + 3], rs1, bv[i].y)));
                }
            };
            auto spill_off = [&]() { uint32_t t_ = c.tid(); return HA + (t_ >> 7) * 8192 + (t_ & 127) * 8; };
            auto reload = [&](auto S0, auto S1) {
                const uint32_t spill = spill_off();
                sfor<decltype(S0)::v * 8, decltype(S1)::v * 8>([&](auto Q) {
                    constexpr int q = decltype(Q)::v;
                    lds64(spill + (q / 8) * 16384 + (q % 8) * 1024, a + q * 2);
                });
            };
            const int it_beg = (blockIdx.x < NMAIN) ? 0 : 19, it_end = (blockIdx.x < NMAIN) ? 19 : 23;
            #pragma unroll 1
            for (int it = it_beg; it < it_end; it++) {
                const int idx = it;
                auto jpar = [&]() { return (uint32_t)(it > 18 ? ((it - 19) & 1) : 0); };
                auto ftile = [&]() {
                    const uint32_t b_ = v_bid();
                    return (int)(it == 18 ? ((b_ >> 3) * 9 + (b_ & 7)) : (((b_ - NMAIN) * 4 + it - 19) * 9 + 8));
                };
                uint32_t* const xr = a;
                uint32_t* const yv = a + 16;
                auto out_off = [&]() {
                    const int ft = ftile(), mt = ft / 9, ch = ft - mt * 9;
                    return (size_t)(mt * 128 + (c.tid() >> 5) * 16 + ((c.tid() >> 2) & 7)) * DM + ch * 64 + 2 * (c.tid() & 3);
                };
                if (idx >= 18) {
                    mbar_wait(bar(B_OFULL), jpar());
                    const uint32_t lrow = lrow_off();
                    sfor<0, 32>([&](auto KS) {
                        constexpr int ks = decltype(KS)::v;
                        ldsm4((lrow ^ ((ks % 4) << 5)) + (ks / 4) * 16384, a + ks * 4);
                    });
                    warp_arrive(bar(B_OFREE));
                    if (it > 18) c.tph = 0;
                }
                run_step<K_H>(c, hc, a, [&](auto ST) {
                    constexpr int st = decltype(ST)::v;
                    if (idx >= 18) {
                        if constexpr (st == 0) {
                            #pragma unroll
                            for (int b = 0; b < 8; b++) {
                                float2 bv = lds64f(B2S + b * 32 + (c.tid() & 3) * 8);
                                pv[4 * b] += bv.x; pv[4 * b + 1] += bv.y; pv[4 * b + 2] += bv.x; pv[4 * b + 3] += bv.y;
                            }
                        } else if constexpr (st == 1) {
                            prof(26);
                            mbar_wait(bar(B_YRDY), jpar());
                            prof(27);
                            const unsigned char* yp = g_yacc + ((v_epoch() & 1) * 144 + ftile()) * YT_BYTES + c.tid() * 16;
                            #pragma unroll
                            for (int q = 0; q < YT_BYTES / 4096; q++)
                                asm volatile("ld.global.cg.v4.u32 {%0,%1,%2,%3}, [%4];" : "=r"(yv[4 * q]), "=r"(yv[4 * q + 1]), "=r"(yv[4 * q + 2]), "=r"(yv[4 * q + 3]) : "l"(yp + q * 4096) : "memory");
                            const __nv_bfloat16* xp = p.x + out_off();
                            #pragma unroll
                            for (int i = 0; i < 8; i++) {
                                asm volatile("ld.global.nc.u32 %0, [%1];" : "=r"(xr[2 * i]) : "l"(xp + i * 8));
                                asm volatile("ld.global.nc.u32 %0, [%1];" : "=r"(xr[2 * i + 1]) : "l"(xp + 8 * DM + i * 8));
                            }
                            if (it > 18) warp_arrive(bar(B_KVB));
                            mbar_wait(bar(B_O8FULL), jpar());
                        } else {
                            prof(28);
                            #pragma unroll
                            for (int i = 0; i < 16; i++) { pv[2 * i] += bf_lo(yv[i]); pv[2 * i + 1] += bf_hi(yv[i]); }
                            #pragma unroll
                            for (int i = 0; i < 32; i++) pv[i] = pv[i] * rcp(1.0f + ex2(pv[i] * -1.4426950408889634f));
                            prof(29);
                        }
                    } else
                    if (idx >= 10) {
                        if constexpr (st < 2) {
                            const uint32_t b_ = v_bid();
                            const uint32_t chunk = (idx == 10) ? 8 : ((b_ + idx - 10) & 7);
                            unsigned char* yp = g_yacc + ((v_epoch() & 1) * 144 + (b_ >> 3) * 9 + chunk) * YT_BYTES + c.tid() * 16;
                            sfor<2 * st, 2 * st + 2>([&](auto Q) {
                                constexpr int q = decltype(Q)::v;
                                asm volatile("red.global.add.noftz.v4.bf16x2 [%0], {%1,%2,%3,%4};" :: "l"(yp + q * 4096),
                                             "r"(pack_bf16(pv[8 * q], pv[8 * q + 1])), "r"(pack_bf16(pv[8 * q + 2], pv[8 * q + 3])),
                                             "r"(pack_bf16(pv[8 * q + 4], pv[8 * q + 5])), "r"(pack_bf16(pv[8 * q + 6], pv[8 * q + 7])) : "memory");
                            });
                            if constexpr (st == 1) event(idx - 7);
                        }
                    } else if (idx >= 1) {
                        const uint32_t bofs = B1S + (idx - 1) * 256 + (c.tid() & 3) * 8;
                        if (idx < 9) {
                            if constexpr (st == 0) { if (idx == OSTEP_AT + 1) event(2); }
                            const uint32_t spill = spill_off() + (idx - 1) * 16384;
                            constexpr int b0 = st * 3, b1 = (st == 2 ? 8 : st * 3 + 3);
                            uint32_t w[6];
                            gelun(IC<b0>{}, IC<b1>{}, bofs, w);
                            #pragma unroll
                            for (int b = b0; b < b1; b++) sts64(spill + b * 1024, w[2 * (b - b0)], w[2 * (b - b0) + 1]);
                        } else {
                            if constexpr (st < 2) {
                                const uint32_t tb = tail_off();
                                uint32_t w[8];
                                gelun(IC<st * 4>{}, IC<st * 4 + 4>{}, bofs, w);
                                #pragma unroll
                                for (int i = 0; i < 4; i++) { sts32(tb ^ ((st * 4 + i) << 4), w[2 * i]); sts32((tb ^ ((st * 4 + i) << 4)) + 1024, w[2 * i + 1]); }
                            }
                            if constexpr (st == 1) { fence_async_smem(); named_bar(2 + (c.tid() >> 7), 128); }
                        }
                    } else {
                        if constexpr (st < 2) {
                            constexpr int hf = st;
                            const int t_ = c.tid(), wg = t_ >> 7, t = t_ & 3;
                            float* dst = g_kv + ((v_epoch() & 1) * 8 + (v_bid() & 7)) * 1440;
                            const int d = wg * 32 + ((t_ >> 5) & 3) * 16 + ((t_ >> 2) & 7) + hf * 8;
                            const bool dv = wg ? (d >= 36 && d < 72) : (d < 36);
                            const int e00 = wg * 24 + 2 * t - (d / 18) * 18;
                            float* dp = dst + d * 20 + e00;
                            #pragma unroll
                            for (int i = 0; i < 6; i++) {
                                const int e = e00 + i * 8;
                                const bool blk = wg ? (i >= 1) : (i <= 4);
                                if (dv && blk && e >= 0 && e < 18)
                                    asm volatile("red.global.add.v2.f32 [%0], {%1,%2};" :: "l"(dp + i * 8), "f"(pv[4 * i + 2 * hf]), "f"(pv[4 * i + 2 * hf + 1]) : "memory");
                            }
                            if (dv && t == 0) atomicAdd(dst + d * 20 + 18, wg ? pv[2 * hf] : pv[20 + 2 * hf]);
                            if constexpr (st == 1) event(1);
                        }
                    }
                }, [&](auto ST) {
                    constexpr int st = decltype(ST)::v;
                    if (idx == 8) {
                        reload(IC<3 * st>{}, IC<(st == 2 ? 8 : 3 * st + 3)>{});
                        if constexpr (st == 2) warp_arrive(bar(B_OFREE));
                    }
                }, it == 18 || it == 22);
                if (idx >= 17) warp_arrive(bar(B_O8FREE));
                if (idx >= 18) {
                    prof(30);
                    __nv_bfloat16* op = p.out + out_off();
                    #pragma unroll
                    for (int b = 0; b < 8; b++) {
                        *reinterpret_cast<uint32_t*>(op + b * 8) =
                            pack_bf16(fmaf(hc[4 * b], pv[4 * b], bf_lo(xr[2 * b])), fmaf(hc[4 * b + 1], pv[4 * b + 1], bf_hi(xr[2 * b])));
                        *reinterpret_cast<uint32_t*>(op + 8 * DM + b * 8) =
                            pack_bf16(fmaf(hc[4 * b + 2], pv[4 * b + 2], bf_lo(xr[2 * b + 1])), fmaf(hc[4 * b + 3], pv[4 * b + 3], bf_hi(xr[2 * b + 1])));
                    }
                    #pragma unroll
                    for (int i = 0; i < 32; i++) pv[i] = 0.f;
                    if (it > 18) prof(it - 11);
                } else {
                    reg_copy<32>(pv, hc);
                    prof(8 + idx);
                }
                if (idx == OSTEP_AT) {
                    mbar_wait(bar(B_KVB), 0);
                    prof(34);
                    const uint32_t pqo = (c.tid() >> 7) * 576;
                    const int t_ = c.tid(), b_ = v_bid(), t = t_ & 3, l4 = t_ & 28;
                    __nv_bfloat16* op = g_o + (size_t)((b_ >> 3) * 128 + (t_ >> 5) * 16 + ((t_ >> 2) & 7)) * DM + (b_ & 7) * 72 + 2 * t;
                    float r3[2];
                    sfor<0, 2>([&](auto PS) {
                        constexpr int ps = decltype(PS)::v;
                        wg_fence();
                        sfor<0, 5>([&](auto KS) {
                            constexpr int ks = decltype(KS)::v;
                            wg_ss64<(ks ? 1 : 0)>(hc, mkdesc(PQT + ks * 2048, ks == 4 ? 0 : 1024, 128, 0) + pqo, mkdesc(KVB + ps * 8 * 1280 + ks * 256, 128, 1280, 0));
                        });
                        wg_commit();
                        wg_wait<0>();
                        reg_fence<32>(hc);
                        #pragma unroll
                        for (int hf = 0; hf < 2; hf++) {
                            if constexpr (ps == 0) {
                                float r[4];
                                r[0] = rcp(__shfl_sync(0xffffffffu, hc[2 * hf], l4) + 1e-6f);
                                r[1] = rcp(__shfl_sync(0xffffffffu, hc[1 + 2 * hf], l4) + 1e-6f);
                                r[2] = rcp(__shfl_sync(0xffffffffu, hc[2 * hf], l4 + 1) + 1e-6f);
                                r[3] = rcp(__shfl_sync(0xffffffffu, hc[1 + 2 * hf], l4 + 1) + 1e-6f);
                                r3[hf] = r[3];
                                #pragma unroll
                                for (int i = 0; i < 7; i++) {
                                    float rr = (i < 2) ? r[0] : (i == 2) ? (t < 1 ? r[0] : r[1]) : (i == 3) ? r[1] : (i == 4) ? (t < 2 ? r[1] : r[2])
                                             : (i == 5) ? r[2] : (t < 3 ? r[2] : r[3]);
                                    *reinterpret_cast<uint32_t*>(op + hf * 8 * DM + i * 8) = pack_bf16(hc[4 * i + 4 + 2 * hf] * rr, hc[4 * i + 5 + 2 * hf] * rr);
                                }
                            } else {
                                #pragma unroll
                                for (int i = 0; i < 2; i++)
                                    *reinterpret_cast<uint32_t*>(op + hf * 8 * DM + 56 + i * 8) = pack_bf16(hc[4 * i + 2 * hf] * r3[hf], hc[4 * i + 1 + 2 * hf] * r3[hf]);
                            }
                        }
                    });
                }
            }
        }
        prof(40);
        if (c.tid() == 0) g_epoch[v_bid()] = v_epoch() + 1;
    }
}

typedef CUresult (*EncodeFn)(CUtensorMap*, CUtensorMapDataType, cuuint32_t, void*, const cuuint64_t*, const cuuint64_t*,
                             const cuuint32_t*, const cuuint32_t*, CUtensorMapInterleave, CUtensorMapSwizzle,
                             CUtensorMapL2promotion, CUtensorMapFloatOOBfill);

void make_map(EncodeFn enc, CUtensorMap* tm, const void* base, int rows, int cols, int box_rows, int box_cols = 64) {
    cuuint64_t gdim[2] = {(cuuint64_t)cols, (cuuint64_t)rows};
    cuuint64_t gstr[1] = {(cuuint64_t)cols * 2};
    cuuint32_t box[2] = {(cuuint32_t)box_cols, (cuuint32_t)box_rows};
    cuuint32_t estr[2] = {1, 1};
    enc(tm, CU_TENSOR_MAP_DATA_TYPE_BFLOAT16, 2, const_cast<void*>(base), gdim, gstr, box, estr, CU_TENSOR_MAP_INTERLEAVE_NONE,
        CU_TENSOR_MAP_SWIZZLE_128B, CU_TENSOR_MAP_L2_PROMOTION_L2_128B, CU_TENSOR_MAP_FLOAT_OOB_FILL_NONE);
}

}

extern "C" void kernel_launch(void* const* d_in, const int* in_sizes, int n_in, void* d_out, int out_size) {
    static EncodeFn enc = nullptr;
    static void* o_ptr = nullptr;
    if (!enc) {
        void* fn = nullptr;
        cudaDriverEntryPointQueryResult qr;
        cudaGetDriverEntryPoint("cuTensorMapEncodeTiled", &fn, cudaEnableDefault, &qr);
        enc = (EncodeFn)fn;
        cudaGetSymbolAddress(&o_ptr, g_o);
        cudaFuncSetAttribute(fused_kernel, cudaFuncAttributeMaxDynamicSharedMemorySize, SMEM_BYTES);
    }
    Params p;
    p.x = (const __nv_bfloat16*)d_in[0];
    p.wqkv = (const __nv_bfloat16*)d_in[1];
    p.wo = (const __nv_bfloat16*)d_in[2];
    p.w1 = (const __nv_bfloat16*)d_in[4];
    p.b1 = (const __nv_bfloat16*)d_in[5];
    p.w2 = (const __nv_bfloat16*)d_in[6];
    p.b2 = (const __nv_bfloat16*)d_in[7];
    p.out = (__nv_bfloat16*)d_out;
    CUtensorMap tm_x, tm_w1, tm_w2, tm_wo, tm_o, tm_qkv, tm_qkve;
    make_map(enc, &tm_qkv, p.wqkv, DM, 3 * DM, 96);
    make_map(enc, &tm_qkve, p.wqkv, DM, 3 * DM, 96, 8);
    make_map(enc, &tm_x, p.x, SEQ, DM, 128);
    make_map(enc, &tm_w1, p.w1, DM, FF, 192);
    make_map(enc, &tm_w2, p.w2, FF, DM, 192);
    make_map(enc, &tm_wo, p.wo, DM, DM, 192);
    make_map(enc, &tm_o, o_ptr, SEQ, DM, 128);
    fused_kernel<<<NMAIN + NAUX, 384, SMEM_BYTES>>>(tm_x, tm_w1, tm_w2, tm_wo, tm_o, tm_qkv, tm_qkve, p);
}
```

```cpp
#include <cuda_runtime.h>
#include <cuda.h>
#include <cuda_bf16.h>
#include <stdint.h>

#define OSTEP_AT 4
#define KNOB_A 1
#define KNOB_B 0
#define PF1_NS 1000
#define PF2_NS 2000
#define PFIDX 3
#define PF3_NS 800
#define YF32 0

namespace {
constexpr int WAIT_ITERS = 3000000;

constexpr int SEQ = 2048, DM = 576, FF = 4608;
constexpr int NMAIN = 128, NAUX = 4;

constexpr uint32_t SB    = 0x400;
constexpr uint32_t HA    = SB;
constexpr uint32_t XB    = SB + 131072;
constexpr uint32_t RING  = SB + 147456;
constexpr uint32_t SLOT  = 24576;
constexpr uint32_t MISC  = SB + 221184;
constexpr uint32_t BARS  = MISC;
constexpr uint32_t B1S   = MISC + 512;
constexpr uint32_t B2S   = MISC + 2816;
constexpr uint32_t EPO   = MISC + 3072;
constexpr uint32_t EVC   = MISC + 3104;
constexpr uint32_t SMEM_BYTES = 221184 + 3200 + 512;
constexpr uint32_t PKT   = HA + 32768;
constexpr uint32_t VT    = HA + 51200;
constexpr uint32_t PQT   = HA + 98304;
constexpr uint32_t KVB   = HA + 116736;

enum { B_FULL = 0, B_EMPTY = 3, B_XFULL = 6, B_OFULL = 9, B_O8FULL = 10, B_OFREE = 11, B_O8FREE = 12, B_KVB = 13, B_YRDY = 14, B_COUNT = 15 };
__device__ __forceinline__ constexpr uint32_t bar(int i) { return BARS + 8u * i; }

constexpr int YT_BYTES = YF32 ? 32768 : 16384;
__device__ __align__(1024) __nv_bfloat16 g_o[SEQ * DM];
__device__ __align__(1024) unsigned char g_yacc[2 * 16 * 9 * YT_BYTES];
__device__ __align__(128) float g_kv[2 * 8 * 72 * 20];
__device__ __align__(128) unsigned int g_cnt[(8 + 16 + 16 * 9) * 8];
__device__ unsigned int g_epoch[NMAIN + NAUX];
__device__ __forceinline__ unsigned int* cnt_kv(int j) { return g_cnt + j * 8; }
__device__ __forceinline__ unsigned int* cnt_o(int m) { return g_cnt + (8 + m) * 8; }
__device__ __forceinline__ unsigned int* cnt_y(int m, int c) { return g_cnt + (24 + m * 9 + c) * 8; }

__device__ __forceinline__ void mbar_init(uint32_t b, uint32_t cnt) { asm volatile("mbarrier.init.shared::cta.b64 [%0], %1;" :: "r"(b), "r"(cnt)); }
__device__ __forceinline__ void mbar_expect_tx(uint32_t b, uint32_t bytes) { asm volatile("mbarrier.arrive.expect_tx.shared::cta.b64 _, [%0], %1;" :: "r"(b), "r"(bytes) : "memory"); }
__device__ __forceinline__ void mbar_arrive(uint32_t b) { asm volatile("mbarrier.arrive.shared::cta.b64 _, [%0];" :: "r"(b) : "memory"); }
__device__ __forceinline__ void prof(int) {}
__device__ __forceinline__ void mbar_wait(uint32_t b, uint32_t parity) {
    asm volatile("{\n.reg .pred p;\n.reg .u32 c;\nmov.u32 c, 0;\n"
                 "WAIT_LOOP:\nmbarrier.try_wait.parity.shared::cta.b64 p, [%0], %1;\n@p bra WAIT_DONE;\n"
                 "add.u32 c, c, 1;\nsetp.lt.u32 p, c, 4000000;\n@p bra WAIT_LOOP;\ntrap;\nWAIT_DONE:\n}"
                 :: "r"(b), "r"(parity) : "memory");
}
__device__ __forceinline__ void smem_wait_gt(uint32_t addr, uint32_t val) {
    asm volatile("{\n.reg .pred p;\n.reg .u32 c, v;\nmov.u32 c, 0;\n"
                 "SW_LOOP:\nld.acquire.cta.shared.u32 v, [%0];\nsetp.gt.u32 p, v, %1;\n@p bra SW_DONE;\n"
                 "add.u32 c, c, 1;\nsetp.lt.u32 p, c, 100000000;\n@p bra SW_LOOP;\ntrap;\nSW_DONE:\n}"
                 :: "r"(addr), "r"(val) : "memory");
}
__device__ __forceinline__ void tma_2d(uint32_t dst, const CUtensorMap* tm, uint32_t b, int c0, int c1) {
    asm volatile("cp.async.bulk.tensor.2d.shared::cluster.global.mbarrier::complete_tx::bytes [%0], [%1, {%3, %4}], [%2];"
                 :: "r"(dst), "l"(tm), "r"(b), "r"(c0), "r"(c1) : "memory");
}
__device__ __forceinline__ void fence_async_smem() { asm volatile("fence.proxy.async.shared::cta;" ::: "memory"); }
__device__ __forceinline__ void fence_async_all() { asm volatile("fence.proxy.async;" ::: "memory"); }
__device__ __forceinline__ void named_bar(int id, int n) { asm volatile("bar.sync %0, %1;" :: "r"(id), "r"(n) : "memory"); }
__device__ __forceinline__ void wg_fence() { asm volatile("wgmma.fence.sync.aligned;" ::: "memory"); }
__device__ __forceinline__ void wg_commit() { asm volatile("wgmma.commit_group.sync.aligned;" ::: "memory"); }
template<int N> __device__ __forceinline__ void wg_wait() { asm volatile("wgmma.wait_group.sync.aligned %0;" :: "n"(N) : "memory"); }
template<int N> __device__ __forceinline__ void reg_fence(float* d) {
    #pragma unroll
    for (int i = 0; i < N; i++) asm volatile("" : "+f"(d[i]) :: "memory");
}
template<int N> __device__ __forceinline__ void reg_copy(float* d, const float* s) {
    #pragma unroll
    for (int i = 0; i < N; i++) asm volatile("mov.b32 %0, %1;" : "=f"(d[i]) : "f"(s[i]));
}
__device__ __forceinline__ uint32_t pack_bf16(float lo, float hi) { uint32_t r; asm("cvt.rn.bf16x2.f32 %0, %1, %2;" : "=r"(r) : "f"(hi), "f"(lo)); return r; }
__device__ __forceinline__ float bf_lo(uint32_t v) { return __uint_as_float(v << 16); }
__device__ __forceinline__ float bf_hi(uint32_t v) { return __uint_as_float(v & 0xffff0000u); }
__device__ __forceinline__ uint32_t sub_bf16x2(uint32_t a, uint32_t b) { uint32_t r; asm("sub.rn.bf16x2 %0, %1, %2;" : "=r"(r) : "r"(a), "r"(b)); return r; }
__device__ __forceinline__ float ex2(float x) { float r; asm("ex2.approx.ftz.f32 %0, %1;" : "=f"(r) : "f"(x)); return r; }
__device__ __forceinline__ float rcp(float x) { float r; asm("rcp.approx.ftz.f32 %0, %1;" : "=f"(r) : "f"(x)); return r; }
__device__ __forceinline__ float tanh_ap(float x) { float r; asm("tanh.approx.f32 %0, %1;" : "=f"(r) : "f"(x)); return r; }
__device__ __forceinline__ void sts32(uint32_t a, uint32_t v) { asm volatile("st.shared.b32 [%0], %1;" :: "r"(a), "r"(v)); }
__device__ __forceinline__ void sts128(uint32_t a, uint32_t x, uint32_t y, uint32_t z, uint32_t w) { asm volatile("st.shared.v4.b32 [%0], {%1,%2,%3,%4};" :: "r"(a), "r"(x), "r"(y), "r"(z), "r"(w)); }
__device__ __forceinline__ void sts64(uint32_t a, uint32_t x, uint32_t y) { asm volatile("st.shared.v2.b32 [%0], {%1,%2};" :: "r"(a), "r"(x), "r"(y)); }
__device__ __forceinline__ void lds64(uint32_t a, uint32_t* v) { asm volatile("ld.shared.v2.b32 {%0,%1}, [%2];" : "=r"(v[0]), "=r"(v[1]) : "r"(a)); }
__device__ __forceinline__ void lds128(uint32_t a, uint32_t* v) { asm volatile("ld.shared.v4.b32 {%0,%1,%2,%3}, [%4];" : "=r"(v[0]), "=r"(v[1]), "=r"(v[2]), "=r"(v[3]) : "r"(a) : "memory"); }
__device__ __forceinline__ float2 lds64f(uint32_t a) { float2 v; asm("ld.shared.v2.f32 {%0,%1}, [%2];" : "=f"(v.x), "=f"(v.y) : "r"(a)); return v; }
__device__ __forceinline__ void ldsm4(uint32_t a, uint32_t* v) {
    asm volatile("ldmatrix.sync.aligned.m8n8.x4.shared.b16 {%0,%1,%2,%3}, [%4];" : "=r"(v[0]), "=r"(v[1]), "=r"(v[2]), "=r"(v[3]) : "r"(a));
}
__device__ __forceinline__ void mma_ones(float* c, const uint32_t* a) {
    const uint32_t one2 = 0x3F803F80u;
    asm volatile("mma.sync.aligned.m16n8k16.row.col.f32.bf16.bf16.f32 {%0,%1,%2,%3}, {%4,%5,%6,%7}, {%8,%8}, {%0,%1,%2,%3};"
                 : "+f"(c[0]), "+f"(c[1]), "+f"(c[2]), "+f"(c[3]) : "r"(a[0]), "r"(a[1]), "r"(a[2]), "r"(a[3]), "r"(one2));
}
__device__ __forceinline__ unsigned int ld_acquire(const unsigned int* p) { unsigned int v; asm volatile("ld.acquire.gpu.global.u32 %0, [%1];" : "=r"(v) : "l"(p) : "memory"); return v; }
__device__ __forceinline__ void wait_cnt(const unsigned int* p, unsigned int target) {
    for (int i = 0; i < WAIT_ITERS; i++) {
        if ((int)(ld_acquire(p) - target) >= 0) return;
        __nanosleep(40);
    }
    __trap();
}
__device__ __forceinline__ uint32_t v_tid() { uint32_t r; asm volatile("mov.u32 %0, %%tid.x;" : "=r"(r)); return r; }
__device__ __forceinline__ uint32_t v_bid() { uint32_t r; asm volatile("mov.u32 %0, %%ctaid.x;" : "=r"(r)); return r; }
__device__ __forceinline__ uint32_t v_epoch() { uint32_t r; asm volatile("ld.shared.u32 %0, [%1];" : "=r"(r) : "r"(EPO)); return r; }
__device__ __forceinline__ void prefetch_l2(const void* p) { asm volatile("prefetch.global.L2 [%0];" :: "l"(p)); }

__host__ __device__ constexpr uint64_t mkdesc(uint32_t addr, uint32_t lbo, uint32_t sbo, uint32_t swz) {
    return (uint64_t)((addr & 0x3FFFF) >> 4) | ((uint64_t)((lbo >> 4) & 0x3FFF) << 16) | ((uint64_t)((sbo >> 4) & 0x3FFF) << 32) | ((uint64_t)swz << 62);
}

template<int SD> __device__ __forceinline__ void wg_rs64(float* d, const uint32_t* a, uint64_t bd) {
  if constexpr (SD) {
    asm volatile("{\n.reg .pred p;\nsetp.eq.b32 p, 0, 0;\n"
    "wgmma.mma_async.sync.aligned.m64n64k16.f32.bf16.bf16 {%0,%1,%2,%3,%4,%5,%6,%7,%8,%9,%10,%11,%12,%13,%14,%15,%16,%17,%18,%19,%20,%21,%22,%23,%24,%25,%26,%27,%28,%29,%30,%31}, {%32,%33,%34,%35}, %36, p, 1, 1, 1;\n}"
    : "+f"(d[0]),"+f"(d[1]),"+f"(d[2]),"+f"(d[3]),"+f"(d[4]),"+f"(d[5]),"+f"(d[6]),"+f"(d[7]),"+f"(d[8]),"+f"(d[9]),"+f"(d[10]),"+f"(d[11]),"+f"(d[12]),"+f"(d[13]),"+f"(d[14]),"+f"(d[15]),"+f"(d[16]),"+f"(d[17]),"+f"(d[18]),"+f"(d[19]),"+f"(d[20]),"+f"(d[21]),"+f"(d[22]),"+f"(d[23]),"+f"(d[24]),"+f"(d[25]),"+f"(d[26]),"+f"(d[27]),"+f"(d[28]),"+f"(d[29]),"+f"(d[30]),"+f"(d[31])
    : "r"(a[0]),"r"(a[1]),"r"(a[2]),"r"(a[3]), "l"(bd));
  } else {
    asm volatile("{\n.reg .pred p;\nsetp.ne.b32 p, 0, 0;\n"
    "wgmma.mma_async.sync.aligned.m64n64k16.f32.bf16.bf16 {%0,%1,%2,%3,%4,%5,%6,%7,%8,%9,%10,%11,%12,%13,%14,%15,%16,%17,%18,%19,%20,%21,%22,%23,%24,%25,%26,%27,%28,%29,%30,%31}, {%32,%33,%34,%35}, %36, p, 1, 1, 1;\n}"
    : "+f"(d[0]),"+f"(d[1]),"+f"(d[2]),"+f"(d[3]),"+f"(d[4]),"+f"(d[5]),"+f"(d[6]),"+f"(d[7]),"+f"(d[8]),"+f"(d[9]),"+f"(d[10]),"+f"(d[11]),"+f"(d[12]),"+f"(d[13]),"+f"(d[14]),"+f"(d[15]),"+f"(d[16]),"+f"(d[17]),"+f"(d[18]),"+f"(d[19]),"+f"(d[20]),"+f"(d[21]),"+f"(d[22]),"+f"(d[23]),"+f"(d[24]),"+f"(d[25]),"+f"(d[26]),"+f"(d[27]),"+f"(d[28]),"+f"(d[29]),"+f"(d[30]),"+f"(d[31])
    : "r"(a[0]),"r"(a[1]),"r"(a[2]),"r"(a[3]), "l"(bd));
  }
}
template<int SD> __device__ __forceinline__ void wg_ss64(float* d, uint64_t ad, uint64_t bd) {
  if constexpr (SD) {
    asm volatile("{\n.reg .pred p;\nsetp.eq.b32 p, 0, 0;\n"
    "wgmma.mma_async.sync.aligned.m64n64k16.f32.bf16.bf16 {%0,%1,%2,%3,%4,%5,%6,%7,%8,%9,%10,%11,%12,%13,%14,%15,%16,%17,%18,%19,%20,%21,%22,%23,%24,%25,%26,%27,%28,%29,%30,%31}, %32, %33, p, 1, 1, 0, 1;\n}"
    : "+f"(d[0]),"+f"(d[1]),"+f"(d[2]),"+f"(d[3]),"+f"(d[4]),"+f"(d[5]),"+f"(d[6]),"+f"(d[7]),"+f"(d[8]),"+f"(d[9]),"+f"(d[10]),"+f"(d[11]),"+f"(d[12]),"+f"(d[13]),"+f"(d[14]),"+f"(d[15]),"+f"(d[16]),"+f"(d[17]),"+f"(d[18]),"+f"(d[19]),"+f"(d[20]),"+f"(d[21]),"+f"(d[22]),"+f"(d[23]),"+f"(d[24]),"+f"(d[25]),"+f"(d[26]),"+f"(d[27]),"+f"(d[28]),"+f"(d[29]),"+f"(d[30]),"+f"(d[31])
    : "l"(ad), "l"(bd));
  } else {
    asm volatile("{\n.reg .pred p;\nsetp.ne.b32 p, 0, 0;\n"
    "wgmma.mma_async.sync.aligned.m64n64k16.f32.bf16.bf16 {%0,%1,%2,%3,%4,%5,%6,%7,%8,%9,%10,%11,%12,%13,%14,%15,%16,%17,%18,%19,%20,%21,%22,%23,%24,%25,%26,%27,%28,%29,%30,%31}, %32, %33, p, 1, 1, 0, 1;\n}"
    : "+f"(d[0]),"+f"(d[1]),"+f"(d[2]),"+f"(d[3]),"+f"(d[4]),"+f"(d[5]),"+f"(d[6]),"+f"(d[7]),"+f"(d[8]),"+f"(d[9]),"+f"(d[10]),"+f"(d[11]),"+f"(d[12]),"+f"(d[13]),"+f"(d[14]),"+f"(d[15]),"+f"(d[16]),"+f"(d[17]),"+f"(d[18]),"+f"(d[19]),"+f"(d[20]),"+f"(d[21]),"+f"(d[22]),"+f"(d[23]),"+f"(d[24]),"+f"(d[25]),"+f"(d[26]),"+f"(d[27]),"+f"(d[28]),"+f"(d[29]),"+f"(d[30]),"+f"(d[31])
    : "l"(ad), "l"(bd));
  }
}
template<int SD> __device__ __forceinline__ void wg_rs72(float* d, const uint32_t* a, uint64_t bd) {
  if constexpr (SD) {
    asm volatile("{\n.reg .pred p;\nsetp.eq.b32 p, 0, 0;\n"
    "wgmma.mma_async.sync.aligned.m64n72k16.f32.bf16.bf16 {%0,%1,%2,%3,%4,%5,%6,%7,%8,%9,%10,%11,%12,%13,%14,%15,%16,%17,%18,%19,%20,%21,%22,%23,%24,%25,%26,%27,%28,%29,%30,%31,%32,%33,%34,%35}, {%36,%37,%38,%39}, %40, p, 1, 1, 1;\n}"
    : "+f"(d[0]),"+f"(d[1]),"+f"(d[2]),"+f"(d[3]),"+f"(d[4]),"+f"(d[5]),"+f"(d[6]),"+f"(d[7]),"+f"(d[8]),"+f"(d[9]),"+f"(d[10]),"+f"(d[11]),"+f"(d[12]),"+f"(d[13]),"+f"(d[14]),"+f"(d[15]),"+f"(d[16]),"+f"(d[17]),"+f"(d[18]),"+f"(d[19]),"+f"(d[20]),"+f"(d[21]),"+f"(d[22]),"+f"(d[23]),"+f"(d[24]),"+f"(d[25]),"+f"(d[26]),"+f"(d[27]),"+f"(d[28]),"+f"(d[29]),"+f"(d[30]),"+f"(d[31]),"+f"(d[32]),"+f"(d[33]),"+f"(d[34]),"+f"(d[35])
    : "r"(a[0]),"r"(a[1]),"r"(a[2]),"r"(a[3]), "l"(bd));
  } else {
    asm volatile("{\n.reg .pred p;\nsetp.ne.b32 p, 0, 0;\n"
    "wgmma.mma_async.sync.aligned.m64n72k16.f32.bf16.bf16 {%0,%1,%2,%3,%4,%5,%6,%7,%8,%9,%10,%11,%12,%13,%14,%15,%16,%17,%18,%19,%20,%21,%22,%23,%24,%25,%26,%27,%28,%29,%30,%31,%32,%33,%34,%35}, {%36,%37,%38,%39}, %40, p, 1, 1, 1;\n}"
    : "+f"(d[0]),"+f"(d[1]),"+f"(d[2]),"+f"(d[3]),"+f"(d[4]),"+f"(d[5]),"+f"(d[6]),"+f"(d[7]),"+f"(d[8]),"+f"(d[9]),"+f"(d[10]),"+f"(d[11]),"+f"(d[12]),"+f"(d[13]),"+f"(d[14]),"+f"(d[15]),"+f"(d[16]),"+f"(d[17]),"+f"(d[18]),"+f"(d[19]),"+f"(d[20]),"+f"(d[21]),"+f"(d[22]),"+f"(d[23]),"+f"(d[24]),"+f"(d[25]),"+f"(d[26]),"+f"(d[27]),"+f"(d[28]),"+f"(d[29]),"+f"(d[30]),"+f"(d[31]),"+f"(d[32]),"+f"(d[33]),"+f"(d[34]),"+f"(d[35])
    : "r"(a[0]),"r"(a[1]),"r"(a[2]),"r"(a[3]), "l"(bd));
  }
}
template<int SD> __device__ __forceinline__ void wg_ss72(float* d, uint64_t ad, uint64_t bd) {
  if constexpr (SD) {
    asm volatile("{\n.reg .pred p;\nsetp.eq.b32 p, 0, 0;\n"
    "wgmma.mma_async.sync.aligned.m64n72k16.f32.bf16.bf16 {%0,%1,%2,%3,%4,%5,%6,%7,%8,%9,%10,%11,%12,%13,%14,%15,%16,%17,%18,%19,%20,%21,%22,%23,%24,%25,%26,%27,%28,%29,%30,%31,%32,%33,%34,%35}, %36, %37, p, 1, 1, 0, 1;\n}"
    : "+f"(d[0]),"+f"(d[1]),"+f"(d[2]),"+f"(d[3]),"+f"(d[4]),"+f"(d[5]),"+f"(d[6]),"+f"(d[7]),"+f"(d[8]),"+f"(d[9]),"+f"(d[10]),"+f"(d[11]),"+f"(d[12]),"+f"(d[13]),"+f"(d[14]),"+f"(d[15]),"+f"(d[16]),"+f"(d[17]),"+f"(d[18]),"+f"(d[19]),"+f"(d[20]),"+f"(d[21]),"+f"(d[22]),"+f"(d[23]),"+f"(d[24]),"+f"(d[25]),"+f"(d[26]),"+f"(d[27]),"+f"(d[28]),"+f"(d[29]),"+f"(d[30]),"+f"(d[31]),"+f"(d[32]),"+f"(d[33]),"+f"(d[34]),"+f"(d[35])
    : "l"(ad), "l"(bd));
  } else {
    asm volatile("{\n.reg .pred p;\nsetp.ne.b32 p, 0, 0;\n"
    "wgmma.mma_async.sync.aligned.m64n72k16.f32.bf16.bf16 {%0,%1,%2,%3,%4,%5,%6,%7,%8,%9,%10,%11,%12,%13,%14,%15,%16,%17,%18,%19,%20,%21,%22,%23,%24,%25,%26,%27,%28,%29,%30,%31,%32,%33,%34,%35}, %36, %37, p, 1, 1, 0, 1;\n}"
    : "+f"(d[0]),"+f"(d[1]),"+f"(d[2]),"+f"(d[3]),"+f"(d[4]),"+f"(d[5]),"+f"(d[6]),"+f"(d[7]),"+f"(d[8]),"+f"(d[9]),"+f"(d[10]),"+f"(d[11]),"+f"(d[12]),"+f"(d[13]),"+f"(d[14]),"+f"(d[15]),"+f"(d[16]),"+f"(d[17]),"+f"(d[18]),"+f"(d[19]),"+f"(d[20]),"+f"(d[21]),"+f"(d[22]),"+f"(d[23]),"+f"(d[24]),"+f"(d[25]),"+f"(d[26]),"+f"(d[27]),"+f"(d[28]),"+f"(d[29]),"+f"(d[30]),"+f"(d[31]),"+f"(d[32]),"+f"(d[33]),"+f"(d[34]),"+f"(d[35])
    : "l"(ad), "l"(bd));
  }
}
template<int SD> __device__ __forceinline__ void wg_tt64(float* d, uint64_t ad, uint64_t bd) {
  if constexpr (SD) {
    asm volatile("{\n.reg .pred p;\nsetp.eq.b32 p, 0, 0;\n"
    "wgmma.mma_async.sync.aligned.m64n64k16.f32.bf16.bf16 {%0,%1,%2,%3,%4,%5,%6,%7,%8,%9,%10,%11,%12,%13,%14,%15,%16,%17,%18,%19,%20,%21,%22,%23,%24,%25,%26,%27,%28,%29,%30,%31}, %32, %33, p, 1, 1, 1, 1;\n}"
    : "+f"(d[0]),"+f"(d[1]),"+f"(d[2]),"+f"(d[3]),"+f"(d[4]),"+f"(d[5]),"+f"(d[6]),"+f"(d[7]),"+f"(d[8]),"+f"(d[9]),"+f"(d[10]),"+f"(d[11]),"+f"(d[12]),"+f"(d[13]),"+f"(d[14]),"+f"(d[15]),"+f"(d[16]),"+f"(d[17]),"+f"(d[18]),"+f"(d[19]),"+f"(d[20]),"+f"(d[21]),"+f"(d[22]),"+f"(d[23]),"+f"(d[24]),"+f"(d[25]),"+f"(d[26]),"+f"(d[27]),"+f"(d[28]),"+f"(d[29]),"+f"(d[30]),"+f"(d[31])
    : "l"(ad), "l"(bd));
  } else {
    asm volatile("{\n.reg .pred p;\nsetp.ne.b32 p, 0, 0;\n"
    "wgmma.mma_async.sync.aligned.m64n64k16.f32.bf16.bf16 {%0,%1,%2,%3,%4,%5,%6,%7,%8,%9,%10,%11,%12,%13,%14,%15,%16,%17,%18,%19,%20,%21,%22,%23,%24,%25,%26,%27,%28,%29,%30,%31}, %32, %33, p, 1, 1, 1, 1;\n}"
    : "+f"(d[0]),"+f"(d[1]),"+f"(d[2]),"+f"(d[3]),"+f"(d[4]),"+f"(d[5]),"+f"(d[6]),"+f"(d[7]),"+f"(d[8]),"+f"(d[9]),"+f"(d[10]),"+f"(d[11]),"+f"(d[12]),"+f"(d[13]),"+f"(d[14]),"+f"(d[15]),"+f"(d[16]),"+f"(d[17]),"+f"(d[18]),"+f"(d[19]),"+f"(d[20]),"+f"(d[21]),"+f"(d[22]),"+f"(d[23]),"+f"(d[24]),"+f"(d[25]),"+f"(d[26]),"+f"(d[27]),"+f"(d[28]),"+f"(d[29]),"+f"(d[30]),"+f"(d[31])
    : "l"(ad), "l"(bd));
  }
}

template<int V> struct IC { static constexpr int v = V; };
template<int I, int N, class F> __device__ __forceinline__ void sfor(F&& f) {
    if constexpr (I < N) { f(IC<I>{}); sfor<I + 1, N>(f); }
}

enum { K_QKV = 0, K_H = 1 };

struct Ctx {
    uint32_t tph;
    uint32_t tid_;
    bool pf = false;
    __device__ __forceinline__ uint32_t tid() const { uint32_t r; asm volatile("mov.u32 %0, %1;" : "=r"(r) : "r"(tid_)); return r; }
};
__device__ __forceinline__ void release_slot(const Ctx& c, int slot) { if ((c.tid() & 31) == 0) mbar_arrive(bar(B_EMPTY + slot)); }

__device__ __forceinline__ void turn_wait(const Ctx& c) { asm volatile("bar.sync %0, 256;" :: "r"(4 + (c.tid() >> 7)) : "memory"); }
__device__ __forceinline__ void turn_pass(const Ctx& c) { asm volatile("bar.arrive %0, 256;" :: "r"(5 - (c.tid() >> 7)) : "memory"); }

template<int KIND, class PART, class POST>
__device__ __forceinline__ void run_step(Ctx& c, float* acc, const uint32_t* a, PART&& part, POST&& post, bool last = false) {
    constexpr int NST = (KIND == K_QKV) ? 6 : 3;
    constexpr int KPS = 36 / NST;
    sfor<0, NST>([&](auto ST) {
        constexpr int st = decltype(ST)::v;
        constexpr int slot = st % 3;
        mbar_wait(bar(B_FULL + slot), c.tph);
        uint32_t wgo = 0;
        if constexpr (st == NST - 1) wgo = (c.tid() >> 7) * 512;
        if (KIND == K_H && c.pf) prof(44 + st * 5);
        turn_wait(c);
        if (KIND == K_H && c.pf) prof(45 + st * 5);
        wg_fence();
        sfor<0, KPS>([&](auto KK) {
            constexpr int kk = decltype(KK)::v;
            constexpr int ks = st * KPS + kk;
            constexpr int SD = ks ? 1 : 0;
            if constexpr (KIND == K_QKV) {
                constexpr uint64_t bd = mkdesc(RING + slot * SLOT + kk * 2048, 12288, 1024, 1);
                if constexpr (ks < 32) wg_rs72<SD>(acc, a + ks * 4, bd);
                else wg_ss72<SD>(acc, mkdesc(XB + (ks - 32) * 32, 16, 1024, 1) + wgo, bd);
            } else {
                constexpr uint64_t bd = mkdesc(RING + slot * SLOT + kk * 2048, 16, 1024, 1);
                if constexpr (ks < 32) wg_rs64<SD>(acc, a + ks * 4, bd);
                else wg_ss64<SD>(acc, mkdesc(XB + (ks - 32) * 32, 16, 1024, 1) + wgo, bd);
            }
        });
        wg_commit();
        if (st < NST - 1 || !last || c.tid() < 128) turn_pass(c);
        if (KIND == K_H && c.pf) prof(46 + st * 5);
        part(ST);
        if (KIND == K_H && c.pf) prof(47 + st * 5);
        wg_wait<0>();
        if (KIND == K_H && c.pf) prof(48 + st * 5);
        release_slot(c, slot);
        if constexpr (slot == 2) c.tph ^= 1;
        post(ST);
    });
    if constexpr (KIND == K_QKV) reg_fence<36>(acc); else reg_fence<32>(acc);
}

__device__ __forceinline__ float phi(float t) {
    float e = ex2(t * 1.4426950408889634f);
    return (t > 0.f ? t + 1.0f : e) + 1e-6f;
}
__device__ __forceinline__ float gelu_h(float hx) {
    float u = hx * fmaf(hx * hx, 0.2854192650f, 1.5957691216f);
    return fmaf(hx, tanh_ap(u), hx);
}

struct Params {
    const __nv_bfloat16* x;
    const __nv_bfloat16* wqkv;
    const __nv_bfloat16* wo;
    const __nv_bfloat16* w1;
    const __nv_bfloat16* b1;
    const __nv_bfloat16* w2;
    const __nv_bfloat16* b2;
    __nv_bfloat16* out;
};

__global__ void __launch_bounds__(384, 1)
fused_kernel(const __grid_constant__ CUtensorMap tm_x, const __grid_constant__ CUtensorMap tm_w1,
             const __grid_constant__ CUtensorMap tm_w2, const __grid_constant__ CUtensorMap tm_wo,
             const __grid_constant__ CUtensorMap tm_o, const __grid_constant__ CUtensorMap tm_qkv,
             const __grid_constant__ CUtensorMap tm_qkve, const Params p) {
    extern __shared__ __align__(1024) unsigned char smem_raw[];
    const int tid = threadIdx.x;
    const int bid = blockIdx.x;
    const bool is_main = bid < NMAIN;
    const int j = bid & 7;
    const int m = bid >> 3;

    if (tid == 0) {
        if ((uint32_t)__cvta_generic_to_shared(smem_raw) != SB) __trap();
        for (int i = 0; i < 3; i++) {
            mbar_init(bar(B_FULL + i), 1); mbar_init(bar(B_EMPTY + i), 8);
            mbar_init(bar(B_XFULL + i), 1);
        }
        mbar_init(bar(B_KVB), 2);
        mbar_init(bar(B_OFULL), 1); mbar_init(bar(B_O8FULL), 1); mbar_init(bar(B_OFREE), 8); mbar_init(bar(B_O8FREE), 8);
        asm volatile("fence.mbarrier_init.release.cluster;" ::: "memory");
        if (is_main) {
            for (int g = 0; g < 3; g++) {
                mbar_expect_tx(bar(B_XFULL + g), 49152);
                for (int kb = 3 * g; kb < 3 * g + 3; kb++) tma_2d(HA + kb * 16384, &tm_x, bar(B_XFULL + g), kb * 64, m * 128);
            }
            for (int st = 0; st < 3; st++) {
                mbar_expect_tx(bar(B_FULL + st), 96 * 144);
                tma_2d(RING + st * SLOT, &tm_qkv, bar(B_FULL + st), 576 + j * 72, st * 96);
                tma_2d(RING + st * SLOT + 12288, &tm_qkve, bar(B_FULL + st), 576 + j * 72 + 64, st * 96);
            }
        }
    }
    if (tid == 32) { sts32(EPO, g_epoch[bid]); sts32(EPO + 4, 0); }
    if (tid >= 40 && tid < 48) sts32(EVC + (tid - 40) * 4, 0);
    if (tid >= 64 && tid < 64 + 288 && is_main) {
        int i = tid - 64;
        uint32_t v = *reinterpret_cast<const uint32_t*>(p.b1 + j * 576 + 2 * i);
        sts32(B1S + 8 * i, __float_as_uint(0.5f * bf_lo(v))); sts32(B1S + 8 * i + 4, __float_as_uint(0.5f * bf_hi(v)));
    }
    if (tid >= 352) {
        int i = tid - 352;
        uint32_t v = *reinterpret_cast<const uint32_t*>(p.b2 + (is_main ? j : 8) * 64 + 2 * i);
        sts32(B2S + 8 * i, v << 16); sts32(B2S + 8 * i + 4, v & 0xffff0000u);
    }
    fence_async_smem();
    __syncthreads();
    uint32_t epoch;
    asm volatile("ld.shared.u32 %0, [%1];" : "=r"(epoch) : "r"(EPO));
    const uint32_t par = epoch & 1;

    if (tid >= 256) {
        asm volatile("setmaxnreg.dec.sync.aligned.u32 24;");
        const int hw = (tid >> 5) - 8, lane = tid & 31;
        if (hw == 0) {
            if (lane == 0) {
                uint32_t n = 0;
                if (is_main) {
                    n = 1;
                    #pragma unroll 1
                    for (int u = 3; u < 18; u++) {
                        const int st = u % 3, step = u / 6;
                        const int col = ((step == 2) ? 0 : (step + 1) * 576) + j * 72, row = (u % 6) * 96;
                        mbar_wait(bar(B_EMPTY + st), (n & 1) ^ 1);
                        mbar_expect_tx(bar(B_FULL + st), 96 * 144);
                        tma_2d(RING + st * SLOT, &tm_qkv, bar(B_FULL + st), col, row);
                        tma_2d(RING + st * SLOT + 12288, &tm_qkve, bar(B_FULL + st), col + 64, row);
                        if (st == 2) n++;
                    }
                }
                const int nsteps = is_main ? 19 : 1;
                #pragma unroll 1
                for (int s = 0; s < nsteps; s++, n++) {
                    const CUtensorMap* tm; int col, row;
                    if (!is_main) { tm = &tm_wo; col = 512; row = 0; }
                    else if (s < 9) { tm = &tm_w1; col = j * 576 + s * 64; row = 0; }
                    else if (s < 18) { tm = &tm_w2; col = (s == 9) ? 512 : (((j + s - 9) & 7) * 64); row = j * 576; }
                    else { tm = &tm_wo; col = j * 64; row = 0; }
                    #pragma unroll 1
                    for (int st = 0; st < 3; st++) {
                        mbar_wait(bar(B_EMPTY + st), (n & 1) ^ 1);
                        mbar_expect_tx(bar(B_FULL + st), SLOT);
                        tma_2d(RING + st * SLOT, tm, bar(B_FULL + st), col, row + st * 192);
                    }
                }
            }
        } else {
            if (is_main) {
                const int t = tid - 288;
                #pragma unroll 1
                for (int i = t; i < 36 * 6; i += 96) {
                    int r = i / 6, q = i - r * 6;
                    prefetch_l2(reinterpret_cast<const char*>(p.wqkv) + (36 * m + r) * 3456 + (q >> 1) * 1152 + j * 144 + (q & 1) * 128);
                }
                __nanosleep(PF1_NS);
                #pragma unroll 1
                for (int i = t; i < 36 * 9; i += 96) {
                    int r = i / 9, q = i - r * 9;
                    prefetch_l2(reinterpret_cast<const char*>(p.w1) + (36 * m + r) * 9216 + j * 1152 + q * 128);
                    __nanosleep(PF3_NS);
                }
                __nanosleep(PF2_NS);
                #pragma unroll 1
                for (int i = t; i < 36 * 9; i += 96)
                    prefetch_l2(reinterpret_cast<const char*>(p.w2) + (576 * j + 36 * m) * 1152 + i * 128);
                if (t < 41 && (bid * 41 + t) < 5184) prefetch_l2(reinterpret_cast<const char*>(p.wo) + (bid * 41 + t) * 128);
                if (hw != 2) {
                    if (lane == 0) wait_cnt(cnt_kv(j), (epoch + 1) * 16);
                    __syncwarp();
                    const float4* kv = reinterpret_cast<const float4*>(g_kv + (par * 8 + j) * 1440);
                    #pragma unroll 2
                    for (int i = lane + (hw == 1 ? 0 : 32); i < 360; i += 64) {
                        const float4 v = __ldcg(kv + i);
                        const int d = i / 5, e = (i - d * 5) * 4, h = d / 18;
                        const uint32_t base = KVB + (d >> 3) * 128 + (d & 7) * 16;
                        const int n0 = 8 + h * 18 + e;
                        sts32(base + (n0 >> 3) * 1280 + (n0 & 7) * 2, pack_bf16(v.x, v.y));
                        if (e < 16) sts32(base + ((n0 + 2) >> 3) * 1280 + ((n0 + 2) & 7) * 2, pack_bf16(v.z, v.w));
                        else asm volatile("st.shared.u16 [%0], %1;" :: "r"(base + h * 2), "h"((unsigned short)pack_bf16(v.z, 0.f)) : "memory");
                    }
                    fence_async_smem();
                    __syncwarp();
                    if (lane == 0) mbar_arrive(bar(B_KVB));
                }
            }
            if (hw == 1) {
                if (lane == 0) {
                    const int nit = is_main ? 1 : 4;
                    for (int it = 0; it < nit; it++) {
                        const int mt = is_main ? m : ((bid - NMAIN) * 4 + it);
                        const bool wf = is_main || it > 0;
                        const uint32_t fp = is_main ? 0 : ((it - 1) & 1);
                        wait_cnt(cnt_o(mt), (epoch + 1) * 8);
                        fence_async_all();
                        if (wf) mbar_wait(bar(B_OFREE), fp);
                        mbar_expect_tx(bar(B_OFULL), 131072);
                        #pragma unroll 1
                        for (int kb = 0; kb < 8; kb++) tma_2d(HA + kb * 16384, &tm_o, bar(B_OFULL), kb * 64, mt * 128);
                        if (wf) mbar_wait(bar(B_O8FREE), fp);
                        mbar_expect_tx(bar(B_O8FULL), 16384);
                        tma_2d(XB, &tm_o, bar(B_O8FULL), 512, mt * 128);
                    }
                    if (is_main) { wait_cnt(cnt_y(m, j), (epoch + 1) * 7); asm volatile("st.release.cta.shared.u32 [%0], %1;" :: "r"(EPO + 4), "r"(1) : "memory"); }
                }
            } else if (hw == 2) {
                if (!is_main) {
                    if (lane == 0) {
                        #pragma unroll 1
                        for (int it = 0; it < 4; it++) {
                            wait_cnt(cnt_y((bid - NMAIN) * 4 + it, 8), (epoch + 1) * 8);
                            asm volatile("st.release.cta.shared.u32 [%0], %1;" :: "r"(EPO + 4), "r"(it + 1) : "memory");
                        }
                    }
                } else {
                    #pragma unroll 1
                    for (int e = 0; e < 10; e++) {
                        int spin = 0;
                        while (true) {
                            uint32_t v;
                            asm volatile("ld.acquire.cta.shared.u32 %0, [%1];" : "=r"(v) : "r"(EVC + (lane & 7) * 4) : "memory");
                            if (__all_sync(0xffffffffu, v > (uint32_t)e)) break;
                            if (++spin > 20000000) __trap();
                            __nanosleep(20);
                        }
                        if (lane == 0) {
                            unsigned int* cp = (e == 0) ? cnt_kv(j) : (e == 1) ? cnt_o(m) : cnt_y(m, e == 2 ? 8 : ((j + e - 2) & 7));
                            if (e == 1) fence_async_all();
                            __threadfence();
                            asm volatile("red.relaxed.gpu.global.add.u32 [%0], 1;" :: "l"(cp) : "memory");
                        }
                        __syncwarp();
                    }
                }
            } else {
                {
                    const int t0 = is_main ? (m * 9 + j) : ((bid - NMAIN) * 4 * 9 + 8);
                    const int nt = is_main ? 1 : 4;
                    for (int t = 0; t < nt; t++) {
                        uint4* z = reinterpret_cast<uint4*>(g_yacc + (size_t)((par ^ 1) * 144 + t0 + t * 9) * YT_BYTES);
                        for (int i = lane; i < YT_BYTES / 16; i += 32) z[i] = make_uint4(0, 0, 0, 0);
                    }
                    if (is_main && m == 0) {
                        float* z = g_kv + ((par ^ 1) * 8 + j) * 1440;
                        for (int i = lane; i < 1440; i += 32) z[i] = 0.f;
                    }
                }
            }
        }
    } else {
        asm volatile("setmaxnreg.inc.sync.aligned.u32 240;");
        prof(0);
        Ctx c; c.tph = 0; c.tid_ = v_tid();
        float hc[32], pv[36];
        if (tid >> 7) turn_pass(c);
        auto event = [&](uint32_t ev) {
            __syncwarp();
            if (((c.tid() & 31) == 0)) asm volatile("st.release.cta.shared.u32 [%0], %1;" :: "r"(EVC + (c.tid() >> 3)), "r"(ev) : "memory");
        };
        auto warp_arrive = [&](uint32_t b) { __syncwarp(); if (((c.tid() & 31) == 0)) mbar_arrive(b); };

        auto lrow_off = [&]() { uint32_t t_ = c.tid(); return HA + ((t_ >> 5) * 16 + (t_ & 15)) * 128 + ((((t_ >> 4) & 1) ^ (t_ & 7)) << 4); };
        auto tail_off = [&]() { uint32_t t_ = c.tid(), g = (t_ >> 2) & 7; return XB + ((t_ >> 5) * 16 + g) * 128 + (g << 4) + (t_ & 3) * 4; };
        if (is_main) {
            uint32_t a[128];
            float rs0, rs1;
            uint32_t m00, m11;
            {
                uint32_t tl[16];
                const uint32_t lrow = lrow_off();
                float cs[2][4] = {{0.f, 0.f, 0.f, 0.f}, {0.f, 0.f, 0.f, 0.f}};
                sfor<0, 36>([&](auto KS) {
                    constexpr int ks = decltype(KS)::v;
                    if constexpr (ks % 12 == 0) mbar_wait(bar(B_XFULL + ks / 12), 0);
                    uint32_t* dst = (ks < 32) ? (a + (ks & 31) * 4) : (tl + (ks & 3) * 4);
                    ldsm4((lrow ^ ((ks % 4) << 5)) + (ks / 4) * 16384, dst);
                    mma_ones(cs[ks & 1], dst);
                });
                prof(2);
                float mean0 = (cs[0][0] + cs[1][0]) * (1.0f / 576.0f), mean1 = (cs[0][2] + cs[1][2]) * (1.0f / 576.0f);
                m00 = pack_bf16(mean0, mean0); m11 = pack_bf16(mean1, mean1);
                rs0 = mean0 - bf_lo(m00); rs1 = mean1 - bf_lo(m11);
                rs0 = -144.0f * rs0 * rs0; rs1 = -144.0f * rs1 * rs1;
                const uint32_t tb = tail_off();
                #pragma unroll
                for (int i = 0; i < 16; i++) {
                    const uint32_t w = sub_bf16x2(tl[i], (i & 1) ? m11 : m00);
                    sts32((tb ^ ((i >> 1) << 4)) + (i & 1) * 1024, w);
                    float lo = bf_lo(w), hi = bf_hi(w);
                    if (i & 1) rs1 = fmaf(lo, lo, fmaf(hi, hi, rs1)); else rs0 = fmaf(lo, lo, fmaf(hi, hi, rs0));
                }
                fence_async_smem();
                #pragma unroll
                for (int i = 0; i < 128; i++) a[i] = sub_bf16x2(a[i], (i & 1) ? m11 : m00);
                named_bar(2 + (tid >> 7), 128);
            }
            prof(3);
            auto cm_off = [&]() { uint32_t t_ = c.tid(); return (t_ >> 5) * 256 + (t_ & 31) * 4; };
            {
                float qc[36];
                #pragma unroll
                for (int i = 0; i < 36; i++) { qc[i] = 0.f; pv[i] = 0.f; }
                #pragma unroll 1
                for (int s = 0; s < 3; s++) {
                    run_step<K_QKV>(c, qc, a, [&](auto ST) {
                        constexpr int st = decltype(ST)::v;
                        if (s == 0) {
                            const uint32_t lrow = lrow_off();
                            sfor<(st * 32) / 6, ((st + 1) * 32) / 6>([&](auto I) {
                                constexpr int ks = decltype(I)::v;
                                uint32_t v[4];
                                ldsm4((lrow ^ ((ks % 4) << 5)) + (ks / 4) * 16384, v);
                                #pragma unroll
                                for (int r = 0; r < 4; r++) {
                                    uint32_t w = sub_bf16x2(v[r], (r & 1) ? m11 : m00);
                                    float lo = bf_lo(w), hi = bf_hi(w);
                                    if (r & 1) rs1 = fmaf(lo, lo, fmaf(hi, hi, rs1)); else rs0 = fmaf(lo, lo, fmaf(hi, hi, rs0));
                                }
                            });
                            if constexpr (st == 5) {
                                rs0 += __shfl_xor_sync(0xffffffffu, rs0, 1); rs1 += __shfl_xor_sync(0xffffffffu, rs1, 1);
                                rs0 += __shfl_xor_sync(0xffffffffu, rs0, 2); rs1 += __shfl_xor_sync(0xffffffffu, rs1, 2);
                                rs0 = rsqrtf(fmaxf(rs0 * (1.0f / 576.0f), 0.f) + 1e-5f);
                                rs1 = rsqrtf(fmaxf(rs1 * (1.0f / 576.0f), 0.f) + 1e-5f);
                                named_bar(1, 256);
                            }
                        } else {
                            const uint32_t cm = cm_off();
                            sfor<0, 9>([&](auto B) {
                                constexpr int b = decltype(B)::v;
                                if constexpr ((b * 6) / 9 == st) {
                                    const float v0 = pv[4 * b] * rs0, v1 = pv[4 * b + 1] * rs0, v2 = pv[4 * b + 2] * rs1, v3 = pv[4 * b + 3] * rs1;
                                    if (s == 1) {
                                        sts32(PKT + b * 2048 + cm, pack_bf16(phi(v0), phi(v1)));
                                        sts32(PKT + b * 2048 + cm + 128, pack_bf16(phi(v2), phi(v3)));
                                    } else {
                                        const uint32_t w0 = pack_bf16(v0, v1), w1 = pack_bf16(v2, v3);
                                        if constexpr (b <= 4) { sts32(VT + b * 2048 + cm, w0); sts32(VT + b * 2048 + cm + 128, w1); }
                                        if constexpr (b >= 4) { sts32(VT + (b + 2) * 2048 + cm, w0); sts32(VT + (b + 2) * 2048 + cm + 128, w1); }
                                        if constexpr (b == 0) {
                                            const uint32_t one = (cm & 12) ? 0u : 0x00003F80u;
                                            sts32(VT + 5 * 2048 + cm, one); sts32(VT + 5 * 2048 + cm + 128, one);
                                        }
                                        if constexpr (b == 8) {
                                            const uint32_t z = KVB + c.tid() * 16;
                                            sts128(z, 0, 0, 0, 0); sts128(z + 4096, 0, 0, 0, 0); sts128(z + 8192, 0, 0, 0, 0);
                                            if (z < KVB + 512) sts128(z + 12288, 0, 0, 0, 0);
                                            fence_async_smem();
                                        }
                                    }
                                }
                            });
                        }
                    }, [](auto) {});
                    reg_copy<36>(pv, qc);
                    prof(4 + s);
                }
            }
            {
                #pragma unroll
                for (int i = 0; i < 32; i++) hc[i] = 0.f;
                named_bar(1, 256);
                const uint32_t wgo = ((c.tid() >> 7) * 512);
                wg_fence();
                sfor<0, 8>([&](auto KS) {
                    constexpr int ks = decltype(KS)::v;
                    wg_tt64<(ks ? 1 : 0)>(hc, mkdesc(PKT + ks * 256, 128, 2048, 0) + wgo,
                                          mkdesc(VT + ks * 256, 128, 2048, 0) + wgo + (wgo >> 2));
                });
                wg_commit();
                const uint32_t pq = PQT + cm_off() + ((c.tid() >> 7) * 512) * 16;
                sfor<0, 9>([&](auto B) {
                    constexpr int b = decltype(B)::v;
                    sts32(pq + b * 1024, pack_bf16(phi(pv[4 * b] * rs0), phi(pv[4 * b + 1] * rs0)));
                    sts32(pq + b * 1024 + 128, pack_bf16(phi(pv[4 * b + 2] * rs1), phi(pv[4 * b + 3] * rs1)));
                });
                fence_async_smem();
                wg_wait<0>();
                reg_fence<32>(hc);
                reg_copy<24>(pv, hc);
            }
            prof(7);
            rs0 *= 0.5f; rs1 *= 0.5f;
            auto gelun = [&](auto B0, auto B1, uint32_t bofs, uint32_t* w) {
                constexpr int b0 = decltype(B0)::v, nb = decltype(B1)::v - b0;
                float2 bv[nb];
                #pragma unroll
                for (int i = 0; i < nb; i++) bv[i] = lds64f(bofs + (b0 + i) * 32);
                #pragma unroll
                for (int i = 0; i < nb; i++) {
                    const int b = b0 + i;
                    w[2 * i]     = pack_bf16(gelu_h(fmaf(pv[4 * b], rs0, bv[i].x)), gelu_h(fmaf(pv[4 * b + 1], rs0, bv[i].y)));
                    w[2 * i + 1] = pack_bf16(gelu_h(fmaf(pv[4 * b + 2], rs1, bv[i].x)), gelu_h(fmaf(pv[4 * b + 3], rs1, bv[i].y)));
                }
            };
            auto spill_off = [&]() { uint32_t t_ = c.tid(); return HA + (t_ >> 7) * 8192 + (t_ & 127) * 8; };
            auto reload = [&](auto S0, auto S1) {
                const uint32_t spill = spill_off();
                sfor<decltype(S0)::v * 8, decltype(S1)::v * 8>([&](auto Q) {
                    constexpr int q = decltype(Q)::v;
                    lds64(spill + (q / 8) * 16384 + (q % 8) * 1024, a + q * 2);
                });
            };
            #pragma unroll 1
            for (int idx = 0; idx < 18; idx++) {
                run_step<K_H>(c, hc, a, [&](auto ST) {
                    constexpr int st = decltype(ST)::v;
                    if (idx >= 10) {
                        if constexpr (st < 2) {
                            const uint32_t b_ = v_bid();
                            const uint32_t chunk = (idx == 10) ? 8 : ((b_ + idx - 10) & 7);
                            unsigned char* yp = g_yacc + ((v_epoch() & 1) * 144 + (b_ >> 3) * 9 + chunk) * YT_BYTES + c.tid() * 16;
                            sfor<2 * st, 2 * st + 2>([&](auto Q) {
                                constexpr int q = decltype(Q)::v;
                                asm volatile("red.global.add.noftz.v4.bf16x2 [%0], {%1,%2,%3,%4};" :: "l"(yp + q * 4096),
                                             "r"(pack_bf16(pv[8 * q], pv[8 * q + 1])), "r"(pack_bf16(pv[8 * q + 2], pv[8 * q + 3])),
                                             "r"(pack_bf16(pv[8 * q + 4], pv[8 * q + 5])), "r"(pack_bf16(pv[8 * q + 6], pv[8 * q + 7])) : "memory");
                            });
                            if constexpr (st == 1) event(idx - 7);
                        }
                    } else if (idx >= 1) {
                        const uint32_t bofs = B1S + (idx - 1) * 256 + (c.tid() & 3) * 8;
                        if (idx < 9) {
                            if constexpr (st == 0) { if (idx == OSTEP_AT + 1) event(2); }
                            const uint32_t spill = spill_off() + (idx - 1) * 16384;
                            constexpr int b0 = st * 3, b1 = (st == 2 ? 8 : st * 3 + 3);
                            uint32_t w[6];
                            gelun(IC<b0>{}, IC<b1>{}, bofs, w);
                            #pragma unroll
                            for (int b = b0; b < b1; b++) sts64(spill + b * 1024, w[2 * (b - b0)], w[2 * (b - b0) + 1]);
                        } else {
                            if constexpr (st < 2) {
                                const uint32_t tb = tail_off();
                                uint32_t w[8];
                                gelun(IC<st * 4>{}, IC<st * 4 + 4>{}, bofs, w);
                                #pragma unroll
                                for (int i = 0; i < 4; i++) { sts32(tb ^ ((st * 4 + i) << 4), w[2 * i]); sts32((tb ^ ((st * 4 + i) << 4)) + 1024, w[2 * i + 1]); }
                            }
                            if constexpr (st == 1) { fence_async_smem(); named_bar(2 + (c.tid() >> 7), 128); }
                        }
                    } else {
                        if constexpr (st < 2) {
                            constexpr int hf = st;
                            const int t_ = c.tid(), wg = t_ >> 7, t = t_ & 3;
                            float* dst = g_kv + ((v_epoch() & 1) * 8 + (v_bid() & 7)) * 1440;
                            const int d = wg * 32 + ((t_ >> 5) & 3) * 16 + ((t_ >> 2) & 7) + hf * 8;
                            const bool dv = wg ? (d >= 36 && d < 72) : (d < 36);
                            const int e00 = wg * 24 + 2 * t - (d / 18) * 18;
                            float* dp = dst + d * 20 + e00;
                            #pragma unroll
                            for (int i = 0; i < 6; i++) {
                                const int e = e00 + i * 8;
                                const bool blk = wg ? (i >= 1) : (i <= 4);
                                if (dv && blk && e >= 0 && e < 18)
                                    asm volatile("red.global.add.v2.f32 [%0], {%1,%2};" :: "l"(dp + i * 8), "f"(pv[4 * i + 2 * hf]), "f"(pv[4 * i + 2 * hf + 1]) : "memory");
                            }
                            if (dv && t == 0) atomicAdd(dst + d * 20 + 18, wg ? pv[2 * hf] : pv[20 + 2 * hf]);
                            if constexpr (st == 1) event(1);
                        }
                    }
                }, [&](auto ST) {
                    constexpr int st = decltype(ST)::v;
                    if (idx == 8) {
                        reload(IC<3 * st>{}, IC<(st == 2 ? 8 : 3 * st + 3)>{});
                        if constexpr (st == 2) warp_arrive(bar(B_OFREE));
                    }
                });
                reg_copy<32>(pv, hc);
                prof(8 + idx);
                if (idx == OSTEP_AT) {
                    mbar_wait(bar(B_KVB), 0);
                    prof(34);
                    const uint32_t pqo = (c.tid() >> 7) * 576;
                    const int t_ = c.tid(), b_ = v_bid(), t = t_ & 3, l4 = t_ & 28;
                    __nv_bfloat16* op = g_o + (size_t)((b_ >> 3) * 128 + (t_ >> 5) * 16 + ((t_ >> 2) & 7)) * DM + (b_ & 7) * 72 + 2 * t;
                    float r3[2];
                    sfor<0, 2>([&](auto PS) {
                        constexpr int ps = decltype(PS)::v;
                        wg_fence();
                        sfor<0, 5>([&](auto KS) {
                            constexpr int ks = decltype(KS)::v;
                            wg_ss64<(ks ? 1 : 0)>(hc, mkdesc(PQT + ks * 2048, ks == 4 ? 0 : 1024, 128, 0) + pqo, mkdesc(KVB + ps * 8 * 1280 + ks * 256, 128, 1280, 0));
                        });
                        wg_commit();
                        wg_wait<0>();
                        reg_fence<32>(hc);
                        #pragma unroll
                        for (int hf = 0; hf < 2; hf++) {
                            if constexpr (ps == 0) {
                                float r[4];
                                r[0] = rcp(__shfl_sync(0xffffffffu, hc[2 * hf], l4) + 1e-6f);
                                r[1] = rcp(__shfl_sync(0xffffffffu, hc[1 + 2 * hf], l4) + 1e-6f);
                                r[2] = rcp(__shfl_sync(0xffffffffu, hc[2 * hf], l4 + 1) + 1e-6f);
                                r[3] = rcp(__shfl_sync(0xffffffffu, hc[1 + 2 * hf], l4 + 1) + 1e-6f);
                                r3[hf] = r[3];
                                #pragma unroll
                                for (int i = 0; i < 7; i++) {
                                    float rr = (i < 2) ? r[0] : (i == 2) ? (t < 1 ? r[0] : r[1]) : (i == 3) ? r[1] : (i == 4) ? (t < 2 ? r[1] : r[2])
                                             : (i == 5) ? r[2] : (t < 3 ? r[2] : r[3]);
                                    *reinterpret_cast<uint32_t*>(op + hf * 8 * DM + i * 8) = pack_bf16(hc[4 * i + 4 + 2 * hf] * rr, hc[4 * i + 5 + 2 * hf] * rr);
                                }
                            } else {
                                #pragma unroll
                                for (int i = 0; i < 2; i++)
                                    *reinterpret_cast<uint32_t*>(op + hf * 8 * DM + 56 + i * 8) = pack_bf16(hc[4 * i + 2 * hf] * r3[hf], hc[4 * i + 1 + 2 * hf] * r3[hf]);
                            }
                        }
                    });
                }
            }
        }
        if (is_main) warp_arrive(bar(B_O8FREE));
        else {
            #pragma unroll
            for (int i = 0; i < 32; i++) { asm volatile("mov.b32 %0, 0;" : "=f"(hc[i])); asm volatile("mov.b32 %0, 0;" : "=f"(pv[i])); }
        }
        const int njob = is_main ? 1 : 4;
        #pragma unroll 1
        for (int job = 0; job < njob; job++) {
            const uint32_t jpar = job & 1;
            const uint32_t b_ = v_bid();
            const int ftile = (b_ < NMAIN) ? ((b_ >> 3) * 9 + (b_ & 7)) : (((b_ - NMAIN) * 4 + job) * 9 + 8);
            uint32_t oa[128], xr[16], yv[YT_BYTES / 1024];
            auto out_off = [&]() {
                const int mt = ftile / 9, ch = ftile - mt * 9;
                const uint32_t t_ = c.tid();
                return (size_t)(mt * 128 + (t_ >> 5) * 16 + ((t_ >> 2) & 7)) * DM + ch * 64 + 2 * (t_ & 3);
            };
            {
                mbar_wait(bar(B_OFULL), jpar);
                const uint32_t lrow = lrow_off();
                sfor<0, 32>([&](auto KS) {
                    constexpr int ks = decltype(KS)::v;
                    ldsm4((lrow ^ ((ks % 4) << 5)) + (ks / 4) * 16384, oa + ks * 4);
                });
                warp_arrive(bar(B_OFREE));
                if (job) c.tph ^= 1;
            }
            c.pf = false;
            run_step<K_H>(c, hc, oa, [&](auto ST) {
                    constexpr int st = decltype(ST)::v;
                    {
                        if constexpr (st == 0) {
                            #pragma unroll
                            for (int b = 0; b < 8; b++) {
                                float2 bv = lds64f(B2S + b * 32 + (c.tid() & 3) * 8);
                                pv[4 * b] += bv.x; pv[4 * b + 1] += bv.y; pv[4 * b + 2] += bv.x; pv[4 * b + 3] += bv.y;
                            }
                        } else if constexpr (st == 1) {
                            prof(26);
                            smem_wait_gt(EPO + 4, job);
                            prof(27);
                            const unsigned char* yp = g_yacc + ((v_epoch() & 1) * 144 + ftile) * YT_BYTES + c.tid() * 16;
                            #pragma unroll
                            for (int q = 0; q < YT_BYTES / 4096; q++)
                                asm volatile("ld.global.cg.v4.u32 {%0,%1,%2,%3}, [%4];" : "=r"(yv[4 * q]), "=r"(yv[4 * q + 1]), "=r"(yv[4 * q + 2]), "=r"(yv[4 * q + 3]) : "l"(yp + q * 4096) : "memory");
                            mbar_wait(bar(B_O8FULL), jpar);
                        } else {
                            prof(28);
                            #pragma unroll
                            for (int i = 0; i < 16; i++) { pv[2 * i] += bf_lo(yv[i]); pv[2 * i + 1] += bf_hi(yv[i]); }
                            reg_fence<32>(pv);
                            const __nv_bfloat16* xp = p.x + out_off();
                            #pragma unroll
                            for (int i = 0; i < 8; i++) {
                                asm volatile("ld.global.nc.u32 %0, [%1];" : "=r"(xr[2 * i]) : "l"(xp + i * 8));
                                asm volatile("ld.global.nc.u32 %0, [%1];" : "=r"(xr[2 * i + 1]) : "l"(xp + 8 * DM + i * 8));
                            }
                            #pragma unroll
                            for (int i = 0; i < 32; i++) pv[i] = pv[i] * rcp(1.0f + ex2(pv[i] * -1.4426950408889634f));
                            prof(29);
                        }
                    }
            }, [](auto) {}, job == njob - 1);
            warp_arrive(bar(B_O8FREE));
            prof(30);
            __nv_bfloat16* op = p.out + out_off();
            #pragma unroll
            for (int b = 0; b < 8; b++) {
                *reinterpret_cast<uint32_t*>(op + b * 8) =
                    pack_bf16(fmaf(hc[4 * b], pv[4 * b], bf_lo(xr[2 * b])), fmaf(hc[4 * b + 1], pv[4 * b + 1], bf_hi(xr[2 * b])));
                *reinterpret_cast<uint32_t*>(op + 8 * DM + b * 8) =
                    pack_bf16(fmaf(hc[4 * b + 2], pv[4 * b + 2], bf_lo(xr[2 * b + 1])), fmaf(hc[4 * b + 3], pv[4 * b + 3], bf_hi(xr[2 * b + 1])));
            }
            #pragma unroll
            for (int i = 0; i < 32; i++) pv[i] = 0.f;
            if (b_ >= NMAIN) prof(8 + job);
        }
        prof(40);
        if (c.tid() == 0) g_epoch[v_bid()] = v_epoch() + 1;
    }
}

typedef CUresult (*EncodeFn)(CUtensorMap*, CUtensorMapDataType, cuuint32_t, void*, const cuuint64_t*, const cuuint64_t*,
                             const cuuint32_t*, const cuuint32_t*, CUtensorMapInterleave, CUtensorMapSwizzle,
                             CUtensorMapL2promotion, CUtensorMapFloatOOBfill);

void make_map(EncodeFn enc, CUtensorMap* tm, const void* base, int rows, int cols, int box_rows, int box_cols = 64) {
    cuuint64_t gdim[2] = {(cuuint64_t)cols, (cuuint64_t)rows};
    cuuint64_t gstr[1] = {(cuuint64_t)cols * 2};
    cuuint32_t box[2] = {(cuuint32_t)box_cols, (cuuint32_t)box_rows};
    cuuint32_t estr[2] = {1, 1};
    enc(tm, CU_TENSOR_MAP_DATA_TYPE_BFLOAT16, 2, const_cast<void*>(base), gdim, gstr, box, estr, CU_TENSOR_MAP_INTERLEAVE_NONE,
        CU_TENSOR_MAP_SWIZZLE_128B, CU_TENSOR_MAP_L2_PROMOTION_L2_128B, CU_TENSOR_MAP_FLOAT_OOB_FILL_NONE);
}

}

extern "C" void kernel_launch(void* const* d_in, const int* in_sizes, int n_in, void* d_out, int out_size) {
    static EncodeFn enc = nullptr;
    static void* o_ptr = nullptr;
    if (!enc) {
        void* fn = nullptr;
        cudaDriverEntryPointQueryResult qr;
        cudaGetDriverEntryPoint("cuTensorMapEncodeTiled", &fn, cudaEnableDefault, &qr);
        enc = (EncodeFn)fn;
        cudaGetSymbolAddress(&o_ptr, g_o);
        cudaFuncSetAttribute(fused_kernel, cudaFuncAttributeMaxDynamicSharedMemorySize, SMEM_BYTES);
    }
    Params p;
    p.x = (const __nv_bfloat16*)d_in[0];
    p.wqkv = (const __nv_bfloat16*)d_in[1];
    p.wo = (const __nv_bfloat16*)d_in[2];
    p.w1 = (const __nv_bfloat16*)d_in[4];
    p.b1 = (const __nv_bfloat16*)d_in[5];
    p.w2 = (const __nv_bfloat16*)d_in[6];
    p.b2 = (const __nv_bfloat16*)d_in[7];
    p.out = (__nv_bfloat16*)d_out;
    CUtensorMap tm_x, tm_w1, tm_w2, tm_wo, tm_o, tm_qkv, tm_qkve;
    make_map(enc, &tm_qkv, p.wqkv, DM, 3 * DM, 96);
    make_map(enc, &tm_qkve, p.wqkv, DM, 3 * DM, 96, 8);
    make_map(enc, &tm_x, p.x, SEQ, DM, 128);
    make_map(enc, &tm_w1, p.w1, DM, FF, 192);
    make_map(enc, &tm_w2, p.w2, FF, DM, 192);
    make_map(enc, &tm_wo, p.wo, DM, DM, 192);
    make_map(enc, &tm_o, o_ptr, SEQ, DM, 128);
    fused_kernel<<<NMAIN + NAUX, 384, SMEM_BYTES>>>(tm_x, tm_w1, tm_w2, tm_wo, tm_o, tm_qkv, tm_qkve, p);
}
```

```cpp
#include <cuda_runtime.h>
#include <cuda.h>
#include <cuda_bf16.h>
#include <stdint.h>

#define OSTEP_AT 4
#define KNOB_A 1
#define KNOB_B 0
#define PF1_NS 1000
#define PF2_NS 2000
#define PFIDX 3
#define PF3_NS 800
#define YF32 0

namespace {
constexpr int WAIT_ITERS = 3000000;

constexpr int SEQ = 2048, DM = 576, FF = 4608;
constexpr int NMAIN = 128, NAUX = 4;

constexpr uint32_t SB    = 0x400;
constexpr uint32_t HA    = SB;
constexpr uint32_t XB    = SB + 131072;
constexpr uint32_t RING  = SB + 147456;
constexpr uint32_t SLOT  = 24576;
constexpr uint32_t MISC  = SB + 221184;
constexpr uint32_t BARS  = MISC;
constexpr uint32_t B1S   = MISC + 512;
constexpr uint32_t B2S   = MISC + 2816;
constexpr uint32_t EPO   = MISC + 3072;
constexpr uint32_t EVC   = MISC + 3104;
constexpr uint32_t SMEM_BYTES = 221184 + 3200 + 512;
constexpr uint32_t PKT   = HA + 32768;
constexpr uint32_t VT    = HA + 51200;
constexpr uint32_t PQT   = HA + 98304;
constexpr uint32_t KVB   = HA + 116736;

enum { B_FULL = 0, B_EMPTY = 3, B_XFULL = 6, B_OFULL = 9, B_O8FULL = 10, B_OFREE = 11, B_O8FREE = 12, B_KVB = 13, B_YRDY = 14, B_COUNT = 15 };
__device__ __forceinline__ constexpr uint32_t bar(int i) { return BARS + 8u * i; }

constexpr int YT_BYTES = YF32 ? 32768 : 16384;
__device__ __align__(1024) __nv_bfloat16 g_o[SEQ * DM];
__device__ __align__(1024) unsigned char g_yacc[2 * 16 * 9 * YT_BYTES];
__device__ __align__(128) float g_kv[2 * 8 * 72 * 20];
__device__ __align__(128) unsigned int g_cnt[(8 + 16 + 16 * 9) * 8];
__device__ unsigned int g_epoch[NMAIN + NAUX];
__device__ __forceinline__ unsigned int* cnt_kv(int j) { return g_cnt + j * 8; }
__device__ __forceinline__ unsigned int* cnt_o(int m) { return g_cnt + (8 + m) * 8; }
__device__ __forceinline__ unsigned int* cnt_y(int m, int c) { return g_cnt + (24 + m * 9 + c) * 8; }

__device__ __forceinline__ void mbar_init(uint32_t b, uint32_t cnt) { asm volatile("mbarrier.init.shared::cta.b64 [%0], %1;" :: "r"(b), "r"(cnt)); }
__device__ __forceinline__ void mbar_expect_tx(uint32_t b, uint32_t bytes) { asm volatile("mbarrier.arrive.expect_tx.shared::cta.b64 _, [%0], %1;" :: "r"(b), "r"(bytes) : "memory"); }
__device__ __forceinline__ void mbar_arrive(uint32_t b) { asm volatile("mbarrier.arrive.shared::cta.b64 _, [%0];" :: "r"(b) : "memory"); }
__device__ __forceinline__ void prof(int) {}
__device__ __forceinline__ void mbar_wait(uint32_t b, uint32_t parity) {
    asm volatile("{\n.reg .pred p;\n.reg .u32 c;\nmov.u32 c, 0;\n"
                 "WAIT_LOOP:\nmbarrier.try_wait.parity.shared::cta.b64 p, [%0], %1;\n@p bra WAIT_DONE;\n"
                 "add.u32 c, c, 1;\nsetp.lt.u32 p, c, 4000000;\n@p bra WAIT_LOOP;\ntrap;\nWAIT_DONE:\n}"
                 :: "r"(b), "r"(parity) : "memory");
}
__device__ __forceinline__ void smem_wait_gt(uint32_t addr, uint32_t val) {
    asm volatile("{\n.reg .pred p;\n.reg .u32 c, v;\nmov.u32 c, 0;\n"
                 "SW_LOOP:\nld.acquire.cta.shared.u32 v, [%0];\nsetp.gt.u32 p, v, %1;\n@p bra SW_DONE;\n"
                 "add.u32 c, c, 1;\nsetp.lt.u32 p, c, 100000000;\n@p bra SW_LOOP;\ntrap;\nSW_DONE:\n}"
                 :: "r"(addr), "r"(val) : "memory");
}
__device__ __forceinline__ void tma_2d(uint32_t dst, const CUtensorMap* tm, uint32_t b, int c0, int c1) {
    asm volatile("cp.async.bulk.tensor.2d.shared::cluster.global.mbarrier::complete_tx::bytes [%0], [%1, {%3, %4}], [%2];"
                 :: "r"(dst), "l"(tm), "r"(b), "r"(c0), "r"(c1) : "memory");
}
__device__ __forceinline__ void fence_async_smem() { asm volatile("fence.proxy.async.shared::cta;" ::: "memory"); }
__device__ __forceinline__ void fence_async_all() { asm volatile("fence.proxy.async;" ::: "memory"); }
__device__ __forceinline__ void named_bar(int id, int n) { asm volatile("bar.sync %0, %1;" :: "r"(id), "r"(n) : "memory"); }
__device__ __forceinline__ void wg_fence() { asm volatile("wgmma.fence.sync.aligned;" ::: "memory"); }
__device__ __forceinline__ void wg_commit() { asm volatile("wgmma.commit_group.sync.aligned;" ::: "memory"); }
template<int N> __device__ __forceinline__ void wg_wait() { asm volatile("wgmma.wait_group.sync.aligned %0;" :: "n"(N) : "memory"); }
template<int N> __device__ __forceinline__ void reg_fence(float* d) {
    #pragma unroll
    for (int i = 0; i < N; i++) asm volatile("" : "+f"(d[i]) :: "memory");
}
template<int N> __device__ __forceinline__ void reg_copy(float* d, const float* s) {
    #pragma unroll
    for (int i = 0; i < N; i++) asm volatile("mov.b32 %0, %1;" : "=f"(d[i]) : "f"(s[i]));
}
__device__ __forceinline__ uint32_t pack_bf16(float lo, float hi) { uint32_t r; asm("cvt.rn.bf16x2.f32 %0, %1, %2;" : "=r"(r) : "f"(hi), "f"(lo)); return r; }
__device__ __forceinline__ float bf_lo(uint32_t v) { return __uint_as_float(v << 16); }
__device__ __forceinline__ float bf_hi(uint32_t v) { return __uint_as_float(v & 0xffff0000u); }
__device__ __forceinline__ uint32_t sub_bf16x2(uint32_t a, uint32_t b) { uint32_t r; asm("sub.rn.bf16x2 %0, %1, %2;" : "=r"(r) : "r"(a), "r"(b)); return r; }
__device__ __forceinline__ float ex2(float x) { float r; asm("ex2.approx.ftz.f32 %0, %1;" : "=f"(r) : "f"(x)); return r; }
__device__ __forceinline__ float rcp(float x) { float r; asm("rcp.approx.ftz.f32 %0, %1;" : "=f"(r) : "f"(x)); return r; }
__device__ __forceinline__ float tanh_ap(float x) { float r; asm("tanh.approx.f32 %0, %1;" : "=f"(r) : "f"(x)); return r; }
__device__ __forceinline__ void sts32(uint32_t a, uint32_t v) { asm volatile("st.shared.b32 [%0], %1;" :: "r"(a), "r"(v)); }
__device__ __forceinline__ void sts128(uint32_t a, uint32_t x, uint32_t y, uint32_t z, uint32_t w) { asm volatile("st.shared.v4.b32 [%0], {%1,%2,%3,%4};" :: "r"(a), "r"(x), "r"(y), "r"(z), "r"(w)); }
__device__ __forceinline__ void sts64(uint32_t a, uint32_t x, uint32_t y) { asm volatile("st.shared.v2.b32 [%0], {%1,%2};" :: "r"(a), "r"(x), "r"(y)); }
__device__ __forceinline__ void lds64(uint32_t a, uint32_t* v) { asm volatile("ld.shared.v2.b32 {%0,%1}, [%2];" : "=r"(v[0]), "=r"(v[1]) : "r"(a)); }
__device__ __forceinline__ void lds128(uint32_t a, uint32_t* v) { asm volatile("ld.shared.v4.b32 {%0,%1,%2,%3}, [%4];" : "=r"(v[0]), "=r"(v[1]), "=r"(v[2]), "=r"(v[3]) : "r"(a) : "memory"); }
__device__ __forceinline__ float2 lds64f(uint32_t a) { float2 v; asm("ld.shared.v2.f32 {%0,%1}, [%2];" : "=f"(v.x), "=f"(v.y) : "r"(a)); return v; }
__device__ __forceinline__ void ldsm4(uint32_t a, uint32_t* v) {
    asm volatile("ldmatrix.sync.aligned.m8n8.x4.shared.b16 {%0,%1,%2,%3}, [%4];" : "=r"(v[0]), "=r"(v[1]), "=r"(v[2]), "=r"(v[3]) : "r"(a));
}
__device__ __forceinline__ void mma_ones(float* c, const uint32_t* a) {
    const uint32_t one2 = 0x3F803F80u;
    asm volatile("mma.sync.aligned.m16n8k16.row.col.f32.bf16.bf16.f32 {%0,%1,%2,%3}, {%4,%5,%6,%7}, {%8,%8}, {%0,%1,%2,%3};"
                 : "+f"(c[0]), "+f"(c[1]), "+f"(c[2]), "+f"(c[3]) : "r"(a[0]), "r"(a[1]), "r"(a[2]), "r"(a[3]), "r"(one2));
}
__device__ __forceinline__ unsigned int ld_acquire(const unsigned int* p) { unsigned int v; asm volatile("ld.acquire.gpu.global.u32 %0, [%1];" : "=r"(v) : "l"(p) : "memory"); return v; }
__device__ __forceinline__ void wait_cnt(const unsigned int* p, unsigned int target) {
    for (int i = 0; i < WAIT_ITERS; i++) {
        if ((int)(ld_acquire(p) - target) >= 0) return;
        __nanosleep(40);
    }
    __trap();
}
__device__ __forceinline__ uint32_t v_tid() { uint32_t r; asm volatile("mov.u32 %0, %%tid.x;" : "=r"(r)); return r; }
__device__ __forceinline__ uint32_t v_bid() { uint32_t r; asm volatile("mov.u32 %0, %%ctaid.x;" : "=r"(r)); return r; }
__device__ __forceinline__ uint32_t v_epoch() { uint32_t r; asm volatile("ld.shared.u32 %0, [%1];" : "=r"(r) : "r"(EPO)); return r; }
__device__ __forceinline__ void prefetch_l2(const void* p) { asm volatile("prefetch.global.L2 [%0];" :: "l"(p)); }

__host__ __device__ constexpr uint64_t mkdesc(uint32_t addr, uint32_t lbo, uint32_t sbo, uint32_t swz) {
    return (uint64_t)((addr & 0x3FFFF) >> 4) | ((uint64_t)((lbo >> 4) & 0x3FFF) << 16) | ((uint64_t)((sbo >> 4) & 0x3FFF) << 32) | ((uint64_t)swz << 62);
}

template<int SD> __device__ __forceinline__ void wg_rs64(float* d, const uint32_t* a, uint64_t bd) {
  if constexpr (SD) {
    asm volatile("{\n.reg .pred p;\nsetp.eq.b32 p, 0, 0;\n"
    "wgmma.mma_async.sync.aligned.m64n64k16.f32.bf16.bf16 {%0,%1,%2,%3,%4,%5,%6,%7,%8,%9,%10,%11,%12,%13,%14,%15,%16,%17,%18,%19,%20,%21,%22,%23,%24,%25,%26,%27,%28,%29,%30,%31}, {%32,%33,%34,%35}, %36, p, 1, 1, 1;\n}"
    : "+f"(d[0]),"+f"(d[1]),"+f"(d[2]),"+f"(d[3]),"+f"(d[4]),"+f"(d[5]),"+f"(d[6]),"+f"(d[7]),"+f"(d[8]),"+f"(d[9]),"+f"(d[10]),"+f"(d[11]),"+f"(d[12]),"+f"(d[13]),"+f"(d[14]),"+f"(d[15]),"+f"(d[16]),"+f"(d[17]),"+f"(d[18]),"+f"(d[19]),"+f"(d[20]),"+f"(d[21]),"+f"(d[22]),"+f"(d[23]),"+f"(d[24]),"+f"(d[25]),"+f"(d[26]),"+f"(d[27]),"+f"(d[28]),"+f"(d[29]),"+f"(d[30]),"+f"(d[31])
    : "r"(a[0]),"r"(a[1]),"r"(a[2]),"r"(a[3]), "l"(bd));
  } else {
    asm volatile("{\n.reg .pred p;\nsetp.ne.b32 p, 0, 0;\n"
    "wgmma.mma_async.sync.aligned.m64n64k16.f32.bf16.bf16 {%0,%1,%2,%3,%4,%5,%6,%7,%8,%9,%10,%11,%12,%13,%14,%15,%16,%17,%18,%19,%20,%21,%22,%23,%24,%25,%26,%27,%28,%29,%30,%31}, {%32,%33,%34,%35}, %36, p, 1, 1, 1;\n}"
    : "+f"(d[0]),"+f"(d[1]),"+f"(d[2]),"+f"(d[3]),"+f"(d[4]),"+f"(d[5]),"+f"(d[6]),"+f"(d[7]),"+f"(d[8]),"+f"(d[9]),"+f"(d[10]),"+f"(d[11]),"+f"(d[12]),"+f"(d[13]),"+f"(d[14]),"+f"(d[15]),"+f"(d[16]),"+f"(d[17]),"+f"(d[18]),"+f"(d[19]),"+f"(d[20]),"+f"(d[21]),"+f"(d[22]),"+f"(d[23]),"+f"(d[24]),"+f"(d[25]),"+f"(d[26]),"+f"(d[27]),"+f"(d[28]),"+f"(d[29]),"+f"(d[30]),"+f"(d[31])
    : "r"(a[0]),"r"(a[1]),"r"(a[2]),"r"(a[3]), "l"(bd));
  }
}
template<int SD> __device__ __forceinline__ void wg_ss64(float* d, uint64_t ad, uint64_t bd) {
  if constexpr (SD) {
    asm volatile("{\n.reg .pred p;\nsetp.eq.b32 p, 0, 0;\n"
    "wgmma.mma_async.sync.aligned.m64n64k16.f32.bf16.bf16 {%0,%1,%2,%3,%4,%5,%6,%7,%8,%9,%10,%11,%12,%13,%14,%15,%16,%17,%18,%19,%20,%21,%22,%23,%24,%25,%26,%27,%28,%29,%30,%31}, %32, %33, p, 1, 1, 0, 1;\n}"
    : "+f"(d[0]),"+f"(d[1]),"+f"(d[2]),"+f"(d[3]),"+f"(d[4]),"+f"(d[5]),"+f"(d[6]),"+f"(d[7]),"+f"(d[8]),"+f"(d[9]),"+f"(d[10]),"+f"(d[11]),"+f"(d[12]),"+f"(d[13]),"+f"(d[14]),"+f"(d[15]),"+f"(d[16]),"+f"(d[17]),"+f"(d[18]),"+f"(d[19]),"+f"(d[20]),"+f"(d[21]),"+f"(d[22]),"+f"(d[23]),"+f"(d[24]),"+f"(d[25]),"+f"(d[26]),"+f"(d[27]),"+f"(d[28]),"+f"(d[29]),"+f"(d[30]),"+f"(d[31])
    : "l"(ad), "l"(bd));
  } else {
    asm volatile("{\n.reg .pred p;\nsetp.ne.b32 p, 0, 0;\n"
    "wgmma.mma_async.sync.aligned.m64n64k16.f32.bf16.bf16 {%0,%1,%2,%3,%4,%5,%6,%7,%8,%9,%10,%11,%12,%13,%14,%15,%16,%17,%18,%19,%20,%21,%22,%23,%24,%25,%26,%27,%28,%29,%30,%31}, %32, %33, p, 1, 1, 0, 1;\n}"
    : "+f"(d[0]),"+f"(d[1]),"+f"(d[2]),"+f"(d[3]),"+f"(d[4]),"+f"(d[5]),"+f"(d[6]),"+f"(d[7]),"+f"(d[8]),"+f"(d[9]),"+f"(d[10]),"+f"(d[11]),"+f"(d[12]),"+f"(d[13]),"+f"(d[14]),"+f"(d[15]),"+f"(d[16]),"+f"(d[17]),"+f"(d[18]),"+f"(d[19]),"+f"(d[20]),"+f"(d[21]),"+f"(d[22]),"+f"(d[23]),"+f"(d[24]),"+f"(d[25]),"+f"(d[26]),"+f"(d[27]),"+f"(d[28]),"+f"(d[29]),"+f"(d[30]),"+f"(d[31])
    : "l"(ad), "l"(bd));
  }
}
template<int SD> __device__ __forceinline__ void wg_rs72(float* d, const uint32_t* a, uint64_t bd) {
  if constexpr (SD) {
    asm volatile("{\n.reg .pred p;\nsetp.eq.b32 p, 0, 0;\n"
    "wgmma.mma_async.sync.aligned.m64n72k16.f32.bf16.bf16 {%0,%1,%2,%3,%4,%5,%6,%7,%8,%9,%10,%11,%12,%13,%14,%15,%16,%17,%18,%19,%20,%21,%22,%23,%24,%25,%26,%27,%28,%29,%30,%31,%32,%33,%34,%35}, {%36,%37,%38,%39}, %40, p, 1, 1, 1;\n}"
    : "+f"(d[0]),"+f"(d[1]),"+f"(d[2]),"+f"(d[3]),"+f"(d[4]),"+f"(d[5]),"+f"(d[6]),"+f"(d[7]),"+f"(d[8]),"+f"(d[9]),"+f"(d[10]),"+f"(d[11]),"+f"(d[12]),"+f"(d[13]),"+f"(d[14]),"+f"(d[15]),"+f"(d[16]),"+f"(d[17]),"+f"(d[18]),"+f"(d[19]),"+f"(d[20]),"+f"(d[21]),"+f"(d[22]),"+f"(d[23]),"+f"(d[24]),"+f"(d[25]),"+f"(d[26]),"+f"(d[27]),"+f"(d[28]),"+f"(d[29]),"+f"(d[30]),"+f"(d[31]),"+f"(d[32]),"+f"(d[33]),"+f"(d[34]),"+f"(d[35])
    : "r"(a[0]),"r"(a[1]),"r"(a[2]),"r"(a[3]), "l"(bd));
  } else {
    asm volatile("{\n.reg .pred p;\nsetp.ne.b32 p, 0, 0;\n"
    "wgmma.mma_async.sync.aligned.m64n72k16.f32.bf16.bf16 {%0,%1,%2,%3,%4,%5,%6,%7,%8,%9,%10,%11,%12,%13,%14,%15,%16,%17,%18,%19,%20,%21,%22,%23,%24,%25,%26,%27,%28,%29,%30,%31,%32,%33,%34,%35}, {%36,%37,%38,%39}, %40, p, 1, 1, 1;\n}"
    : "+f"(d[0]),"+f"(d[1]),"+f"(d[2]),"+f"(d[3]),"+f"(d[4]),"+f"(d[5]),"+f"(d[6]),"+f"(d[7]),"+f"(d[8]),"+f"(d[9]),"+f"(d[10]),"+f"(d[11]),"+f"(d[12]),"+f"(d[13]),"+f"(d[14]),"+f"(d[15]),"+f"(d[16]),"+f"(d[17]),"+f"(d[18]),"+f"(d[19]),"+f"(d[20]),"+f"(d[21]),"+f"(d[22]),"+f"(d[23]),"+f"(d[24]),"+f"(d[25]),"+f"(d[26]),"+f"(d[27]),"+f"(d[28]),"+f"(d[29]),"+f"(d[30]),"+f"(d[31]),"+f"(d[32]),"+f"(d[33]),"+f"(d[34]),"+f"(d[35])
    : "r"(a[0]),"r"(a[1]),"r"(a[2]),"r"(a[3]), "l"(bd));
  }
}
template<int SD> __device__ __forceinline__ void wg_ss72(float* d, uint64_t ad, uint64_t bd) {
  if constexpr (SD) {
    asm volatile("{\n.reg .pred p;\nsetp.eq.b32 p, 0, 0;\n"
    "wgmma.mma_async.sync.aligned.m64n72k16.f32.bf16.bf16 {%0,%1,%2,%3,%4,%5,%6,%7,%8,%9,%10,%11,%12,%13,%14,%15,%16,%17,%18,%19,%20,%21,%22,%23,%24,%25,%26,%27,%28,%29,%30,%31,%32,%33,%34,%35}, %36, %37, p, 1, 1, 0, 1;\n}"
    : "+f"(d[0]),"+f"(d[1]),"+f"(d[2]),"+f"(d[3]),"+f"(d[4]),"+f"(d[5]),"+f"(d[6]),"+f"(d[7]),"+f"(d[8]),"+f"(d[9]),"+f"(d[10]),"+f"(d[11]),"+f"(d[12]),"+f"(d[13]),"+f"(d[14]),"+f"(d[15]),"+f"(d[16]),"+f"(d[17]),"+f"(d[18]),"+f"(d[19]),"+f"(d[20]),"+f"(d[21]),"+f"(d[22]),"+f"(d[23]),"+f"(d[24]),"+f"(d[25]),"+f"(d[26]),"+f"(d[27]),"+f"(d[28]),"+f"(d[29]),"+f"(d[30]),"+f"(d[31]),"+f"(d[32]),"+f"(d[33]),"+f"(d[34]),"+f"(d[35])
    : "l"(ad), "l"(bd));
  } else {
    asm volatile("{\n.reg .pred p;\nsetp.ne.b32 p, 0, 0;\n"
    "wgmma.mma_async.sync.aligned.m64n72k16.f32.bf16.bf16 {%0,%1,%2,%3,%4,%5,%6,%7,%8,%9,%10,%11,%12,%13,%14,%15,%16,%17,%18,%19,%20,%21,%22,%23,%24,%25,%26,%27,%28,%29,%30,%31,%32,%33,%34,%35}, %36, %37, p, 1, 1, 0, 1;\n}"
    : "+f"(d[0]),"+f"(d[1]),"+f"(d[2]),"+f"(d[3]),"+f"(d[4]),"+f"(d[5]),"+f"(d[6]),"+f"(d[7]),"+f"(d[8]),"+f"(d[9]),"+f"(d[10]),"+f"(d[11]),"+f"(d[12]),"+f"(d[13]),"+f"(d[14]),"+f"(d[15]),"+f"(d[16]),"+f"(d[17]),"+f"(d[18]),"+f"(d[19]),"+f"(d[20]),"+f"(d[21]),"+f"(d[22]),"+f"(d[23]),"+f"(d[24]),"+f"(d[25]),"+f"(d[26]),"+f"(d[27]),"+f"(d[28]),"+f"(d[29]),"+f"(d[30]),"+f"(d[31]),"+f"(d[32]),"+f"(d[33]),"+f"(d[34]),"+f"(d[35])
    : "l"(ad), "l"(bd));
  }
}
template<int SD> __device__ __forceinline__ void wg_tt64(float* d, uint64_t ad, uint64_t bd) {
  if constexpr (SD) {
    asm volatile("{\n.reg .pred p;\nsetp.eq.b32 p, 0, 0;\n"
    "wgmma.mma_async.sync.aligned.m64n64k16.f32.bf16.bf16 {%0,%1,%2,%3,%4,%5,%6,%7,%8,%9,%10,%11,%12,%13,%14,%15,%16,%17,%18,%19,%20,%21,%22,%23,%24,%25,%26,%27,%28,%29,%30,%31}, %32, %33, p, 1, 1, 1, 1;\n}"
    : "+f"(d[0]),"+f"(d[1]),"+f"(d[2]),"+f"(d[3]),"+f"(d[4]),"+f"(d[5]),"+f"(d[6]),"+f"(d[7]),"+f"(d[8]),"+f"(d[9]),"+f"(d[10]),"+f"(d[11]),"+f"(d[12]),"+f"(d[13]),"+f"(d[14]),"+f"(d[15]),"+f"(d[16]),"+f"(d[17]),"+f"(d[18]),"+f"(d[19]),"+f"(d[20]),"+f"(d[21]),"+f"(d[22]),"+f"(d[23]),"+f"(d[24]),"+f"(d[25]),"+f"(d[26]),"+f"(d[27]),"+f"(d[28]),"+f"(d[29]),"+f"(d[30]),"+f"(d[31])
    : "l"(ad), "l"(bd));
  } else {
    asm volatile("{\n.reg .pred p;\nsetp.ne.b32 p, 0, 0;\n"
    "wgmma.mma_async.sync.aligned.m64n64k16.f32.bf16.bf16 {%0,%1,%2,%3,%4,%5,%6,%7,%8,%9,%10,%11,%12,%13,%14,%15,%16,%17,%18,%19,%20,%21,%22,%23,%24,%25,%26,%27,%28,%29,%30,%31}, %32, %33, p, 1, 1, 1, 1;\n}"
    : "+f"(d[0]),"+f"(d[1]),"+f"(d[2]),"+f"(d[3]),"+f"(d[4]),"+f"(d[5]),"+f"(d[6]),"+f"(d[7]),"+f"(d[8]),"+f"(d[9]),"+f"(d[10]),"+f"(d[11]),"+f"(d[12]),"+f"(d[13]),"+f"(d[14]),"+f"(d[15]),"+f"(d[16]),"+f"(d[17]),"+f"(d[18]),"+f"(d[19]),"+f"(d[20]),"+f"(d[21]),"+f"(d[22]),"+f"(d[23]),"+f"(d[24]),"+f"(d[25]),"+f"(d[26]),"+f"(d[27]),"+f"(d[28]),"+f"(d[29]),"+f"(d[30]),"+f"(d[31])
    : "l"(ad), "l"(bd));
  }
}

template<int V> struct IC { static constexpr int v = V; };
template<int I, int N, class F> __device__ __forceinline__ void sfor(F&& f) {
    if constexpr (I < N) { f(IC<I>{}); sfor<I + 1, N>(f); }
}

enum { K_QKV = 0, K_H = 1 };

struct Ctx {
    uint32_t tph;
    uint32_t tid_;
    bool pf = false;
    __device__ __forceinline__ uint32_t tid() const { uint32_t r; asm volatile("mov.u32 %0, %1;" : "=r"(r) : "r"(tid_)); return r; }
};
__device__ __forceinline__ void release_slot(const Ctx& c, int slot) { if ((c.tid() & 31) == 0) mbar_arrive(bar(B_EMPTY + slot)); }

__device__ __forceinline__ void turn_wait(const Ctx& c) { asm volatile("bar.sync %0, 256;" :: "r"(4 + (c.tid() >> 7)) : "memory"); }
__device__ __forceinline__ void turn_pass(const Ctx& c) { asm volatile("bar.arrive %0, 256;" :: "r"(5 - (c.tid() >> 7)) : "memory"); }

template<int KIND, class PART, class POST>
__device__ __forceinline__ void run_step(Ctx& c, float* acc, const uint32_t* a, PART&& part, POST&& post, bool last = false) {
    constexpr int NST = (KIND == K_QKV) ? 6 : 3;
    constexpr int KPS = 36 / NST;
    sfor<0, NST>([&](auto ST) {
        constexpr int st = decltype(ST)::v;
        constexpr int slot = st % 3;
        mbar_wait(bar(B_FULL + slot), c.tph);
        uint32_t wgo = 0;
        if constexpr (st == NST - 1) wgo = (c.tid() >> 7) * 512;
        if (KIND == K_H && c.pf) prof(44 + st * 5);
        turn_wait(c);
        if (KIND == K_H && c.pf) prof(45 + st * 5);
        wg_fence();
        sfor<0, KPS>([&](auto KK) {
            constexpr int kk = decltype(KK)::v;
            constexpr int ks = st * KPS + kk;
            constexpr int SD = ks ? 1 : 0;
            if constexpr (KIND == K_QKV) {
                constexpr uint64_t bd = mkdesc(RING + slot * SLOT + kk * 2048, 12288, 1024, 1);
                if constexpr (ks < 32) wg_rs72<SD>(acc, a + ks * 4, bd);
                else wg_ss72<SD>(acc, mkdesc(XB + (ks - 32) * 32, 16, 1024, 1) + wgo, bd);
            } else {
                constexpr uint64_t bd = mkdesc(RING + slot * SLOT + kk * 2048, 16, 1024, 1);
                if constexpr (ks < 32) wg_rs64<SD>(acc, a + ks * 4, bd);
                else wg_ss64<SD>(acc, mkdesc(XB + (ks - 32) * 32, 16, 1024, 1) + wgo, bd);
            }
        });
        wg_commit();
        if (st < NST - 1 || !last || c.tid() < 128) turn_pass(c);
        if (KIND == K_H && c.pf) prof(46 + st * 5);
        part(ST);
        if (KIND == K_H && c.pf) prof(47 + st * 5);
        wg_wait<0>();
        if (KIND == K_H && c.pf) prof(48 + st * 5);
        release_slot(c, slot);
        if constexpr (slot == 2) c.tph ^= 1;
        post(ST);
    });
    if constexpr (KIND == K_QKV) reg_fence<36>(acc); else reg_fence<32>(acc);
}

__device__ __forceinline__ float phi(float t) {
    float e = ex2(t * 1.4426950408889634f);
    return (t > 0.f ? t + 1.0f : e) + 1e-6f;
}
__device__ __forceinline__ float gelu_h(float hx) {
    float u = hx * fmaf(hx * hx, 0.2854192650f, 1.5957691216f);
    return fmaf(hx, tanh_ap(u), hx);
}

struct Params {
    const __nv_bfloat16* x;
    const __nv_bfloat16* wqkv;
    const __nv_bfloat16* wo;
    const __nv_bfloat16* w1;
    const __nv_bfloat16* b1;
    const __nv_bfloat16* w2;
    const __nv_bfloat16* b2;
    __nv_bfloat16* out;
};

__global__ void __launch_bounds__(384, 1)
fused_kernel(const __grid_constant__ CUtensorMap tm_x, const __grid_constant__ CUtensorMap tm_w1,
             const __grid_constant__ CUtensorMap tm_w2, const __grid_constant__ CUtensorMap tm_wo,
             const __grid_constant__ CUtensorMap tm_o, const __grid_constant__ CUtensorMap tm_qkv,
             const __grid_constant__ CUtensorMap tm_qkve, const __grid_constant__ CUtensorMap tm_out, const Params p) {
    extern __shared__ __align__(1024) unsigned char smem_raw[];
    const int tid = threadIdx.x;
    const int bid = blockIdx.x;
    const bool is_main = bid < NMAIN;
    const int j = bid & 7;
    const int m = bid >> 3;

    if (tid == 0) {
        if ((uint32_t)__cvta_generic_to_shared(smem_raw) != SB) __trap();
        for (int i = 0; i < 3; i++) {
            mbar_init(bar(B_FULL + i), 1); mbar_init(bar(B_EMPTY + i), 8);
            mbar_init(bar(B_XFULL + i), 1);
        }
        mbar_init(bar(B_KVB), 2);
        mbar_init(bar(B_OFULL), 1); mbar_init(bar(B_O8FULL), 1); mbar_init(bar(B_OFREE), 8); mbar_init(bar(B_O8FREE), 8);
        asm volatile("fence.mbarrier_init.release.cluster;" ::: "memory");
        if (is_main) {
            for (int g = 0; g < 3; g++) {
                mbar_expect_tx(bar(B_XFULL + g), 49152);
                for (int kb = 3 * g; kb < 3 * g + 3; kb++) tma_2d(HA + kb * 16384, &tm_x, bar(B_XFULL + g), kb * 64, m * 128);
            }
            for (int st = 0; st < 3; st++) {
                mbar_expect_tx(bar(B_FULL + st), 96 * 144);
                tma_2d(RING + st * SLOT, &tm_qkv, bar(B_FULL + st), 576 + j * 72, st * 96);
                tma_2d(RING + st * SLOT + 12288, &tm_qkve, bar(B_FULL + st), 576 + j * 72 + 64, st * 96);
            }
        }
    }
    if (tid == 32) { sts32(EPO, g_epoch[bid]); sts32(EPO + 4, 0); }
    if (tid >= 40 && tid < 48) sts32(EVC + (tid - 40) * 4, 0);
    if (tid >= 64 && tid < 64 + 288 && is_main) {
        int i = tid - 64;
        uint32_t v = *reinterpret_cast<const uint32_t*>(p.b1 + j * 576 + 2 * i);
        sts32(B1S + 8 * i, __float_as_uint(0.5f * bf_lo(v))); sts32(B1S + 8 * i + 4, __float_as_uint(0.5f * bf_hi(v)));
    }
    if (tid >= 352) {
        int i = tid - 352;
        uint32_t v = *reinterpret_cast<const uint32_t*>(p.b2 + (is_main ? j : 8) * 64 + 2 * i);
        sts32(B2S + 8 * i, v << 16); sts32(B2S + 8 * i + 4, v & 0xffff0000u);
    }
    fence_async_smem();
    __syncthreads();
    uint32_t epoch;
    asm volatile("ld.shared.u32 %0, [%1];" : "=r"(epoch) : "r"(EPO));
    const uint32_t par = epoch & 1;

    if (tid >= 256) {
        asm volatile("setmaxnreg.dec.sync.aligned.u32 24;");
        const int hw = (tid >> 5) - 8, lane = tid & 31;
        if (hw == 0) {
            if (lane == 0) {
                uint32_t n = 0;
                if (is_main) {
                    n = 1;
                    #pragma unroll 1
                    for (int u = 3; u < 18; u++) {
                        const int st = u % 3, step = u / 6;
                        const int col = ((step == 2) ? 0 : (step + 1) * 576) + j * 72, row = (u % 6) * 96;
                        mbar_wait(bar(B_EMPTY + st), (n & 1) ^ 1);
                        mbar_expect_tx(bar(B_FULL + st), 96 * 144);
                        tma_2d(RING + st * SLOT, &tm_qkv, bar(B_FULL + st), col, row);
                        tma_2d(RING + st * SLOT + 12288, &tm_qkve, bar(B_FULL + st), col + 64, row);
                        if (st == 2) n++;
                    }
                }
                const int nsteps = is_main ? 19 : 1;
                #pragma unroll 1
                for (int s = 0; s < nsteps; s++, n++) {
                    const CUtensorMap* tm; int col, row;
                    if (!is_main) { tm = &tm_wo; col = 512; row = 0; }
                    else if (s < 9) { tm = &tm_w1; col = j * 576 + s * 64; row = 0; }
                    else if (s < 18) { tm = &tm_w2; col = (s == 9) ? 512 : (((j + s - 9) & 7) * 64); row = j * 576; }
                    else { tm = &tm_wo; col = j * 64; row = 0; }
                    #pragma unroll 1
                    for (int st = 0; st < 3; st++) {
                        mbar_wait(bar(B_EMPTY + st), (n & 1) ^ 1);
                        mbar_expect_tx(bar(B_FULL + st), SLOT);
                        tma_2d(RING + st * SLOT, tm, bar(B_FULL + st), col, row + st * 192);
                    }
                }
            }
        } else {
            if (is_main) {
                const int t = tid - 288;
                #pragma unroll 1
                for (int i = t; i < 36 * 6; i += 96) {
                    int r = i / 6, q = i - r * 6;
                    prefetch_l2(reinterpret_cast<const char*>(p.wqkv) + (36 * m + r) * 3456 + (q >> 1) * 1152 + j * 144 + (q & 1) * 128);
                }
                __nanosleep(PF1_NS);
                #pragma unroll 1
                for (int i = t; i < 36 * 9; i += 96) {
                    int r = i / 9, q = i - r * 9;
                    prefetch_l2(reinterpret_cast<const char*>(p.w1) + (36 * m + r) * 9216 + j * 1152 + q * 128);
                    __nanosleep(PF3_NS);
                }
                __nanosleep(PF2_NS);
                #pragma unroll 1
                for (int i = t; i < 36 * 9; i += 96)
                    prefetch_l2(reinterpret_cast<const char*>(p.w2) + (576 * j + 36 * m) * 1152 + i * 128);
                if (t < 41 && (bid * 41 + t) < 5184) prefetch_l2(reinterpret_cast<const char*>(p.wo) + (bid * 41 + t) * 128);
                if (hw != 2) {
                    if (lane == 0) wait_cnt(cnt_kv(j), (epoch + 1) * 16);
                    __syncwarp();
                    const float4* kv = reinterpret_cast<const float4*>(g_kv + (par * 8 + j) * 1440);
                    #pragma unroll 2
                    for (int i = lane + (hw == 1 ? 0 : 32); i < 360; i += 64) {
                        const float4 v = __ldcg(kv + i);
                        const int d = i / 5, e = (i - d * 5) * 4, h = d / 18;
                        const uint32_t base = KVB + (d >> 3) * 128 + (d & 7) * 16;
                        const int n0 = 8 + h * 18 + e;
                        sts32(base + (n0 >> 3) * 1280 + (n0 & 7) * 2, pack_bf16(v.x, v.y));
                        if (e < 16) sts32(base + ((n0 + 2) >> 3) * 1280 + ((n0 + 2) & 7) * 2, pack_bf16(v.z, v.w));
                        else asm volatile("st.shared.u16 [%0], %1;" :: "r"(base + h * 2), "h"((unsigned short)pack_bf16(v.z, 0.f)) : "memory");
                    }
                    fence_async_smem();
                    __syncwarp();
                    if (lane == 0) mbar_arrive(bar(B_KVB));
                }
            }
            if (hw == 1) {
                if (lane == 0) {
                    const int nit = is_main ? 1 : 4;
                    for (int it = 0; it < nit; it++) {
                        const int mt = is_main ? m : ((bid - NMAIN) * 4 + it);
                        const bool wf = is_main || it > 0;
                        const uint32_t fp = is_main ? 0 : ((it - 1) & 1);
                        wait_cnt(cnt_o(mt), (epoch + 1) * 8);
                        fence_async_all();
                        if (wf) mbar_wait(bar(B_OFREE), fp);
                        mbar_expect_tx(bar(B_OFULL), 131072);
                        #pragma unroll 1
                        for (int kb = 0; kb < 8; kb++) tma_2d(HA + kb * 16384, &tm_o, bar(B_OFULL), kb * 64, mt * 128);
                        if (wf) mbar_wait(bar(B_O8FREE), fp);
                        mbar_expect_tx(bar(B_O8FULL), 16384);
                        tma_2d(XB, &tm_o, bar(B_O8FULL), 512, mt * 128);
                    }
                    if (is_main) { wait_cnt(cnt_y(m, j), (epoch + 1) * 7); asm volatile("st.release.cta.shared.u32 [%0], %1;" :: "r"(EPO + 4), "r"(1) : "memory"); }
                }
            } else if (hw == 2) {
                if (!is_main) {
                    if (lane == 0) {
                        #pragma unroll 1
                        for (int it = 0; it < 4; it++) {
                            wait_cnt(cnt_y((bid - NMAIN) * 4 + it, 8), (epoch + 1) * 8);
                            asm volatile("st.release.cta.shared.u32 [%0], %1;" :: "r"(EPO + 4), "r"(it + 1) : "memory");
                        }
                    }
                } else {
                    #pragma unroll 1
                    for (int e = 0; e < 10; e++) {
                        int spin = 0;
                        while (true) {
                            uint32_t v;
                            asm volatile("ld.acquire.cta.shared.u32 %0, [%1];" : "=r"(v) : "r"(EVC + (lane & 7) * 4) : "memory");
                            if (__all_sync(0xffffffffu, v > (uint32_t)e)) break;
                            if (++spin > 20000000) __trap();
                            __nanosleep(20);
                        }
                        if (lane == 0) {
                            unsigned int* cp = (e == 0) ? cnt_kv(j) : (e == 1) ? cnt_o(m) : cnt_y(m, e == 2 ? 8 : ((j + e - 2) & 7));
                            if (e == 1) fence_async_all();
                            __threadfence();
                            asm volatile("red.relaxed.gpu.global.add.u32 [%0], 1;" :: "l"(cp) : "memory");
                        }
                        __syncwarp();
                    }
                }
            } else {
                {
                    const int t0 = is_main ? (m * 9 + j) : ((bid - NMAIN) * 4 * 9 + 8);
                    const int nt = is_main ? 1 : 4;
                    for (int t = 0; t < nt; t++) {
                        uint4* z = reinterpret_cast<uint4*>(g_yacc + (size_t)((par ^ 1) * 144 + t0 + t * 9) * YT_BYTES);
                        for (int i = lane; i < YT_BYTES / 16; i += 32) z[i] = make_uint4(0, 0, 0, 0);
                    }
                    if (is_main && m == 0) {
                        float* z = g_kv + ((par ^ 1) * 8 + j) * 1440;
                        for (int i = lane; i < 1440; i += 32) z[i] = 0.f;
                    }
                }
            }
        }
    } else {
        asm volatile("setmaxnreg.inc.sync.aligned.u32 240;");
        prof(0);
        Ctx c; c.tph = 0; c.tid_ = v_tid();
        float hc[32], pv[36];
        if (tid >> 7) turn_pass(c);
        auto event = [&](uint32_t ev) {
            __syncwarp();
            if (((c.tid() & 31) == 0)) asm volatile("st.release.cta.shared.u32 [%0], %1;" :: "r"(EVC + (c.tid() >> 3)), "r"(ev) : "memory");
        };
        auto warp_arrive = [&](uint32_t b) { __syncwarp(); if (((c.tid() & 31) == 0)) mbar_arrive(b); };

        auto lrow_off = [&]() { uint32_t t_ = c.tid(); return HA + ((t_ >> 5) * 16 + (t_ & 15)) * 128 + ((((t_ >> 4) & 1) ^ (t_ & 7)) << 4); };
        auto tail_off = [&]() { uint32_t t_ = c.tid(), g = (t_ >> 2) & 7; return XB + ((t_ >> 5) * 16 + g) * 128 + (g << 4) + (t_ & 3) * 4; };
        if (is_main) {
            uint32_t a[128];
            float rs0, rs1;
            uint32_t m00, m11;
            {
                uint32_t tl[16];
                const uint32_t lrow = lrow_off();
                float cs[2][4] = {{0.f, 0.f, 0.f, 0.f}, {0.f, 0.f, 0.f, 0.f}};
                sfor<0, 36>([&](auto KS) {
                    constexpr int ks = decltype(KS)::v;
                    if constexpr (ks % 12 == 0) mbar_wait(bar(B_XFULL + ks / 12), 0);
                    uint32_t* dst = (ks < 32) ? (a + (ks & 31) * 4) : (tl + (ks & 3) * 4);
                    ldsm4((lrow ^ ((ks % 4) << 5)) + (ks / 4) * 16384, dst);
                    mma_ones(cs[ks & 1], dst);
                });
                prof(2);
                float mean0 = (cs[0][0] + cs[1][0]) * (1.0f / 576.0f), mean1 = (cs[0][2] + cs[1][2]) * (1.0f / 576.0f);
                m00 = pack_bf16(mean0, mean0); m11 = pack_bf16(mean1, mean1);
                rs0 = mean0 - bf_lo(m00); rs1 = mean1 - bf_lo(m11);
                rs0 = -144.0f * rs0 * rs0; rs1 = -144.0f * rs1 * rs1;
                const uint32_t tb = tail_off();
                #pragma unroll
                for (int i = 0; i < 16; i++) {
                    const uint32_t w = sub_bf16x2(tl[i], (i & 1) ? m11 : m00);
                    sts32((tb ^ ((i >> 1) << 4)) + (i & 1) * 1024, w);
                    float lo = bf_lo(w), hi = bf_hi(w);
                    if (i & 1) rs1 = fmaf(lo, lo, fmaf(hi, hi, rs1)); else rs0 = fmaf(lo, lo, fmaf(hi, hi, rs0));
                }
                fence_async_smem();
                #pragma unroll
                for (int i = 0; i < 128; i++) a[i] = sub_bf16x2(a[i], (i & 1) ? m11 : m00);
                named_bar(2 + (tid >> 7), 128);
            }
            prof(3);
            auto cm_off = [&]() { uint32_t t_ = c.tid(); return (t_ >> 5) * 256 + (t_ & 31) * 4; };
            {
                float qc[36];
                #pragma unroll
                for (int i = 0; i < 36; i++) { qc[i] = 0.f; pv[i] = 0.f; }
                #pragma unroll 1
                for (int s = 0; s < 3; s++) {
                    run_step<K_QKV>(c, qc, a, [&](auto ST) {
                        constexpr int st = decltype(ST)::v;
                        if (s == 0) {
                            const uint32_t lrow = lrow_off();
                            sfor<(st * 32) / 6, ((st + 1) * 32) / 6>([&](auto I) {
                                constexpr int ks = decltype(I)::v;
                                uint32_t v[4];
                                ldsm4((lrow ^ ((ks % 4) << 5)) + (ks / 4) * 16384, v);
                                #pragma unroll
                                for (int r = 0; r < 4; r++) {
                                    uint32_t w = sub_bf16x2(v[r], (r & 1) ? m11 : m00);
                                    float lo = bf_lo(w), hi = bf_hi(w);
                                    if (r & 1) rs1 = fmaf(lo, lo, fmaf(hi, hi, rs1)); else rs0 = fmaf(lo, lo, fmaf(hi, hi, rs0));
                                }
                            });
                            if constexpr (st == 5) {
                                rs0 += __shfl_xor_sync(0xffffffffu, rs0, 1); rs1 += __shfl_xor_sync(0xffffffffu, rs1, 1);
                                rs0 += __shfl_xor_sync(0xffffffffu, rs0, 2); rs1 += __shfl_xor_sync(0xffffffffu, rs1, 2);
                                rs0 = rsqrtf(fmaxf(rs0 * (1.0f / 576.0f), 0.f) + 1e-5f);
                                rs1 = rsqrtf(fmaxf(rs1 * (1.0f / 576.0f), 0.f) + 1e-5f);
                                named_bar(1, 256);
                            }
                        } else {
                            const uint32_t cm = cm_off();
                            sfor<0, 9>([&](auto B) {
                                constexpr int b = decltype(B)::v;
                                if constexpr ((b * 6) / 9 == st) {
                                    const float v0 = pv[4 * b] * rs0, v1 = pv[4 * b + 1] * rs0, v2 = pv[4 * b + 2] * rs1, v3 = pv[4 * b + 3] * rs1;
                                    if (s == 1) {
                                        sts32(PKT + b * 2048 + cm, pack_bf16(phi(v0), phi(v1)));
                                        sts32(PKT + b * 2048 + cm + 128, pack_bf16(phi(v2), phi(v3)));
                                    } else {
                                        const uint32_t w0 = pack_bf16(v0, v1), w1 = pack_bf16(v2, v3);
                                        if constexpr (b <= 4) { sts32(VT + b * 2048 + cm, w0); sts32(VT + b * 2048 + cm + 128, w1); }
                                        if constexpr (b >= 4) { sts32(VT + (b + 2) * 2048 + cm, w0); sts32(VT + (b + 2) * 2048 + cm + 128, w1); }
                                        if constexpr (b == 0) {
                                            const uint32_t one = (cm & 12) ? 0u : 0x00003F80u;
                                            sts32(VT + 5 * 2048 + cm, one); sts32(VT + 5 * 2048 + cm + 128, one);
                                        }
                                        if constexpr (b == 8) {
                                            const uint32_t z = KVB + c.tid() * 16;
                                            sts128(z, 0, 0, 0, 0); sts128(z + 4096, 0, 0, 0, 0); sts128(z + 8192, 0, 0, 0, 0);
                                            if (z < KVB + 512) sts128(z + 12288, 0, 0, 0, 0);
                                            fence_async_smem();
                                        }
                                    }
                                }
                            });
                        }
                    }, [](auto) {});
                    reg_copy<36>(pv, qc);
                    prof(4 + s);
                }
            }
            {
                #pragma unroll
                for (int i = 0; i < 32; i++) hc[i] = 0.f;
                named_bar(1, 256);
                const uint32_t wgo = ((c.tid() >> 7) * 512);
                wg_fence();
                sfor<0, 8>([&](auto KS) {
                    constexpr int ks = decltype(KS)::v;
                    wg_tt64<(ks ? 1 : 0)>(hc, mkdesc(PKT + ks * 256, 128, 2048, 0) + wgo,
                                          mkdesc(VT + ks * 256, 128, 2048, 0) + wgo + (wgo >> 2));
                });
                wg_commit();
                const uint32_t pq = PQT + cm_off() + ((c.tid() >> 7) * 512) * 16;
                sfor<0, 9>([&](auto B) {
                    constexpr int b = decltype(B)::v;
                    sts32(pq + b * 1024, pack_bf16(phi(pv[4 * b] * rs0), phi(pv[4 * b + 1] * rs0)));
                    sts32(pq + b * 1024 + 128, pack_bf16(phi(pv[4 * b + 2] * rs1), phi(pv[4 * b + 3] * rs1)));
                });
                fence_async_smem();
                wg_wait<0>();
                reg_fence<32>(hc);
                reg_copy<24>(pv, hc);
            }
            prof(7);
            rs0 *= 0.5f; rs1 *= 0.5f;
            auto gelun = [&](auto B0, auto B1, uint32_t bofs, uint32_t* w) {
                constexpr int b0 = decltype(B0)::v, nb = decltype(B1)::v - b0;
                float2 bv[nb];
                #pragma unroll
                for (int i = 0; i < nb; i++) bv[i] = lds64f(bofs + (b0 + i) * 32);
                #pragma unroll
                for (int i = 0; i < nb; i++) {
                    const int b = b0 + i;
                    w[2 * i]     = pack_bf16(gelu_h(fmaf(pv[4 * b], rs0, bv[i].x)), gelu_h(fmaf(pv[4 * b + 1], rs0, bv[i].y)));
                    w[2 * i + 1] = pack_bf16(gelu_h(fmaf(pv[4 * b + 2], rs1, bv[i].x)), gelu_h(fmaf(pv[4 * b + 3], rs1, bv[i].y)));
                }
            };
            auto spill_off = [&]() { uint32_t t_ = c.tid(); return HA + (t_ >> 7) * 8192 + (t_ & 127) * 8; };
            auto reload = [&](auto S0, auto S1) {
                const uint32_t spill = spill_off();
                sfor<decltype(S0)::v * 8, decltype(S1)::v * 8>([&](auto Q) {
                    constexpr int q = decltype(Q)::v;
                    lds64(spill + (q / 8) * 16384 + (q % 8) * 1024, a + q * 2);
                });
            };
            #pragma unroll 1
            for (int idx = 0; idx < 18; idx++) {
                run_step<K_H>(c, hc, a, [&](auto ST) {
                    constexpr int st = decltype(ST)::v;
                    if (idx >= 10) {
                        if constexpr (st < 2) {
                            const uint32_t b_ = v_bid();
                            const uint32_t chunk = (idx == 10) ? 8 : ((b_ + idx - 10) & 7);
                            unsigned char* yp = g_yacc + ((v_epoch() & 1) * 144 + (b_ >> 3) * 9 + chunk) * YT_BYTES + c.tid() * 16;
                            sfor<2 * st, 2 * st + 2>([&](auto Q) {
                                constexpr int q = decltype(Q)::v;
                                asm volatile("red.global.add.noftz.v4.bf16x2 [%0], {%1,%2,%3,%4};" :: "l"(yp + q * 4096),
                                             "r"(pack_bf16(pv[8 * q], pv[8 * q + 1])), "r"(pack_bf16(pv[8 * q + 2], pv[8 * q + 3])),
                                             "r"(pack_bf16(pv[8 * q + 4], pv[8 * q + 5])), "r"(pack_bf16(pv[8 * q + 6], pv[8 * q + 7])) : "memory");
                            });
                            if constexpr (st == 1) event(idx - 7);
                        }
                    } else if (idx >= 1) {
                        const uint32_t bofs = B1S + (idx - 1) * 256 + (c.tid() & 3) * 8;
                        if (idx < 9) {
                            if constexpr (st == 0) { if (idx == OSTEP_AT + 1) event(2); }
                            const uint32_t spill = spill_off() + (idx - 1) * 16384;
                            constexpr int b0 = st * 3, b1 = (st == 2 ? 8 : st * 3 + 3);
                            uint32_t w[6];
                            gelun(IC<b0>{}, IC<b1>{}, bofs, w);
                            #pragma unroll
                            for (int b = b0; b < b1; b++) sts64(spill + b * 1024, w[2 * (b - b0)], w[2 * (b - b0) + 1]);
                        } else {
                            if constexpr (st < 2) {
                                const uint32_t tb = tail_off();
                                uint32_t w[8];
                                gelun(IC<st * 4>{}, IC<st * 4 + 4>{}, bofs, w);
                                #pragma unroll
                                for (int i = 0; i < 4; i++) { sts32(tb ^ ((st * 4 + i) << 4), w[2 * i]); sts32((tb ^ ((st * 4 + i) << 4)) + 1024, w[2 * i + 1]); }
                            }
                            if constexpr (st == 1) { fence_async_smem(); named_bar(2 + (c.tid() >> 7), 128); }
                        }
                    } else {
                        if constexpr (st < 2) {
                            constexpr int hf = st;
                            const int t_ = c.tid(), wg = t_ >> 7, t = t_ & 3;
                            float* dst = g_kv + ((v_epoch() & 1) * 8 + (v_bid() & 7)) * 1440;
                            const int d = wg * 32 + ((t_ >> 5) & 3) * 16 + ((t_ >> 2) & 7) + hf * 8;
                            const bool dv = wg ? (d >= 36 && d < 72) : (d < 36);
                            const int e00 = wg * 24 + 2 * t - (d / 18) * 18;
                            float* dp = dst + d * 20 + e00;
                            #pragma unroll
                            for (int i = 0; i < 6; i++) {
                                const int e = e00 + i * 8;
                                const bool blk = wg ? (i >= 1) : (i <= 4);
                                if (dv && blk && e >= 0 && e < 18)
                                    asm volatile("red.global.add.v2.f32 [%0], {%1,%2};" :: "l"(dp + i * 8), "f"(pv[4 * i + 2 * hf]), "f"(pv[4 * i + 2 * hf + 1]) : "memory");
                            }
                            if (dv && t == 0) atomicAdd(dst + d * 20 + 18, wg ? pv[2 * hf] : pv[20 + 2 * hf]);
                            if constexpr (st == 1) event(1);
                        }
                    }
                }, [&](auto ST) {
                    constexpr int st = decltype(ST)::v;
                    if (idx == 8) {
                        reload(IC<3 * st>{}, IC<(st == 2 ? 8 : 3 * st + 3)>{});
                        if constexpr (st == 2) warp_arrive(bar(B_OFREE));
                    }
                });
                reg_copy<32>(pv, hc);
                prof(8 + idx);
                if (idx == OSTEP_AT) {
                    mbar_wait(bar(B_KVB), 0);
                    prof(34);
                    const uint32_t pqo = (c.tid() >> 7) * 576;
                    const int t_ = c.tid(), b_ = v_bid(), t = t_ & 3, l4 = t_ & 28;
                    __nv_bfloat16* op = g_o + (size_t)((b_ >> 3) * 128 + (t_ >> 5) * 16 + ((t_ >> 2) & 7)) * DM + (b_ & 7) * 72 + 2 * t;
                    float r3[2];
                    sfor<0, 2>([&](auto PS) {
                        constexpr int ps = decltype(PS)::v;
                        wg_fence();
                        sfor<0, 5>([&](auto KS) {
                            constexpr int ks = decltype(KS)::v;
                            wg_ss64<(ks ? 1 : 0)>(hc, mkdesc(PQT + ks * 2048, ks == 4 ? 0 : 1024, 128, 0) + pqo, mkdesc(KVB + ps * 8 * 1280 + ks * 256, 128, 1280, 0));
                        });
                        wg_commit();
                        wg_wait<0>();
                        reg_fence<32>(hc);
                        #pragma unroll
                        for (int hf = 0; hf < 2; hf++) {
                            if constexpr (ps == 0) {
                                float r[4];
                                r[0] = rcp(__shfl_sync(0xffffffffu, hc[2 * hf], l4) + 1e-6f);
                                r[1] = rcp(__shfl_sync(0xffffffffu, hc[1 + 2 * hf], l4) + 1e-6f);
                                r[2] = rcp(__shfl_sync(0xffffffffu, hc[2 * hf], l4 + 1) + 1e-6f);
                                r[3] = rcp(__shfl_sync(0xffffffffu, hc[1 + 2 * hf], l4 + 1) + 1e-6f);
                                r3[hf] = r[3];
                                #pragma unroll
                                for (int i = 0; i < 7; i++) {
                                    float rr = (i < 2) ? r[0] : (i == 2) ? (t < 1 ? r[0] : r[1]) : (i == 3) ? r[1] : (i == 4) ? (t < 2 ? r[1] : r[2])
                                             : (i == 5) ? r[2] : (t < 3 ? r[2] : r[3]);
                                    *reinterpret_cast<uint32_t*>(op + hf * 8 * DM + i * 8) = pack_bf16(hc[4 * i + 4 + 2 * hf] * rr, hc[4 * i + 5 + 2 * hf] * rr);
                                }
                            } else {
                                #pragma unroll
                                for (int i = 0; i < 2; i++)
                                    *reinterpret_cast<uint32_t*>(op + hf * 8 * DM + 56 + i * 8) = pack_bf16(hc[4 * i + 2 * hf] * r3[hf], hc[4 * i + 1 + 2 * hf] * r3[hf]);
                            }
                        }
                    });
                }
            }
        }
        if (is_main) warp_arrive(bar(B_O8FREE));
        else {
            #pragma unroll
            for (int i = 0; i < 32; i++) { asm volatile("mov.b32 %0, 0;" : "=f"(hc[i])); asm volatile("mov.b32 %0, 0;" : "=f"(pv[i])); }
        }
        const int njob = is_main ? 1 : 4;
        #pragma unroll 1
        for (int job = 0; job < njob; job++) {
            const uint32_t jpar = job & 1;
            const uint32_t b_ = v_bid();
            const int ftile = (b_ < NMAIN) ? ((b_ >> 3) * 9 + (b_ & 7)) : (((b_ - NMAIN) * 4 + job) * 9 + 8);
            uint32_t oa[128];
            uint32_t* const xr = oa;
            uint32_t* const yv = oa + 16;
            auto out_off = [&]() {
                const int mt = ftile / 9, ch = ftile - mt * 9;
                const uint32_t t_ = c.tid();
                return (size_t)(mt * 128 + (t_ >> 5) * 16 + ((t_ >> 2) & 7)) * DM + ch * 64 + 2 * (t_ & 3);
            };
            {
                mbar_wait(bar(B_OFULL), jpar);
                const uint32_t lrow = lrow_off();
                sfor<0, 32>([&](auto KS) {
                    constexpr int ks = decltype(KS)::v;
                    ldsm4((lrow ^ ((ks % 4) << 5)) + (ks / 4) * 16384, oa + ks * 4);
                });
                warp_arrive(bar(B_OFREE));
                if (job) c.tph ^= 1;
            }
            c.pf = false;
            run_step<K_H>(c, hc, oa, [&](auto ST) {
                    constexpr int st = decltype(ST)::v;
                    {
                        if constexpr (st == 0) {
                            #pragma unroll
                            for (int b = 0; b < 8; b++) {
                                float2 bv = lds64f(B2S + b * 32 + (c.tid() & 3) * 8);
                                pv[4 * b] += bv.x; pv[4 * b + 1] += bv.y; pv[4 * b + 2] += bv.x; pv[4 * b + 3] += bv.y;
                            }
                        } else if constexpr (st == 1) {
                            const __nv_bfloat16* xp = p.x + out_off();
                            #pragma unroll
                            for (int i = 0; i < 8; i++) {
                                asm volatile("ld.global.nc.u32 %0, [%1];" : "=r"(xr[2 * i]) : "l"(xp + i * 8));
                                asm volatile("ld.global.nc.u32 %0, [%1];" : "=r"(xr[2 * i + 1]) : "l"(xp + 8 * DM + i * 8));
                            }
                            prof(26);
                            smem_wait_gt(EPO + 4, job);
                            prof(27);
                            const unsigned char* yp = g_yacc + ((v_epoch() & 1) * 144 + ftile) * YT_BYTES + c.tid() * 16;
                            #pragma unroll
                            for (int q = 0; q < YT_BYTES / 4096; q++)
                                asm volatile("ld.global.cg.v4.u32 {%0,%1,%2,%3}, [%4];" : "=r"(yv[4 * q]), "=r"(yv[4 * q + 1]), "=r"(yv[4 * q + 2]), "=r"(yv[4 * q + 3]) : "l"(yp + q * 4096) : "memory");
                            mbar_wait(bar(B_O8FULL), jpar);
                        } else {
                            prof(28);
                            #pragma unroll
                            for (int i = 0; i < 16; i++) { pv[2 * i] += bf_lo(yv[i]); pv[2 * i + 1] += bf_hi(yv[i]); }
                            #pragma unroll
                            for (int i = 0; i < 32; i++) { const float h = 0.5f * pv[i]; pv[i] = fmaf(h, tanh_ap(h), h); }
                            prof(29);
                        }
                    }
            }, [](auto) {}, job == njob - 1);
            prof(30);
            {
                named_bar(2 + (c.tid() >> 7), 128);
                const uint32_t tb = tail_off();
                #pragma unroll
                for (int b = 0; b < 8; b++) {
                    sts32(tb ^ (b << 4), pack_bf16(fmaf(hc[4 * b], pv[4 * b], bf_lo(xr[2 * b])), fmaf(hc[4 * b + 1], pv[4 * b + 1], bf_hi(xr[2 * b]))));
                    sts32((tb ^ (b << 4)) + 1024, pack_bf16(fmaf(hc[4 * b + 2], pv[4 * b + 2], bf_lo(xr[2 * b + 1])), fmaf(hc[4 * b + 3], pv[4 * b + 3], bf_hi(xr[2 * b + 1]))));
                }
                fence_async_smem();
                __syncwarp();
                const uint32_t t_ = c.tid();
                if ((t_ & 31) == 0) {
                    const int mt = ftile / 9, ch = ftile - mt * 9;
                    asm volatile("cp.async.bulk.tensor.2d.global.shared::cta.bulk_group [%0, {%2, %3}], [%1];"
                                 :: "l"(&tm_out), "r"(XB + (t_ >> 5) * 2048), "r"(ch * 64), "r"(mt * 128 + (int)(t_ >> 5) * 16) : "memory");
                    asm volatile("cp.async.bulk.commit_group;" ::: "memory");
                    asm volatile("cp.async.bulk.wait_group.read 0;" ::: "memory");
                    mbar_arrive(bar(B_O8FREE));
                }
            }
            #pragma unroll
            for (int i = 0; i < 32; i++) pv[i] = 0.f;
            if (b_ >= NMAIN) prof(8 + job);
        }
        if ((c.tid() & 31) == 0) asm volatile("cp.async.bulk.wait_group 0;" ::: "memory");
        prof(40);
        if (c.tid() == 0) g_epoch[v_bid()] = v_epoch() + 1;
    }
}

typedef CUresult (*EncodeFn)(CUtensorMap*, CUtensorMapDataType, cuuint32_t, void*, const cuuint64_t*, const cuuint64_t*,
                             const cuuint32_t*, const cuuint32_t*, CUtensorMapInterleave, CUtensorMapSwizzle,
                             CUtensorMapL2promotion, CUtensorMapFloatOOBfill);

void make_map(EncodeFn enc, CUtensorMap* tm, const void* base, int rows, int cols, int box_rows, int box_cols = 64) {
    cuuint64_t gdim[2] = {(cuuint64_t)cols, (cuuint64_t)rows};
    cuuint64_t gstr[1] = {(cuuint64_t)cols * 2};
    cuuint32_t box[2] = {(cuuint32_t)box_cols, (cuuint32_t)box_rows};
    cuuint32_t estr[2] = {1, 1};
    enc(tm, CU_TENSOR_MAP_DATA_TYPE_BFLOAT16, 2, const_cast<void*>(base), gdim, gstr, box, estr, CU_TENSOR_MAP_INTERLEAVE_NONE,
        CU_TENSOR_MAP_SWIZZLE_128B, CU_TENSOR_MAP_L2_PROMOTION_L2_128B, CU_TENSOR_MAP_FLOAT_OOB_FILL_NONE);
}

}

extern "C" void kernel_launch(void* const* d_in, const int* in_sizes, int n_in, void* d_out, int out_size) {
    static EncodeFn enc = nullptr;
    static void* o_ptr = nullptr;
    if (!enc) {
        void* fn = nullptr;
        cudaDriverEntryPointQueryResult qr;
        cudaGetDriverEntryPoint("cuTensorMapEncodeTiled", &fn, cudaEnableDefault, &qr);
        enc = (EncodeFn)fn;
        cudaGetSymbolAddress(&o_ptr, g_o);
        cudaFuncSetAttribute(fused_kernel, cudaFuncAttributeMaxDynamicSharedMemorySize, SMEM_BYTES);
    }
    Params p;
    p.x = (const __nv_bfloat16*)d_in[0];
    p.wqkv = (const __nv_bfloat16*)d_in[1];
    p.wo = (const __nv_bfloat16*)d_in[2];
    p.w1 = (const __nv_bfloat16*)d_in[4];
    p.b1 = (const __nv_bfloat16*)d_in[5];
    p.w2 = (const __nv_bfloat16*)d_in[6];
    p.b2 = (const __nv_bfloat16*)d_in[7];
    p.out = (__nv_bfloat16*)d_out;
    CUtensorMap tm_x, tm_w1, tm_w2, tm_wo, tm_o, tm_qkv, tm_qkve, tm_out;
    make_map(enc, &tm_out, p.out, SEQ, DM, 16);
    make_map(enc, &tm_qkv, p.wqkv, DM, 3 * DM, 96);
    make_map(enc, &tm_qkve, p.wqkv, DM, 3 * DM, 96, 8);
    make_map(enc, &tm_x, p.x, SEQ, DM, 128);
    make_map(enc, &tm_w1, p.w1, DM, FF, 192);
    make_map(enc, &tm_w2, p.w2, FF, DM, 192);
    make_map(enc, &tm_wo, p.wo, DM, DM, 192);
    make_map(enc, &tm_o, o_ptr, SEQ, DM, 128);
    fused_kernel<<<NMAIN + NAUX, 384, SMEM_BYTES>>>(tm_x, tm_w1, tm_w2, tm_wo, tm_o, tm_qkv, tm_qkve, tm_out, p);
}
```

```cpp
#include <cuda_runtime.h>
#include <cuda.h>
#include <cuda_bf16.h>
#include <stdint.h>

#define OSTEP_AT 4
#define KNOB_A 1
#define KNOB_B 0
#define PF1_NS 1000
#define PF2_NS 2000
#define PFIDX 3
#define PF3_NS 800
#define YF32 0

namespace {
constexpr int WAIT_ITERS = 3000000;

constexpr int SEQ = 2048, DM = 576, FF = 4608;
constexpr int NMAIN = 128, NAUX = 4;

constexpr uint32_t SB    = 0x400;
constexpr uint32_t HA    = SB;
constexpr uint32_t XB    = SB + 131072;
constexpr uint32_t RING  = SB + 147456;
constexpr uint32_t SLOT  = 24576;
constexpr uint32_t MISC  = SB + 221184;
constexpr uint32_t BARS  = MISC;
constexpr uint32_t B1S   = MISC + 512;
constexpr uint32_t B2S   = MISC + 2816;
constexpr uint32_t EPO   = MISC + 3072;
constexpr uint32_t EVC   = MISC + 3104;
constexpr uint32_t SMEM_BYTES = 221184 + 3200 + 512;
constexpr uint32_t PKT   = HA + 32768;
constexpr uint32_t VT    = HA + 51200;
constexpr uint32_t PQT   = HA + 98304;
constexpr uint32_t KVB   = HA + 116736;

enum { B_FULL = 0, B_EMPTY = 3, B_XFULL = 6, B_OFULL = 9, B_O8FULL = 10, B_OFREE = 11, B_O8FREE = 12, B_KVB = 13, B_YRDY = 14, B_COUNT = 15 };
__device__ __forceinline__ constexpr uint32_t bar(int i) { return BARS + 8u * i; }

constexpr int YT_BYTES = YF32 ? 32768 : 16384;
__device__ __align__(1024) __nv_bfloat16 g_o[SEQ * DM];
__device__ __align__(1024) unsigned char g_yacc[2 * 16 * 9 * YT_BYTES];
__device__ __align__(128) float g_kv[2 * 8 * 72 * 20];
__device__ __align__(128) unsigned int g_s8[16 * 4096];
__device__ __align__(128) unsigned int g_cnt[(8 + 16 + 16 * 9) * 8];
__device__ unsigned int g_epoch[NMAIN + NAUX];
__device__ __forceinline__ unsigned int* cnt_kv(int j) { return g_cnt + j * 8; }
__device__ __forceinline__ unsigned int* cnt_o(int m) { return g_cnt + (8 + m) * 8; }
__device__ __forceinline__ unsigned int* cnt_y(int m, int c) { return g_cnt + (24 + m * 9 + c) * 8; }

__device__ __forceinline__ void mbar_init(uint32_t b, uint32_t cnt) { asm volatile("mbarrier.init.shared::cta.b64 [%0], %1;" :: "r"(b), "r"(cnt)); }
__device__ __forceinline__ void mbar_expect_tx(uint32_t b, uint32_t bytes) { asm volatile("mbarrier.arrive.expect_tx.shared::cta.b64 _, [%0], %1;" :: "r"(b), "r"(bytes) : "memory"); }
__device__ __forceinline__ void mbar_arrive(uint32_t b) { asm volatile("mbarrier.arrive.shared::cta.b64 _, [%0];" :: "r"(b) : "memory"); }
__device__ __forceinline__ void prof(int) {}
__device__ __forceinline__ void mbar_wait(uint32_t b, uint32_t parity) {
    asm volatile("{\n.reg .pred p;\n.reg .u32 c;\nmov.u32 c, 0;\n"
                 "WAIT_LOOP:\nmbarrier.try_wait.parity.shared::cta.b64 p, [%0], %1;\n@p bra WAIT_DONE;\n"
                 "add.u32 c, c, 1;\nsetp.lt.u32 p, c, 4000000;\n@p bra WAIT_LOOP;\ntrap;\nWAIT_DONE:\n}"
                 :: "r"(b), "r"(parity) : "memory");
}
__device__ __forceinline__ void smem_wait_gt(uint32_t addr, uint32_t val) {
    asm volatile("{\n.reg .pred p;\n.reg .u32 c, v;\nmov.u32 c, 0;\n"
                 "SW_LOOP:\nld.acquire.cta.shared.u32 v, [%0];\nsetp.gt.u32 p, v, %1;\n@p bra SW_DONE;\n"
                 "add.u32 c, c, 1;\nsetp.lt.u32 p, c, 100000000;\n@p bra SW_LOOP;\ntrap;\nSW_DONE:\n}"
                 :: "r"(addr), "r"(val) : "memory");
}
__device__ __forceinline__ void tma_2d(uint32_t dst, const CUtensorMap* tm, uint32_t b, int c0, int c1) {
    asm volatile("cp.async.bulk.tensor.2d.shared::cluster.global.mbarrier::complete_tx::bytes [%0], [%1, {%3, %4}], [%2];"
                 :: "r"(dst), "l"(tm), "r"(b), "r"(c0), "r"(c1) : "memory");
}
__device__ __forceinline__ void fence_async_smem() { asm volatile("fence.proxy.async.shared::cta;" ::: "memory"); }
__device__ __forceinline__ void fence_async_all() { asm volatile("fence.proxy.async;" ::: "memory"); }
__device__ __forceinline__ void named_bar(int id, int n) { asm volatile("bar.sync %0, %1;" :: "r"(id), "r"(n) : "memory"); }
__device__ __forceinline__ void wg_fence() { asm volatile("wgmma.fence.sync.aligned;" ::: "memory"); }
__device__ __forceinline__ void wg_commit() { asm volatile("wgmma.commit_group.sync.aligned;" ::: "memory"); }
template<int N> __device__ __forceinline__ void wg_wait() { asm volatile("wgmma.wait_group.sync.aligned %0;" :: "n"(N) : "memory"); }
template<int N> __device__ __forceinline__ void reg_fence(float* d) {
    #pragma unroll
    for (int i = 0; i < N; i++) asm volatile("" : "+f"(d[i]) :: "memory");
}
template<int N> __device__ __forceinline__ void reg_copy(float* d, const float* s) {
    #pragma unroll
    for (int i = 0; i < N; i++) asm volatile("mov.b32 %0, %1;" : "=f"(d[i]) : "f"(s[i]));
}
__device__ __forceinline__ uint32_t pack_bf16(float lo, float hi) { uint32_t r; asm("cvt.rn.bf16x2.f32 %0, %1, %2;" : "=r"(r) : "f"(hi), "f"(lo)); return r; }
__device__ __forceinline__ float bf_lo(uint32_t v) { return __uint_as_float(v << 16); }
__device__ __forceinline__ float bf_hi(uint32_t v) { return __uint_as_float(v & 0xffff0000u); }
__device__ __forceinline__ uint32_t sub_bf16x2(uint32_t a, uint32_t b) { uint32_t r; asm("sub.rn.bf16x2 %0, %1, %2;" : "=r"(r) : "r"(a), "r"(b)); return r; }
__device__ __forceinline__ float ex2(float x) { float r; asm("ex2.approx.ftz.f32 %0, %1;" : "=f"(r) : "f"(x)); return r; }
__device__ __forceinline__ float rcp(float x) { float r; asm("rcp.approx.ftz.f32 %0, %1;" : "=f"(r) : "f"(x)); return r; }
__device__ __forceinline__ float tanh_ap(float x) { float r; asm("tanh.approx.f32 %0, %1;" : "=f"(r) : "f"(x)); return r; }
__device__ __forceinline__ void sts32(uint32_t a, uint32_t v) { asm volatile("st.shared.b32 [%0], %1;" :: "r"(a), "r"(v)); }
__device__ __forceinline__ void sts128(uint32_t a, uint32_t x, uint32_t y, uint32_t z, uint32_t w) { asm volatile("st.shared.v4.b32 [%0], {%1,%2,%3,%4};" :: "r"(a), "r"(x), "r"(y), "r"(z), "r"(w)); }
__device__ __forceinline__ void sts64(uint32_t a, uint32_t x, uint32_t y) { asm volatile("st.shared.v2.b32 [%0], {%1,%2};" :: "r"(a), "r"(x), "r"(y)); }
__device__ __forceinline__ void lds64(uint32_t a, uint32_t* v) { asm volatile("ld.shared.v2.b32 {%0,%1}, [%2];" : "=r"(v[0]), "=r"(v[1]) : "r"(a)); }
__device__ __forceinline__ void lds128(uint32_t a, uint32_t* v) { asm volatile("ld.shared.v4.b32 {%0,%1,%2,%3}, [%4];" : "=r"(v[0]), "=r"(v[1]), "=r"(v[2]), "=r"(v[3]) : "r"(a) : "memory"); }
__device__ __forceinline__ float2 lds64f(uint32_t a) { float2 v; asm("ld.shared.v2.f32 {%0,%1}, [%2];" : "=f"(v.x), "=f"(v.y) : "r"(a)); return v; }
__device__ __forceinline__ void ldsm4(uint32_t a, uint32_t* v) {
    asm volatile("ldmatrix.sync.aligned.m8n8.x4.shared.b16 {%0,%1,%2,%3}, [%4];" : "=r"(v[0]), "=r"(v[1]), "=r"(v[2]), "=r"(v[3]) : "r"(a));
}
__device__ __forceinline__ void mma_ones(float* c, const uint32_t* a) {
    const uint32_t one2 = 0x3F803F80u;
    asm volatile("mma.sync.aligned.m16n8k16.row.col.f32.bf16.bf16.f32 {%0,%1,%2,%3}, {%4,%5,%6,%7}, {%8,%8}, {%0,%1,%2,%3};"
                 : "+f"(c[0]), "+f"(c[1]), "+f"(c[2]), "+f"(c[3]) : "r"(a[0]), "r"(a[1]), "r"(a[2]), "r"(a[3]), "r"(one2));
}
__device__ __forceinline__ unsigned int ld_acquire(const unsigned int* p) { unsigned int v; asm volatile("ld.acquire.gpu.global.u32 %0, [%1];" : "=r"(v) : "l"(p) : "memory"); return v; }
__device__ __forceinline__ void wait_cnt(const unsigned int* p, unsigned int target) {
    for (int i = 0; i < WAIT_ITERS; i++) {
        if ((int)(ld_acquire(p) - target) >= 0) return;
        __nanosleep(40);
    }
    __trap();
}
__device__ __forceinline__ uint32_t v_tid() { uint32_t r; asm volatile("mov.u32 %0, %%tid.x;" : "=r"(r)); return r; }
__device__ __forceinline__ uint32_t v_bid() { uint32_t r; asm volatile("mov.u32 %0, %%ctaid.x;" : "=r"(r)); return r; }
__device__ __forceinline__ uint32_t v_epoch() { uint32_t r; asm volatile("ld.shared.u32 %0, [%1];" : "=r"(r) : "r"(EPO)); return r; }
__device__ __forceinline__ void prefetch_l2(const void* p) { asm volatile("prefetch.global.L2 [%0];" :: "l"(p)); }

__host__ __device__ constexpr uint64_t mkdesc(uint32_t addr, uint32_t lbo, uint32_t sbo, uint32_t swz) {
    return (uint64_t)((addr & 0x3FFFF) >> 4) | ((uint64_t)((lbo >> 4) & 0x3FFF) << 16) | ((uint64_t)((sbo >> 4) & 0x3FFF) << 32) | ((uint64_t)swz << 62);
}

template<int SD> __device__ __forceinline__ void wg_rs64(float* d, const uint32_t* a, uint64_t bd) {
  if constexpr (SD) {
    asm volatile("{\n.reg .pred p;\nsetp.eq.b32 p, 0, 0;\n"
    "wgmma.mma_async.sync.aligned.m64n64k16.f32.bf16.bf16 {%0,%1,%2,%3,%4,%5,%6,%7,%8,%9,%10,%11,%12,%13,%14,%15,%16,%17,%18,%19,%20,%21,%22,%23,%24,%25,%26,%27,%28,%29,%30,%31}, {%32,%33,%34,%35}, %36, p, 1, 1, 1;\n}"
    : "+f"(d[0]),"+f"(d[1]),"+f"(d[2]),"+f"(d[3]),"+f"(d[4]),"+f"(d[5]),"+f"(d[6]),"+f"(d[7]),"+f"(d[8]),"+f"(d[9]),"+f"(d[10]),"+f"(d[11]),"+f"(d[12]),"+f"(d[13]),"+f"(d[14]),"+f"(d[15]),"+f"(d[16]),"+f"(d[17]),"+f"(d[18]),"+f"(d[19]),"+f"(d[20]),"+f"(d[21]),"+f"(d[22]),"+f"(d[23]),"+f"(d[24]),"+f"(d[25]),"+f"(d[26]),"+f"(d[27]),"+f"(d[28]),"+f"(d[29]),"+f"(d[30]),"+f"(d[31])
    : "r"(a[0]),"r"(a[1]),"r"(a[2]),"r"(a[3]), "l"(bd));
  } else {
    asm volatile("{\n.reg .pred p;\nsetp.ne.b32 p, 0, 0;\n"
    "wgmma.mma_async.sync.aligned.m64n64k16.f32.bf16.bf16 {%0,%1,%2,%3,%4,%5,%6,%7,%8,%9,%10,%11,%12,%13,%14,%15,%16,%17,%18,%19,%20,%21,%22,%23,%24,%25,%26,%27,%28,%29,%30,%31}, {%32,%33,%34,%35}, %36, p, 1, 1, 1;\n}"
    : "+f"(d[0]),"+f"(d[1]),"+f"(d[2]),"+f"(d[3]),"+f"(d[4]),"+f"(d[5]),"+f"(d[6]),"+f"(d[7]),"+f"(d[8]),"+f"(d[9]),"+f"(d[10]),"+f"(d[11]),"+f"(d[12]),"+f"(d[13]),"+f"(d[14]),"+f"(d[15]),"+f"(d[16]),"+f"(d[17]),"+f"(d[18]),"+f"(d[19]),"+f"(d[20]),"+f"(d[21]),"+f"(d[22]),"+f"(d[23]),"+f"(d[24]),"+f"(d[25]),"+f"(d[26]),"+f"(d[27]),"+f"(d[28]),"+f"(d[29]),"+f"(d[30]),"+f"(d[31])
    : "r"(a[0]),"r"(a[1]),"r"(a[2]),"r"(a[3]), "l"(bd));
  }
}
template<int SD> __device__ __forceinline__ void wg_ss64(float* d, uint64_t ad, uint64_t bd) {
  if constexpr (SD) {
    asm volatile("{\n.reg .pred p;\nsetp.eq.b32 p, 0, 0;\n"
    "wgmma.mma_async.sync.aligned.m64n64k16.f32.bf16.bf16 {%0,%1,%2,%3,%4,%5,%6,%7,%8,%9,%10,%11,%12,%13,%14,%15,%16,%17,%18,%19,%20,%21,%22,%23,%24,%25,%26,%27,%28,%29,%30,%31}, %32, %33, p, 1, 1, 0, 1;\n}"
    : "+f"(d[0]),"+f"(d[1]),"+f"(d[2]),"+f"(d[3]),"+f"(d[4]),"+f"(d[5]),"+f"(d[6]),"+f"(d[7]),"+f"(d[8]),"+f"(d[9]),"+f"(d[10]),"+f"(d[11]),"+f"(d[12]),"+f"(d[13]),"+f"(d[14]),"+f"(d[15]),"+f"(d[16]),"+f"(d[17]),"+f"(d[18]),"+f"(d[19]),"+f"(d[20]),"+f"(d[21]),"+f"(d[22]),"+f"(d[23]),"+f"(d[24]),"+f"(d[25]),"+f"(d[26]),"+f"(d[27]),"+f"(d[28]),"+f"(d[29]),"+f"(d[30]),"+f"(d[31])
    : "l"(ad), "l"(bd));
  } else {
    asm volatile("{\n.reg .pred p;\nsetp.ne.b32 p, 0, 0;\n"
    "wgmma.mma_async.sync.aligned.m64n64k16.f32.bf16.bf16 {%0,%1,%2,%3,%4,%5,%6,%7,%8,%9,%10,%11,%12,%13,%14,%15,%16,%17,%18,%19,%20,%21,%22,%23,%24,%25,%26,%27,%28,%29,%30,%31}, %32, %33, p, 1, 1, 0, 1;\n}"
    : "+f"(d[0]),"+f"(d[1]),"+f"(d[2]),"+f"(d[3]),"+f"(d[4]),"+f"(d[5]),"+f"(d[6]),"+f"(d[7]),"+f"(d[8]),"+f"(d[9]),"+f"(d[10]),"+f"(d[11]),"+f"(d[12]),"+f"(d[13]),"+f"(d[14]),"+f"(d[15]),"+f"(d[16]),"+f"(d[17]),"+f"(d[18]),"+f"(d[19]),"+f"(d[20]),"+f"(d[21]),"+f"(d[22]),"+f"(d[23]),"+f"(d[24]),"+f"(d[25]),"+f"(d[26]),"+f"(d[27]),"+f"(d[28]),"+f"(d[29]),"+f"(d[30]),"+f"(d[31])
    : "l"(ad), "l"(bd));
  }
}
template<int SD> __device__ __forceinline__ void wg_rs72(float* d, const uint32_t* a, uint64_t bd) {
  if constexpr (SD) {
    asm volatile("{\n.reg .pred p;\nsetp.eq.b32 p, 0, 0;\n"
    "wgmma.mma_async.sync.aligned.m64n72k16.f32.bf16.bf16 {%0,%1,%2,%3,%4,%5,%6,%7,%8,%9,%10,%11,%12,%13,%14,%15,%16,%17,%18,%19,%20,%21,%22,%23,%24,%25,%26,%27,%28,%29,%30,%31,%32,%33,%34,%35}, {%36,%37,%38,%39}, %40, p, 1, 1, 1;\n}"
    : "+f"(d[0]),"+f"(d[1]),"+f"(d[2]),"+f"(d[3]),"+f"(d[4]),"+f"(d[5]),"+f"(d[6]),"+f"(d[7]),"+f"(d[8]),"+f"(d[9]),"+f"(d[10]),"+f"(d[11]),"+f"(d[12]),"+f"(d[13]),"+f"(d[14]),"+f"(d[15]),"+f"(d[16]),"+f"(d[17]),"+f"(d[18]),"+f"(d[19]),"+f"(d[20]),"+f"(d[21]),"+f"(d[22]),"+f"(d[23]),"+f"(d[24]),"+f"(d[25]),"+f"(d[26]),"+f"(d[27]),"+f"(d[28]),"+f"(d[29]),"+f"(d[30]),"+f"(d[31]),"+f"(d[32]),"+f"(d[33]),"+f"(d[34]),"+f"(d[35])
    : "r"(a[0]),"r"(a[1]),"r"(a[2]),"r"(a[3]), "l"(bd));
  } else {
    asm volatile("{\n.reg .pred p;\nsetp.ne.b32 p, 0, 0;\n"
    "wgmma.mma_async.sync.aligned.m64n72k16.f32.bf16.bf16 {%0,%1,%2,%3,%4,%5,%6,%7,%8,%9,%10,%11,%12,%13,%14,%15,%16,%17,%18,%19,%20,%21,%22,%23,%24,%25,%26,%27,%28,%29,%30,%31,%32,%33,%34,%35}, {%36,%37,%38,%39}, %40, p, 1, 1, 1;\n}"
    : "+f"(d[0]),"+f"(d[1]),"+f"(d[2]),"+f"(d[3]),"+f"(d[4]),"+f"(d[5]),"+f"(d[6]),"+f"(d[7]),"+f"(d[8]),"+f"(d[9]),"+f"(d[10]),"+f"(d[11]),"+f"(d[12]),"+f"(d[13]),"+f"(d[14]),"+f"(d[15]),"+f"(d[16]),"+f"(d[17]),"+f"(d[18]),"+f"(d[19]),"+f"(d[20]),"+f"(d[21]),"+f"(d[22]),"+f"(d[23]),"+f"(d[24]),"+f"(d[25]),"+f"(d[26]),"+f"(d[27]),"+f"(d[28]),"+f"(d[29]),"+f"(d[30]),"+f"(d[31]),"+f"(d[32]),"+f"(d[33]),"+f"(d[34]),"+f"(d[35])
    : "r"(a[0]),"r"(a[1]),"r"(a[2]),"r"(a[3]), "l"(bd));
  }
}
template<int SD> __device__ __forceinline__ void wg_ss72(float* d, uint64_t ad, uint64_t bd) {
  if constexpr (SD) {
    asm volatile("{\n.reg .pred p;\nsetp.eq.b32 p, 0, 0;\n"
    "wgmma.mma_async.sync.aligned.m64n72k16.f32.bf16.bf16 {%0,%1,%2,%3,%4,%5,%6,%7,%8,%9,%10,%11,%12,%13,%14,%15,%16,%17,%18,%19,%20,%21,%22,%23,%24,%25,%26,%27,%28,%29,%30,%31,%32,%33,%34,%35}, %36, %37, p, 1, 1, 0, 1;\n}"
    : "+f"(d[0]),"+f"(d[1]),"+f"(d[2]),"+f"(d[3]),"+f"(d[4]),"+f"(d[5]),"+f"(d[6]),"+f"(d[7]),"+f"(d[8]),"+f"(d[9]),"+f"(d[10]),"+f"(d[11]),"+f"(d[12]),"+f"(d[13]),"+f"(d[14]),"+f"(d[15]),"+f"(d[16]),"+f"(d[17]),"+f"(d[18]),"+f"(d[19]),"+f"(d[20]),"+f"(d[21]),"+f"(d[22]),"+f"(d[23]),"+f"(d[24]),"+f"(d[25]),"+f"(d[26]),"+f"(d[27]),"+f"(d[28]),"+f"(d[29]),"+f"(d[30]),"+f"(d[31]),"+f"(d[32]),"+f"(d[33]),"+f"(d[34]),"+f"(d[35])
    : "l"(ad), "l"(bd));
  } else {
    asm volatile("{\n.reg .pred p;\nsetp.ne.b32 p, 0, 0;\n"
    "wgmma.mma_async.sync.aligned.m64n72k16.f32.bf16.bf16 {%0,%1,%2,%3,%4,%5,%6,%7,%8,%9,%10,%11,%12,%13,%14,%15,%16,%17,%18,%19,%20,%21,%22,%23,%24,%25,%26,%27,%28,%29,%30,%31,%32,%33,%34,%35}, %36, %37, p, 1, 1, 0, 1;\n}"
    : "+f"(d[0]),"+f"(d[1]),"+f"(d[2]),"+f"(d[3]),"+f"(d[4]),"+f"(d[5]),"+f"(d[6]),"+f"(d[7]),"+f"(d[8]),"+f"(d[9]),"+f"(d[10]),"+f"(d[11]),"+f"(d[12]),"+f"(d[13]),"+f"(d[14]),"+f"(d[15]),"+f"(d[16]),"+f"(d[17]),"+f"(d[18]),"+f"(d[19]),"+f"(d[20]),"+f"(d[21]),"+f"(d[22]),"+f"(d[23]),"+f"(d[24]),"+f"(d[25]),"+f"(d[26]),"+f"(d[27]),"+f"(d[28]),"+f"(d[29]),"+f"(d[30]),"+f"(d[31]),"+f"(d[32]),"+f"(d[33]),"+f"(d[34]),"+f"(d[35])
    : "l"(ad), "l"(bd));
  }
}
template<int SD> __device__ __forceinline__ void wg_tt64(float* d, uint64_t ad, uint64_t bd) {
  if constexpr (SD) {
    asm volatile("{\n.reg .pred p;\nsetp.eq.b32 p, 0, 0;\n"
    "wgmma.mma_async.sync.aligned.m64n64k16.f32.bf16.bf16 {%0,%1,%2,%3,%4,%5,%6,%7,%8,%9,%10,%11,%12,%13,%14,%15,%16,%17,%18,%19,%20,%21,%22,%23,%24,%25,%26,%27,%28,%29,%30,%31}, %32, %33, p, 1, 1, 1, 1;\n}"
    : "+f"(d[0]),"+f"(d[1]),"+f"(d[2]),"+f"(d[3]),"+f"(d[4]),"+f"(d[5]),"+f"(d[6]),"+f"(d[7]),"+f"(d[8]),"+f"(d[9]),"+f"(d[10]),"+f"(d[11]),"+f"(d[12]),"+f"(d[13]),"+f"(d[14]),"+f"(d[15]),"+f"(d[16]),"+f"(d[17]),"+f"(d[18]),"+f"(d[19]),"+f"(d[20]),"+f"(d[21]),"+f"(d[22]),"+f"(d[23]),"+f"(d[24]),"+f"(d[25]),"+f"(d[26]),"+f"(d[27]),"+f"(d[28]),"+f"(d[29]),"+f"(d[30]),"+f"(d[31])
    : "l"(ad), "l"(bd));
  } else {
    asm volatile("{\n.reg .pred p;\nsetp.ne.b32 p, 0, 0;\n"
    "wgmma.mma_async.sync.aligned.m64n64k16.f32.bf16.bf16 {%0,%1,%2,%3,%4,%5,%6,%7,%8,%9,%10,%11,%12,%13,%14,%15,%16,%17,%18,%19,%20,%21,%22,%23,%24,%25,%26,%27,%28,%29,%30,%31}, %32, %33, p, 1, 1, 1, 1;\n}"
    : "+f"(d[0]),"+f"(d[1]),"+f"(d[2]),"+f"(d[3]),"+f"(d[4]),"+f"(d[5]),"+f"(d[6]),"+f"(d[7]),"+f"(d[8]),"+f"(d[9]),"+f"(d[10]),"+f"(d[11]),"+f"(d[12]),"+f"(d[13]),"+f"(d[14]),"+f"(d[15]),"+f"(d[16]),"+f"(d[17]),"+f"(d[18]),"+f"(d[19]),"+f"(d[20]),"+f"(d[21]),"+f"(d[22]),"+f"(d[23]),"+f"(d[24]),"+f"(d[25]),"+f"(d[26]),"+f"(d[27]),"+f"(d[28]),"+f"(d[29]),"+f"(d[30]),"+f"(d[31])
    : "l"(ad), "l"(bd));
  }
}

template<int V> struct IC { static constexpr int v = V; };
template<int I, int N, class F> __device__ __forceinline__ void sfor(F&& f) {
    if constexpr (I < N) { f(IC<I>{}); sfor<I + 1, N>(f); }
}

enum { K_QKV = 0, K_H = 1 };

struct Ctx {
    uint32_t tph;
    uint32_t tid_;
    bool pf = false;
    __device__ __forceinline__ uint32_t tid() const { uint32_t r; asm volatile("mov.u32 %0, %1;" : "=r"(r) : "r"(tid_)); return r; }
};
__device__ __forceinline__ void release_slot(const Ctx& c, int slot) { if ((c.tid() & 31) == 0) mbar_arrive(bar(B_EMPTY + slot)); }

__device__ __forceinline__ void turn_wait(const Ctx& c) { asm volatile("bar.sync %0, 256;" :: "r"(4 + (c.tid() >> 7)) : "memory"); }
__device__ __forceinline__ void turn_pass(const Ctx& c) { asm volatile("bar.arrive %0, 256;" :: "r"(5 - (c.tid() >> 7)) : "memory"); }

template<int KIND, class PART, class POST>
__device__ __forceinline__ void run_step(Ctx& c, float* acc, const uint32_t* a, PART&& part, POST&& post, bool last = false) {
    constexpr int NST = (KIND == K_QKV) ? 6 : 3;
    constexpr int KPS = 36 / NST;
    sfor<0, NST>([&](auto ST) {
        constexpr int st = decltype(ST)::v;
        constexpr int slot = st % 3;
        mbar_wait(bar(B_FULL + slot), c.tph);
        uint32_t wgo = 0;
        if constexpr (st == NST - 1) wgo = (c.tid() >> 7) * 512;
        if (KIND == K_H && c.pf) prof(44 + st * 5);
        turn_wait(c);
        if (KIND == K_H && c.pf) prof(45 + st * 5);
        wg_fence();
        sfor<0, KPS>([&](auto KK) {
            constexpr int kk = decltype(KK)::v;
            constexpr int ks = st * KPS + kk;
            constexpr int SD = ks ? 1 : 0;
            if constexpr (KIND == K_QKV) {
                constexpr uint64_t bd = mkdesc(RING + slot * SLOT + kk * 2048, 12288, 1024, 1);
                if constexpr (ks < 32) wg_rs72<SD>(acc, a + ks * 4, bd);
                else wg_ss72<SD>(acc, mkdesc(XB + (ks - 32) * 32, 16, 1024, 1) + wgo, bd);
            } else {
                constexpr uint64_t bd = mkdesc(RING + slot * SLOT + kk * 2048, 16, 1024, 1);
                if constexpr (ks < 32) wg_rs64<SD>(acc, a + ks * 4, bd);
                else wg_ss64<SD>(acc, mkdesc(XB + (ks - 32) * 32, 16, 1024, 1) + wgo, bd);
            }
        });
        wg_commit();
        if (st < NST - 1 || !last || c.tid() < 128) turn_pass(c);
        if (KIND == K_H && c.pf) prof(46 + st * 5);
        part(ST);
        if (KIND == K_H && c.pf) prof(47 + st * 5);
        wg_wait<0>();
        if (KIND == K_H && c.pf) prof(48 + st * 5);
        release_slot(c, slot);
        if constexpr (slot == 2) c.tph ^= 1;
        post(ST);
    });
    if constexpr (KIND == K_QKV) reg_fence<36>(acc); else reg_fence<32>(acc);
}

__device__ __forceinline__ float phi(float t) {
    float e = ex2(t * 1.4426950408889634f);
    return (t > 0.f ? t + 1.0f : e) + 1e-6f;
}
__device__ __forceinline__ float gelu_h(float hx) {
    float u = hx * fmaf(hx * hx, 0.2854192650f, 1.5957691216f);
    return fmaf(hx, tanh_ap(u), hx);
}

struct Params {
    const __nv_bfloat16* x;
    const __nv_bfloat16* wqkv;
    const __nv_bfloat16* wo;
    const __nv_bfloat16* w1;
    const __nv_bfloat16* b1;
    const __nv_bfloat16* w2;
    const __nv_bfloat16* b2;
    __nv_bfloat16* out;
};

__global__ void __launch_bounds__(384, 1)
fused_kernel(const __grid_constant__ CUtensorMap tm_x, const __grid_constant__ CUtensorMap tm_w1,
             const __grid_constant__ CUtensorMap tm_w2, const __grid_constant__ CUtensorMap tm_wo,
             const __grid_constant__ CUtensorMap tm_o, const __grid_constant__ CUtensorMap tm_qkv,
             const __grid_constant__ CUtensorMap tm_qkve, const __grid_constant__ CUtensorMap tm_out, const Params p) {
    extern __shared__ __align__(1024) unsigned char smem_raw[];
    const int tid = threadIdx.x;
    const int bid = blockIdx.x;
    const bool is_main = bid < NMAIN;
    const int j = bid & 7;
    const int m = bid >> 3;

    if (tid == 0) {
        if ((uint32_t)__cvta_generic_to_shared(smem_raw) != SB) __trap();
        for (int i = 0; i < 3; i++) {
            mbar_init(bar(B_FULL + i), 1); mbar_init(bar(B_EMPTY + i), 8);
            mbar_init(bar(B_XFULL + i), 1);
        }
        mbar_init(bar(B_KVB), 2);
        mbar_init(bar(B_OFULL), 1); mbar_init(bar(B_O8FULL), 1); mbar_init(bar(B_OFREE), 8); mbar_init(bar(B_O8FREE), 8);
        asm volatile("fence.mbarrier_init.release.cluster;" ::: "memory");
        if (is_main) {
            for (int g = 0; g < 3; g++) {
                mbar_expect_tx(bar(B_XFULL + g), 49152);
                for (int kb = 3 * g; kb < 3 * g + 3; kb++) tma_2d(HA + kb * 16384, &tm_x, bar(B_XFULL + g), kb * 64, m * 128);
            }
            for (int st = 0; st < 3; st++) {
                mbar_expect_tx(bar(B_FULL + st), 96 * 144);
                tma_2d(RING + st * SLOT, &tm_qkv, bar(B_FULL + st), 576 + j * 72, st * 96);
                tma_2d(RING + st * SLOT + 12288, &tm_qkve, bar(B_FULL + st), 576 + j * 72 + 64, st * 96);
            }
        }
    }
    if (tid == 32) { sts32(EPO, g_epoch[bid]); sts32(EPO + 4, 0); }
    if (tid >= 40 && tid < 48) sts32(EVC + (tid - 40) * 4, 0);
    if (tid >= 64 && tid < 64 + 288 && is_main) {
        int i = tid - 64;
        uint32_t v = *reinterpret_cast<const uint32_t*>(p.b1 + j * 576 + 2 * i);
        sts32(B1S + 8 * i, __float_as_uint(0.5f * bf_lo(v))); sts32(B1S + 8 * i + 4, __float_as_uint(0.5f * bf_hi(v)));
    }
    if (tid >= 352) {
        int i = tid - 352;
        uint32_t v = *reinterpret_cast<const uint32_t*>(p.b2 + (is_main ? j : 8) * 64 + 2 * i);
        sts32(B2S + 8 * i, v << 16); sts32(B2S + 8 * i + 4, v & 0xffff0000u);
    }
    fence_async_smem();
    __syncthreads();
    uint32_t epoch;
    asm volatile("ld.shared.u32 %0, [%1];" : "=r"(epoch) : "r"(EPO));
    const uint32_t par = epoch & 1;

    if (tid >= 256) {
        asm volatile("setmaxnreg.dec.sync.aligned.u32 24;");
        const int hw = (tid >> 5) - 8, lane = tid & 31;
        if (hw == 0) {
            if (lane == 0) {
                uint32_t n = 0;
                if (is_main) {
                    n = 1;
                    #pragma unroll 1
                    for (int u = 3; u < 18; u++) {
                        const int st = u % 3, step = u / 6;
                        const int col = ((step == 2) ? 0 : (step + 1) * 576) + j * 72, row = (u % 6) * 96;
                        mbar_wait(bar(B_EMPTY + st), (n & 1) ^ 1);
                        mbar_expect_tx(bar(B_FULL + st), 96 * 144);
                        tma_2d(RING + st * SLOT, &tm_qkv, bar(B_FULL + st), col, row);
                        tma_2d(RING + st * SLOT + 12288, &tm_qkve, bar(B_FULL + st), col + 64, row);
                        if (st == 2) n++;
                    }
                }
                const int nsteps = is_main ? 19 : 1;
                #pragma unroll 1
                for (int s = 0; s < nsteps; s++, n++) {
                    const CUtensorMap* tm; int col, row;
                    if (!is_main) { tm = &tm_wo; col = 512; row = 0; }
                    else if (s < 9) { tm = &tm_w1; col = j * 576 + s * 64; row = 0; }
                    else if (s < 18) { tm = &tm_w2; col = (s == 9) ? 512 : (((j + s - 9) & 7) * 64); row = j * 576; }
                    else { tm = &tm_wo; col = j * 64; row = 0; }
                    #pragma unroll 1
                    for (int st = 0; st < 3; st++) {
                        mbar_wait(bar(B_EMPTY + st), (n & 1) ^ 1);
                        mbar_expect_tx(bar(B_FULL + st), SLOT);
                        tma_2d(RING + st * SLOT, tm, bar(B_FULL + st), col, row + st * 192);
                    }
                }
            }
        } else {
            if (is_main) {
                const int t = tid - 288;
                #pragma unroll 1
                for (int i = t; i < 36 * 6; i += 96) {
                    int r = i / 6, q = i - r * 6;
                    prefetch_l2(reinterpret_cast<const char*>(p.wqkv) + (36 * m + r) * 3456 + (q >> 1) * 1152 + j * 144 + (q & 1) * 128);
                }
                __nanosleep(PF1_NS);
                #pragma unroll 1
                for (int i = t; i < 36 * 9; i += 96) {
                    int r = i / 9, q = i - r * 9;
                    prefetch_l2(reinterpret_cast<const char*>(p.w1) + (36 * m + r) * 9216 + j * 1152 + q * 128);
                    __nanosleep(PF3_NS);
                }
                __nanosleep(PF2_NS);
                #pragma unroll 1
                for (int i = t; i < 36 * 9; i += 96)
                    prefetch_l2(reinterpret_cast<const char*>(p.w2) + (576 * j + 36 * m) * 1152 + i * 128);
                if (t < 41 && (bid * 41 + t) < 5184) prefetch_l2(reinterpret_cast<const char*>(p.wo) + (bid * 41 + t) * 128);
                if (hw != 2) {
                    if (lane == 0) wait_cnt(cnt_kv(j), (epoch + 1) * 16);
                    __syncwarp();
                    const float4* kv = reinterpret_cast<const float4*>(g_kv + (par * 8 + j) * 1440);
                    #pragma unroll 2
                    for (int i = lane + (hw == 1 ? 0 : 32); i < 360; i += 64) {
                        const float4 v = __ldcg(kv + i);
                        const int d = i / 5, e = (i - d * 5) * 4, h = d / 18;
                        const uint32_t base = KVB + (d >> 3) * 128 + (d & 7) * 16;
                        const int n0 = 8 + h * 18 + e;
                        sts32(base + (n0 >> 3) * 1280 + (n0 & 7) * 2, pack_bf16(v.x, v.y));
                        if (e < 16) sts32(base + ((n0 + 2) >> 3) * 1280 + ((n0 + 2) & 7) * 2, pack_bf16(v.z, v.w));
                        else asm volatile("st.shared.u16 [%0], %1;" :: "r"(base + h * 2), "h"((unsigned short)pack_bf16(v.z, 0.f)) : "memory");
                    }
                    fence_async_smem();
                    __syncwarp();
                    if (lane == 0) mbar_arrive(bar(B_KVB));
                }
            }
            if (hw == 1) {
                if (lane == 0) {
                    const int nit = is_main ? 1 : 4;
                    for (int it = 0; it < nit; it++) {
                        const int mt = is_main ? m : ((bid - NMAIN) * 4 + it);
                        const bool wf = is_main || it > 0;
                        const uint32_t fp = is_main ? 0 : ((it - 1) & 1);
                        wait_cnt(cnt_o(mt), (epoch + 1) * 8);
                        fence_async_all();
                        if (wf) mbar_wait(bar(B_OFREE), fp);
                        mbar_expect_tx(bar(B_OFULL), 131072);
                        #pragma unroll 1
                        for (int kb = 0; kb < 8; kb++) tma_2d(HA + kb * 16384, &tm_o, bar(B_OFULL), kb * 64, mt * 128);
                        if (wf) mbar_wait(bar(B_O8FREE), fp);
                        mbar_expect_tx(bar(B_O8FULL), 16384);
                        tma_2d(XB, &tm_o, bar(B_O8FULL), 512, mt * 128);
                    }
                    if (is_main) { wait_cnt(cnt_y(m, j), (epoch + 1) * 7); asm volatile("st.release.cta.shared.u32 [%0], %1;" :: "r"(EPO + 4), "r"(1) : "memory"); }
                }
            } else if (hw == 2) {
                if (!is_main) {
                    if (lane == 0) {
                        #pragma unroll 1
                        for (int it = 0; it < 4; it++) {
                            wait_cnt(cnt_y((bid - NMAIN) * 4 + it, 8), (epoch + 1) * 8);
                            asm volatile("st.release.cta.shared.u32 [%0], %1;" :: "r"(EPO + 4), "r"(it + 1) : "memory");
                        }
                    }
                } else {
                    #pragma unroll 1
                    for (int e = 0; e < 10; e++) {
                        int spin = 0;
                        while (true) {
                            uint32_t v;
                            asm volatile("ld.acquire.cta.shared.u32 %0, [%1];" : "=r"(v) : "r"(EVC + (lane & 7) * 4) : "memory");
                            if (__all_sync(0xffffffffu, v > (uint32_t)e)) break;
                            if (++spin > 20000000) __trap();
                            __nanosleep(20);
                        }
                        if (lane == 0) {
                            unsigned int* cp = (e == 0) ? cnt_kv(j) : (e == 1) ? cnt_o(m) : cnt_y(m, e == 2 ? 8 : ((j + e - 2) & 7));
                            if (e == 1) fence_async_all();
                            __threadfence();
                            asm volatile("red.relaxed.gpu.global.add.u32 [%0], 1;" :: "l"(cp) : "memory");
                        }
                        __syncwarp();
                    }
                }
            } else {
                {
                    const int t0 = is_main ? (m * 9 + j) : ((bid - NMAIN) * 4 * 9 + 8);
                    const int nt = is_main ? 1 : 4;
                    for (int t = 0; t < nt; t++) {
                        uint4* z = reinterpret_cast<uint4*>(g_yacc + (size_t)((par ^ 1) * 144 + t0 + t * 9) * YT_BYTES);
                        for (int i = lane; i < YT_BYTES / 16; i += 32) z[i] = make_uint4(0, 0, 0, 0);
                    }
                    if (is_main && m == 0) {
                        float* z = g_kv + ((par ^ 1) * 8 + j) * 1440;
                        for (int i = lane; i < 1440; i += 32) z[i] = 0.f;
                    }
                }
            }
        }
    } else {
        asm volatile("setmaxnreg.inc.sync.aligned.u32 240;");
        prof(0);
        Ctx c; c.tph = 0; c.tid_ = v_tid();
        float hc[32], pv[36];
        if (tid >> 7) turn_pass(c);
        auto event = [&](uint32_t ev) {
            __syncwarp();
            if (((c.tid() & 31) == 0)) asm volatile("st.release.cta.shared.u32 [%0], %1;" :: "r"(EVC + (c.tid() >> 3)), "r"(ev) : "memory");
        };
        auto warp_arrive = [&](uint32_t b) { __syncwarp(); if (((c.tid() & 31) == 0)) mbar_arrive(b); };

        auto lrow_off = [&]() { uint32_t t_ = c.tid(); return HA + ((t_ >> 5) * 16 + (t_ & 15)) * 128 + ((((t_ >> 4) & 1) ^ (t_ & 7)) << 4); };
        auto tail_off = [&]() { uint32_t t_ = c.tid(), g = (t_ >> 2) & 7; return XB + ((t_ >> 5) * 16 + g) * 128 + (g << 4) + (t_ & 3) * 4; };
        if (is_main) {
            uint32_t a[128];
            float rs0, rs1;
            uint32_t m00, m11;
            {
                uint32_t tl[16];
                const uint32_t lrow = lrow_off();
                float cs[2][4] = {{0.f, 0.f, 0.f, 0.f}, {0.f, 0.f, 0.f, 0.f}};
                sfor<0, 36>([&](auto KS) {
                    constexpr int ks = decltype(KS)::v;
                    if constexpr (ks % 12 == 0) mbar_wait(bar(B_XFULL + ks / 12), 0);
                    uint32_t* dst = (ks < 32) ? (a + (ks & 31) * 4) : (tl + (ks & 3) * 4);
                    ldsm4((lrow ^ ((ks % 4) << 5)) + (ks / 4) * 16384, dst);
                    mma_ones(cs[ks & 1], dst);
                });
                prof(2);
                float mean0 = (cs[0][0] + cs[1][0]) * (1.0f / 576.0f), mean1 = (cs[0][2] + cs[1][2]) * (1.0f / 576.0f);
                m00 = pack_bf16(mean0, mean0); m11 = pack_bf16(mean1, mean1);
                rs0 = mean0 - bf_lo(m00); rs1 = mean1 - bf_lo(m11);
                rs0 = -144.0f * rs0 * rs0; rs1 = -144.0f * rs1 * rs1;
                const uint32_t tb = tail_off();
                #pragma unroll
                for (int i = 0; i < 16; i++) {
                    const uint32_t w = sub_bf16x2(tl[i], (i & 1) ? m11 : m00);
                    sts32((tb ^ ((i >> 1) << 4)) + (i & 1) * 1024, w);
                    float lo = bf_lo(w), hi = bf_hi(w);
                    if (i & 1) rs1 = fmaf(lo, lo, fmaf(hi, hi, rs1)); else rs0 = fmaf(lo, lo, fmaf(hi, hi, rs0));
                }
                fence_async_smem();
                #pragma unroll
                for (int i = 0; i < 128; i++) a[i] = sub_bf16x2(a[i], (i & 1) ? m11 : m00);
                named_bar(2 + (tid >> 7), 128);
            }
            prof(3);
            auto cm_off = [&]() { uint32_t t_ = c.tid(); return (t_ >> 5) * 256 + (t_ & 31) * 4; };
            {
                float qc[36];
                #pragma unroll
                for (int i = 0; i < 36; i++) { qc[i] = 0.f; pv[i] = 0.f; }
                #pragma unroll 1
                for (int s = 0; s < 3; s++) {
                    run_step<K_QKV>(c, qc, a, [&](auto ST) {
                        constexpr int st = decltype(ST)::v;
                        if (s == 0) {
                            const uint32_t lrow = lrow_off();
                            sfor<(st * 32) / 6, ((st + 1) * 32) / 6>([&](auto I) {
                                constexpr int ks = decltype(I)::v;
                                uint32_t v[4];
                                ldsm4((lrow ^ ((ks % 4) << 5)) + (ks / 4) * 16384, v);
                                #pragma unroll
                                for (int r = 0; r < 4; r++) {
                                    uint32_t w = sub_bf16x2(v[r], (r & 1) ? m11 : m00);
                                    float lo = bf_lo(w), hi = bf_hi(w);
                                    if (r & 1) rs1 = fmaf(lo, lo, fmaf(hi, hi, rs1)); else rs0 = fmaf(lo, lo, fmaf(hi, hi, rs0));
                                }
                            });
                            if constexpr (st == 5) {
                                rs0 += __shfl_xor_sync(0xffffffffu, rs0, 1); rs1 += __shfl_xor_sync(0xffffffffu, rs1, 1);
                                rs0 += __shfl_xor_sync(0xffffffffu, rs0, 2); rs1 += __shfl_xor_sync(0xffffffffu, rs1, 2);
                                rs0 = rsqrtf(fmaxf(rs0 * (1.0f / 576.0f), 0.f) + 1e-5f);
                                rs1 = rsqrtf(fmaxf(rs1 * (1.0f / 576.0f), 0.f) + 1e-5f);
                                named_bar(1, 256);
                            }
                        } else {
                            const uint32_t cm = cm_off();
                            sfor<0, 9>([&](auto B) {
                                constexpr int b = decltype(B)::v;
                                if constexpr ((b * 6) / 9 == st) {
                                    const float v0 = pv[4 * b] * rs0, v1 = pv[4 * b + 1] * rs0, v2 = pv[4 * b + 2] * rs1, v3 = pv[4 * b + 3] * rs1;
                                    if (s == 1) {
                                        sts32(PKT + b * 2048 + cm, pack_bf16(phi(v0), phi(v1)));
                                        sts32(PKT + b * 2048 + cm + 128, pack_bf16(phi(v2), phi(v3)));
                                    } else {
                                        const uint32_t w0 = pack_bf16(v0, v1), w1 = pack_bf16(v2, v3);
                                        if constexpr (b <= 4) { sts32(VT + b * 2048 + cm, w0); sts32(VT + b * 2048 + cm + 128, w1); }
                                        if constexpr (b >= 4) { sts32(VT + (b + 2) * 2048 + cm, w0); sts32(VT + (b + 2) * 2048 + cm + 128, w1); }
                                        if constexpr (b == 0) {
                                            const uint32_t one = (cm & 12) ? 0u : 0x00003F80u;
                                            sts32(VT + 5 * 2048 + cm, one); sts32(VT + 5 * 2048 + cm + 128, one);
                                        }
                                        if constexpr (b == 8) {
                                            const uint32_t z = KVB + c.tid() * 16;
                                            sts128(z, 0, 0, 0, 0); sts128(z + 4096, 0, 0, 0, 0); sts128(z + 8192, 0, 0, 0, 0);
                                            if (z < KVB + 512) sts128(z + 12288, 0, 0, 0, 0);
                                            fence_async_smem();
                                        }
                                    }
                                }
                            });
                        }
                    }, [](auto) {});
                    reg_copy<36>(pv, qc);
                    prof(4 + s);
                }
            }
            {
                #pragma unroll
                for (int i = 0; i < 32; i++) hc[i] = 0.f;
                named_bar(1, 256);
                const uint32_t wgo = ((c.tid() >> 7) * 512);
                wg_fence();
                sfor<0, 8>([&](auto KS) {
                    constexpr int ks = decltype(KS)::v;
                    wg_tt64<(ks ? 1 : 0)>(hc, mkdesc(PKT + ks * 256, 128, 2048, 0) + wgo,
                                          mkdesc(VT + ks * 256, 128, 2048, 0) + wgo + (wgo >> 2));
                });
                wg_commit();
                const uint32_t pq = PQT + cm_off() + ((c.tid() >> 7) * 512) * 16;
                sfor<0, 9>([&](auto B) {
                    constexpr int b = decltype(B)::v;
                    sts32(pq + b * 1024, pack_bf16(phi(pv[4 * b] * rs0), phi(pv[4 * b + 1] * rs0)));
                    sts32(pq + b * 1024 + 128, pack_bf16(phi(pv[4 * b + 2] * rs1), phi(pv[4 * b + 3] * rs1)));
                });
                fence_async_smem();
                wg_wait<0>();
                reg_fence<32>(hc);
                reg_copy<24>(pv, hc);
            }
            prof(7);
            rs0 *= 0.5f; rs1 *= 0.5f;
            auto gelun = [&](auto B0, auto B1, uint32_t bofs, uint32_t* w) {
                constexpr int b0 = decltype(B0)::v, nb = decltype(B1)::v - b0;
                float2 bv[nb];
                #pragma unroll
                for (int i = 0; i < nb; i++) bv[i] = lds64f(bofs + (b0 + i) * 32);
                #pragma unroll
                for (int i = 0; i < nb; i++) {
                    const int b = b0 + i;
                    w[2 * i]     = pack_bf16(gelu_h(fmaf(pv[4 * b], rs0, bv[i].x)), gelu_h(fmaf(pv[4 * b + 1], rs0, bv[i].y)));
                    w[2 * i + 1] = pack_bf16(gelu_h(fmaf(pv[4 * b + 2], rs1, bv[i].x)), gelu_h(fmaf(pv[4 * b + 3], rs1, bv[i].y)));
                }
            };
            auto spill_off = [&]() { uint32_t t_ = c.tid(); return HA + (t_ >> 7) * 8192 + (t_ & 127) * 8; };
            auto reload = [&](auto S0, auto S1) {
                const uint32_t spill = spill_off();
                sfor<decltype(S0)::v * 8, decltype(S1)::v * 8>([&](auto Q) {
                    constexpr int q = decltype(Q)::v;
                    lds64(spill + (q / 8) * 16384 + (q % 8) * 1024, a + q * 2);
                });
            };
            #pragma unroll 1
            for (int idx = 0; idx < 18; idx++) {
                run_step<K_H>(c, hc, a, [&](auto ST) {
                    constexpr int st = decltype(ST)::v;
                    if (idx >= 10) {
                        if constexpr (st < 2) {
                            const uint32_t b_ = v_bid();
                            const uint32_t chunk = (idx == 10) ? 8 : ((b_ + idx - 10) & 7);
                            unsigned char* yp = g_yacc + ((v_epoch() & 1) * 144 + (b_ >> 3) * 9 + chunk) * YT_BYTES + c.tid() * 16;
                            sfor<2 * st, 2 * st + 2>([&](auto Q) {
                                constexpr int q = decltype(Q)::v;
                                asm volatile("red.global.add.noftz.v4.bf16x2 [%0], {%1,%2,%3,%4};" :: "l"(yp + q * 4096),
                                             "r"(pack_bf16(pv[8 * q], pv[8 * q + 1])), "r"(pack_bf16(pv[8 * q + 2], pv[8 * q + 3])),
                                             "r"(pack_bf16(pv[8 * q + 4], pv[8 * q + 5])), "r"(pack_bf16(pv[8 * q + 6], pv[8 * q + 7])) : "memory");
                            });
                            if constexpr (st == 1) event(idx - 7);
                        }
                    } else if (idx >= 1) {
                        const uint32_t bofs = B1S + (idx - 1) * 256 + (c.tid() & 3) * 8;
                        if (idx < 9) {
                            if constexpr (st == 0) { if (idx == OSTEP_AT + 1) event(2); }
                            const uint32_t spill = spill_off() + (idx - 1) * 16384;
                            constexpr int b0 = st * 3, b1 = (st == 2 ? 8 : st * 3 + 3);
                            uint32_t w[6];
                            gelun(IC<b0>{}, IC<b1>{}, bofs, w);
                            #pragma unroll
                            for (int b = b0; b < b1; b++) sts64(spill + b * 1024, w[2 * (b - b0)], w[2 * (b - b0) + 1]);
                        } else {
                            if constexpr (st < 2) {
                                const uint32_t tb = tail_off();
                                uint32_t w[8];
                                gelun(IC<st * 4>{}, IC<st * 4 + 4>{}, bofs, w);
                                #pragma unroll
                                for (int i = 0; i < 4; i++) { sts32(tb ^ ((st * 4 + i) << 4), w[2 * i]); sts32((tb ^ ((st * 4 + i) << 4)) + 1024, w[2 * i + 1]); }
                            }
                            if constexpr (st == 1) { fence_async_smem(); named_bar(2 + (c.tid() >> 7), 128); }
                        }
                    } else {
                        if constexpr (st < 2) {
                            constexpr int hf = st;
                            const int t_ = c.tid(), wg = t_ >> 7, t = t_ & 3;
                            float* dst = g_kv + ((v_epoch() & 1) * 8 + (v_bid() & 7)) * 1440;
                            const int d = wg * 32 + ((t_ >> 5) & 3) * 16 + ((t_ >> 2) & 7) + hf * 8;
                            const bool dv = wg ? (d >= 36 && d < 72) : (d < 36);
                            const int e00 = wg * 24 + 2 * t - (d / 18) * 18;
                            float* dp = dst + d * 20 + e00;
                            #pragma unroll
                            for (int i = 0; i < 6; i++) {
                                const int e = e00 + i * 8;
                                const bool blk = wg ? (i >= 1) : (i <= 4);
                                if (dv && blk && e >= 0 && e < 18)
                                    asm volatile("red.global.add.v2.f32 [%0], {%1,%2};" :: "l"(dp + i * 8), "f"(pv[4 * i + 2 * hf]), "f"(pv[4 * i + 2 * hf + 1]) : "memory");
                            }
                            if (dv && t == 0) atomicAdd(dst + d * 20 + 18, wg ? pv[2 * hf] : pv[20 + 2 * hf]);
                            if constexpr (st == 1) event(1);
                        }
                    }
                }, [&](auto ST) {
                    constexpr int st = decltype(ST)::v;
                    if (idx == 8) {
                        reload(IC<3 * st>{}, IC<(st == 2 ? 8 : 3 * st + 3)>{});
                        if constexpr (st == 2) warp_arrive(bar(B_OFREE));
                    }
                });
                reg_copy<32>(pv, hc);
                prof(8 + idx);
                if (idx == OSTEP_AT) {
                    mbar_wait(bar(B_KVB), 0);
                    prof(34);
                    const uint32_t pqo = (c.tid() >> 7) * 576;
                    const int t_ = c.tid(), b_ = v_bid(), t = t_ & 3, l4 = t_ & 28;
                    __nv_bfloat16* op = g_o + (size_t)((b_ >> 3) * 128 + (t_ >> 5) * 16 + ((t_ >> 2) & 7)) * DM + (b_ & 7) * 72 + 2 * t;
                    float r3[2];
                    sfor<0, 2>([&](auto PS) {
                        constexpr int ps = decltype(PS)::v;
                        wg_fence();
                        sfor<0, 5>([&](auto KS) {
                            constexpr int ks = decltype(KS)::v;
                            wg_ss64<(ks ? 1 : 0)>(hc, mkdesc(PQT + ks * 2048, ks == 4 ? 0 : 1024, 128, 0) + pqo, mkdesc(KVB + ps * 8 * 1280 + ks * 256, 128, 1280, 0));
                        });
                        wg_commit();
                        wg_wait<0>();
                        reg_fence<32>(hc);
                        #pragma unroll
                        for (int hf = 0; hf < 2; hf++) {
                            if constexpr (ps == 0) {
                                float r[4];
                                r[0] = rcp(__shfl_sync(0xffffffffu, hc[2 * hf], l4) + 1e-6f);
                                r[1] = rcp(__shfl_sync(0xffffffffu, hc[1 + 2 * hf], l4) + 1e-6f);
                                r[2] = rcp(__shfl_sync(0xffffffffu, hc[2 * hf], l4 + 1) + 1e-6f);
                                r[3] = rcp(__shfl_sync(0xffffffffu, hc[1 + 2 * hf], l4 + 1) + 1e-6f);
                                r3[hf] = r[3];
                                #pragma unroll
                                for (int i = 0; i < 7; i++) {
                                    float rr = (i < 2) ? r[0] : (i == 2) ? (t < 1 ? r[0] : r[1]) : (i == 3) ? r[1] : (i == 4) ? (t < 2 ? r[1] : r[2])
                                             : (i == 5) ? r[2] : (t < 3 ? r[2] : r[3]);
                                    *reinterpret_cast<uint32_t*>(op + hf * 8 * DM + i * 8) = pack_bf16(hc[4 * i + 4 + 2 * hf] * rr, hc[4 * i + 5 + 2 * hf] * rr);
                                }
                            } else {
                                #pragma unroll
                                for (int i = 0; i < 2; i++)
                                    *reinterpret_cast<uint32_t*>(op + hf * 8 * DM + 56 + i * 8) = pack_bf16(hc[4 * i + 2 * hf] * r3[hf], hc[4 * i + 1 + 2 * hf] * r3[hf]);
                            }
                        }
                    });
                }
            }
        }
        if (is_main) warp_arrive(bar(B_O8FREE));
        else {
            #pragma unroll
            for (int i = 0; i < 32; i++) { asm volatile("mov.b32 %0, 0;" : "=f"(hc[i])); asm volatile("mov.b32 %0, 0;" : "=f"(pv[i])); }
        }
        auto add_b2 = [&]() {
            #pragma unroll
            for (int b = 0; b < 8; b++) {
                float2 bv = lds64f(B2S + b * 32 + (c.tid() & 3) * 8);
                pv[4 * b] += bv.x; pv[4 * b + 1] += bv.y; pv[4 * b + 2] += bv.x; pv[4 * b + 3] += bv.y;
            }
        };
        auto load_xy = [&](int ftile, int nrdy, uint32_t* xr, uint32_t* yv) {
            const int mt = ftile / 9, ch = ftile - mt * 9;
            const uint32_t t_ = c.tid();
            const __nv_bfloat16* xp = p.x + (size_t)(mt * 128 + (t_ >> 5) * 16 + ((t_ >> 2) & 7)) * DM + ch * 64 + 2 * (t_ & 3);
            #pragma unroll
            for (int i = 0; i < 8; i++) {
                asm volatile("ld.global.nc.u32 %0, [%1];" : "=r"(xr[2 * i]) : "l"(xp + i * 8));
                asm volatile("ld.global.nc.u32 %0, [%1];" : "=r"(xr[2 * i + 1]) : "l"(xp + 8 * DM + i * 8));
            }
            prof(26);
            smem_wait_gt(EPO + 4, nrdy);
            prof(27);
            const unsigned char* yp = g_yacc + ((v_epoch() & 1) * 144 + ftile) * YT_BYTES + t_ * 16;
            #pragma unroll
            for (int q = 0; q < YT_BYTES / 4096; q++)
                asm volatile("ld.global.cg.v4.u32 {%0,%1,%2,%3}, [%4];" : "=r"(yv[4 * q]), "=r"(yv[4 * q + 1]), "=r"(yv[4 * q + 2]), "=r"(yv[4 * q + 3]) : "l"(yp + q * 4096) : "memory");
        };
        auto gate = [&](const uint32_t* yv) {
            #pragma unroll
            for (int i = 0; i < 16; i++) { pv[2 * i] += bf_lo(yv[i]); pv[2 * i + 1] += bf_hi(yv[i]); }
            #pragma unroll
            for (int i = 0; i < 32; i++) { const float h = 0.5f * pv[i]; pv[i] = fmaf(h, tanh_ap(h), h); }
        };
        auto store_out = [&](int ftile, const uint32_t* xr) {
            const uint32_t tb = tail_off();
            #pragma unroll
            for (int b = 0; b < 8; b++) {
                sts32(tb ^ (b << 4), pack_bf16(fmaf(hc[4 * b], pv[4 * b], bf_lo(xr[2 * b])), fmaf(hc[4 * b + 1], pv[4 * b + 1], bf_hi(xr[2 * b]))));
                sts32((tb ^ (b << 4)) + 1024, pack_bf16(fmaf(hc[4 * b + 2], pv[4 * b + 2], bf_lo(xr[2 * b + 1])), fmaf(hc[4 * b + 3], pv[4 * b + 3], bf_hi(xr[2 * b + 1]))));
            }
            fence_async_smem();
            __syncwarp();
            const uint32_t t_ = c.tid();
            if ((t_ & 31) == 0) {
                const int mt = ftile / 9, ch = ftile - mt * 9;
                asm volatile("cp.async.bulk.tensor.2d.global.shared::cta.bulk_group [%0, {%2, %3}], [%1];"
                             :: "l"(&tm_out), "r"(XB + (t_ >> 5) * 2048), "r"(ch * 64), "r"(mt * 128 + (int)(t_ >> 5) * 16) : "memory");
                asm volatile("cp.async.bulk.commit_group;" ::: "memory");
                asm volatile("cp.async.bulk.wait_group.read 0;" ::: "memory");
            }
            __syncwarp();
        };
        const int njob = is_main ? 1 : 4;
        #pragma unroll 1
        for (int job = 0; job < njob; job++) {
            const uint32_t jpar = job & 1;
            const uint32_t b_ = v_bid();
            const bool mainf = b_ < NMAIN;
            const int ftile = (b_ >> 3) * 9 + (b_ & 7);
            uint32_t oa[128];
            {
                mbar_wait(bar(B_OFULL), jpar);
                const uint32_t lrow = lrow_off();
                sfor<0, 32>([&](auto KS) {
                    constexpr int ks = decltype(KS)::v;
                    ldsm4((lrow ^ ((ks % 4) << 5)) + (ks / 4) * 16384, oa + ks * 4);
                });
                warp_arrive(bar(B_OFREE));
                if (job) c.tph ^= 1;
            }
            c.pf = false;
            run_step<K_H>(c, hc, oa, [&](auto ST) {
                constexpr int st = decltype(ST)::v;
                if (mainf) {
                    if constexpr (st == 0) add_b2();
                    else if constexpr (st == 1) load_xy(ftile, 0, oa, oa + 16);
                    else { prof(28); gate(oa + 16); prof(29); }
                }
                if constexpr (st == 1) mbar_wait(bar(B_O8FULL), jpar);
            }, [](auto) {}, job == njob - 1);
            prof(30);
            if (mainf) {
                named_bar(2 + (c.tid() >> 7), 128);
                store_out(ftile, oa);
            } else {
                warp_arrive(bar(B_O8FREE));
                uint4* sp = reinterpret_cast<uint4*>(g_s8) + ((b_ - NMAIN) * 4 + job) * 1024 + c.tid();
                #pragma unroll
                for (int q = 0; q < 4; q++)
                    sp[q * 256] = make_uint4(pack_bf16(hc[8 * q], hc[8 * q + 1]), pack_bf16(hc[8 * q + 2], hc[8 * q + 3]),
                                             pack_bf16(hc[8 * q + 4], hc[8 * q + 5]), pack_bf16(hc[8 * q + 6], hc[8 * q + 7]));
                prof(8 + job);
            }
        }
        if (!is_main) {
            named_bar(2 + (c.tid() >> 7), 128);
            #pragma unroll 1
            for (int job = 0; job < 4; job++) {
                const int tile = (v_bid() - NMAIN) * 4 + job;
                uint32_t xr[16], yv[YT_BYTES / 1024];
                const uint4* sp = reinterpret_cast<const uint4*>(g_s8) + tile * 1024 + c.tid();
                #pragma unroll
                for (int q = 0; q < 4; q++) {
                    const uint4 u = __ldcg(sp + q * 256);
                    hc[8 * q] = bf_lo(u.x); hc[8 * q + 1] = bf_hi(u.x); hc[8 * q + 2] = bf_lo(u.y); hc[8 * q + 3] = bf_hi(u.y);
                    hc[8 * q + 4] = bf_lo(u.z); hc[8 * q + 5] = bf_hi(u.z); hc[8 * q + 6] = bf_lo(u.w); hc[8 * q + 7] = bf_hi(u.w);
                }
                #pragma unroll
                for (int i = 0; i < 32; i++) pv[i] = 0.f;
                add_b2();
                load_xy(tile * 9 + 8, job, xr, yv);
                gate(yv);
                store_out(tile * 9 + 8, xr);
                prof(12 + job);
            }
        }
        if ((c.tid() & 31) == 0) asm volatile("cp.async.bulk.wait_group 0;" ::: "memory");
        prof(40);
        if (c.tid() == 0) g_epoch[v_bid()] = v_epoch() + 1;
    }
}

typedef CUresult (*EncodeFn)(CUtensorMap*, CUtensorMapDataType, cuuint32_t, void*, const cuuint64_t*, const cuuint64_t*,
                             const cuuint32_t*, const cuuint32_t*, CUtensorMapInterleave, CUtensorMapSwizzle,
                             CUtensorMapL2promotion, CUtensorMapFloatOOBfill);

void make_map(EncodeFn enc, CUtensorMap* tm, const void* base, int rows, int cols, int box_rows, int box_cols = 64) {
    cuuint64_t gdim[2] = {(cuuint64_t)cols, (cuuint64_t)rows};
    cuuint64_t gstr[1] = {(cuuint64_t)cols * 2};
    cuuint32_t box[2] = {(cuuint32_t)box_cols, (cuuint32_t)box_rows};
    cuuint32_t estr[2] = {1, 1};
    enc(tm, CU_TENSOR_MAP_DATA_TYPE_BFLOAT16, 2, const_cast<void*>(base), gdim, gstr, box, estr, CU_TENSOR_MAP_INTERLEAVE_NONE,
        CU_TENSOR_MAP_SWIZZLE_128B, CU_TENSOR_MAP_L2_PROMOTION_L2_128B, CU_TENSOR_MAP_FLOAT_OOB_FILL_NONE);
}

}

extern "C" void kernel_launch(void* const* d_in, const int* in_sizes, int n_in, void* d_out, int out_size) {
    static EncodeFn enc = nullptr;
    static void* o_ptr = nullptr;
    if (!enc) {
        void* fn = nullptr;
        cudaDriverEntryPointQueryResult qr;
        cudaGetDriverEntryPoint("cuTensorMapEncodeTiled", &fn, cudaEnableDefault, &qr);
        enc = (EncodeFn)fn;
        cudaGetSymbolAddress(&o_ptr, g_o);
        cudaFuncSetAttribute(fused_kernel, cudaFuncAttributeMaxDynamicSharedMemorySize, SMEM_BYTES);
    }
    Params p;
    p.x = (const __nv_bfloat16*)d_in[0];
    p.wqkv = (const __nv_bfloat16*)d_in[1];
    p.wo = (const __nv_bfloat16*)d_in[2];
    p.w1 = (const __nv_bfloat16*)d_in[4];
    p.b1 = (const __nv_bfloat16*)d_in[5];
    p.w2 = (const __nv_bfloat16*)d_in[6];
    p.b2 = (const __nv_bfloat16*)d_in[7];
    p.out = (__nv_bfloat16*)d_out;
    CUtensorMap tm_x, tm_w1, tm_w2, tm_wo, tm_o, tm_qkv, tm_qkve, tm_out;
    make_map(enc, &tm_out, p.out, SEQ, DM, 16);
    make_map(enc, &tm_qkv, p.wqkv, DM, 3 * DM, 96);
    make_map(enc, &tm_qkve, p.wqkv, DM, 3 * DM, 96, 8);
    make_map(enc, &tm_x, p.x, SEQ, DM, 128);
    make_map(enc, &tm_w1, p.w1, DM, FF, 192);
    make_map(enc, &tm_w2, p.w2, FF, DM, 192);
    make_map(enc, &tm_wo, p.wo, DM, DM, 192);
    make_map(enc, &tm_o, o_ptr, SEQ, DM, 128);
    fused_kernel<<<NMAIN + NAUX, 384, SMEM_BYTES>>>(tm_x, tm_w1, tm_w2, tm_wo, tm_o, tm_qkv, tm_qkve, tm_out, p);
}
```

```cpp
#include <cuda_runtime.h>
#include <cuda.h>
#include <cuda_bf16.h>
#include <stdint.h>

#define OSTEP_AT 4
#define KNOB_A 1
#define KNOB_B 0
#define PF1_NS 1000
#define PF2_NS 2000
#define PFIDX 3
#define PF3_NS 800
#define YF32 0

namespace {
constexpr int WAIT_ITERS = 3000000;

constexpr int SEQ = 2048, DM = 576, FF = 4608;
constexpr int NMAIN = 128, NAUX = 4;

constexpr uint32_t SB    = 0x400;
constexpr uint32_t HA    = SB;
constexpr uint32_t XB    = SB + 131072;
constexpr uint32_t RING  = SB + 147456;
constexpr uint32_t SLOT  = 24576;
constexpr uint32_t MISC  = SB + 221184;
constexpr uint32_t BARS  = MISC;
constexpr uint32_t B1S   = MISC + 512;
constexpr uint32_t B2S   = MISC + 2816;
constexpr uint32_t EPO   = MISC + 3072;
constexpr uint32_t EVC   = MISC + 3104;
constexpr uint32_t SMEM_BYTES = 221184 + 3200 + 512;
constexpr uint32_t PKT   = HA + 32768;
constexpr uint32_t VT    = HA + 51200;
constexpr uint32_t OST   = HA + 79872;
constexpr uint32_t PQT   = HA + 98304;
constexpr uint32_t KVB   = HA + 116736;

enum { B_FULL = 0, B_EMPTY = 3, B_XFULL = 6, B_OFULL = 9, B_O8FULL = 10, B_OFREE = 11, B_O8FREE = 12, B_KVB = 13, B_YRDY = 14, B_COUNT = 15 };
__device__ __forceinline__ constexpr uint32_t bar(int i) { return BARS + 8u * i; }

constexpr int YT_BYTES = YF32 ? 32768 : 16384;
__device__ __align__(1024) __nv_bfloat16 g_o[SEQ * DM];
__device__ __align__(1024) unsigned char g_yacc[2 * 16 * 9 * YT_BYTES];
__device__ __align__(128) float g_kv[2 * 8 * 72 * 20];
__device__ __align__(128) unsigned int g_s8[16 * 4096];
__device__ __align__(128) unsigned int g_cnt[(8 + 16 + 16 * 9) * 8];
__device__ unsigned int g_epoch[NMAIN + NAUX];
__device__ __forceinline__ unsigned int* cnt_kv(int j) { return g_cnt + j * 8; }
__device__ __forceinline__ unsigned int* cnt_o(int m) { return g_cnt + (8 + m) * 8; }
__device__ __forceinline__ unsigned int* cnt_y(int m, int c) { return g_cnt + (24 + m * 9 + c) * 8; }

__device__ __forceinline__ void mbar_init(uint32_t b, uint32_t cnt) { asm volatile("mbarrier.init.shared::cta.b64 [%0], %1;" :: "r"(b), "r"(cnt)); }
__device__ __forceinline__ void mbar_expect_tx(uint32_t b, uint32_t bytes) { asm volatile("mbarrier.arrive.expect_tx.shared::cta.b64 _, [%0], %1;" :: "r"(b), "r"(bytes) : "memory"); }
__device__ __forceinline__ void mbar_arrive(uint32_t b) { asm volatile("mbarrier.arrive.shared::cta.b64 _, [%0];" :: "r"(b) : "memory"); }
__device__ __forceinline__ void prof(int) {}
__device__ __forceinline__ void mbar_wait(uint32_t b, uint32_t parity) {
    asm volatile("{\n.reg .pred p;\n.reg .u32 c;\nmov.u32 c, 0;\n"
                 "WAIT_LOOP:\nmbarrier.try_wait.parity.shared::cta.b64 p, [%0], %1;\n@p bra WAIT_DONE;\n"
                 "add.u32 c, c, 1;\nsetp.lt.u32 p, c, 4000000;\n@p bra WAIT_LOOP;\ntrap;\nWAIT_DONE:\n}"
                 :: "r"(b), "r"(parity) : "memory");
}
__device__ __forceinline__ void smem_wait_gt(uint32_t addr, uint32_t val) {
    asm volatile("{\n.reg .pred p;\n.reg .u32 c, v;\nmov.u32 c, 0;\n"
                 "SW_LOOP:\nld.acquire.cta.shared.u32 v, [%0];\nsetp.gt.u32 p, v, %1;\n@p bra SW_DONE;\n"
                 "add.u32 c, c, 1;\nsetp.lt.u32 p, c, 100000000;\n@p bra SW_LOOP;\ntrap;\nSW_DONE:\n}"
                 :: "r"(addr), "r"(val) : "memory");
}
__device__ __forceinline__ void tma_2d(uint32_t dst, const CUtensorMap* tm, uint32_t b, int c0, int c1) {
    asm volatile("cp.async.bulk.tensor.2d.shared::cluster.global.mbarrier::complete_tx::bytes [%0], [%1, {%3, %4}], [%2];"
                 :: "r"(dst), "l"(tm), "r"(b), "r"(c0), "r"(c1) : "memory");
}
__device__ __forceinline__ void fence_async_smem() { asm volatile("fence.proxy.async.shared::cta;" ::: "memory"); }
__device__ __forceinline__ void fence_async_all() { asm volatile("fence.proxy.async;" ::: "memory"); }
__device__ __forceinline__ void named_bar(int id, int n) { asm volatile("bar.sync %0, %1;" :: "r"(id), "r"(n) : "memory"); }
__device__ __forceinline__ void wg_fence() { asm volatile("wgmma.fence.sync.aligned;" ::: "memory"); }
__device__ __forceinline__ void wg_commit() { asm volatile("wgmma.commit_group.sync.aligned;" ::: "memory"); }
template<int N> __device__ __forceinline__ void wg_wait() { asm volatile("wgmma.wait_group.sync.aligned %0;" :: "n"(N) : "memory"); }
template<int N> __device__ __forceinline__ void reg_fence(float* d) {
    #pragma unroll
    for (int i = 0; i < N; i++) asm volatile("" : "+f"(d[i]) :: "memory");
}
template<int N> __device__ __forceinline__ void reg_copy(float* d, const float* s) {
    #pragma unroll
    for (int i = 0; i < N; i++) asm volatile("mov.b32 %0, %1;" : "=f"(d[i]) : "f"(s[i]));
}
__device__ __forceinline__ uint32_t pack_bf16(float lo, float hi) { uint32_t r; asm("cvt.rn.bf16x2.f32 %0, %1, %2;" : "=r"(r) : "f"(hi), "f"(lo)); return r; }
__device__ __forceinline__ float bf_lo(uint32_t v) { return __uint_as_float(v << 16); }
__device__ __forceinline__ float bf_hi(uint32_t v) { return __uint_as_float(v & 0xffff0000u); }
__device__ __forceinline__ uint32_t sub_bf16x2(uint32_t a, uint32_t b) { uint32_t r; asm("sub.rn.bf16x2 %0, %1, %2;" : "=r"(r) : "r"(a), "r"(b)); return r; }
__device__ __forceinline__ float ex2(float x) { float r; asm("ex2.approx.ftz.f32 %0, %1;" : "=f"(r) : "f"(x)); return r; }
__device__ __forceinline__ float rcp(float x) { float r; asm("rcp.approx.ftz.f32 %0, %1;" : "=f"(r) : "f"(x)); return r; }
__device__ __forceinline__ float tanh_ap(float x) { float r; asm("tanh.approx.f32 %0, %1;" : "=f"(r) : "f"(x)); return r; }
__device__ __forceinline__ void sts32(uint32_t a, uint32_t v) { asm volatile("st.shared.b32 [%0], %1;" :: "r"(a), "r"(v)); }
__device__ __forceinline__ void sts128(uint32_t a, uint32_t x, uint32_t y, uint32_t z, uint32_t w) { asm volatile("st.shared.v4.b32 [%0], {%1,%2,%3,%4};" :: "r"(a), "r"(x), "r"(y), "r"(z), "r"(w)); }
__device__ __forceinline__ void sts64(uint32_t a, uint32_t x, uint32_t y) { asm volatile("st.shared.v2.b32 [%0], {%1,%2};" :: "r"(a), "r"(x), "r"(y)); }
__device__ __forceinline__ void lds64(uint32_t a, uint32_t* v) { asm volatile("ld.shared.v2.b32 {%0,%1}, [%2];" : "=r"(v[0]), "=r"(v[1]) : "r"(a)); }
__device__ __forceinline__ void lds128(uint32_t a, uint32_t* v) { asm volatile("ld.shared.v4.b32 {%0,%1,%2,%3}, [%4];" : "=r"(v[0]), "=r"(v[1]), "=r"(v[2]), "=r"(v[3]) : "r"(a) : "memory"); }
__device__ __forceinline__ float2 lds64f(uint32_t a) { float2 v; asm("ld.shared.v2.f32 {%0,%1}, [%2];" : "=f"(v.x), "=f"(v.y) : "r"(a)); return v; }
__device__ __forceinline__ void ldsm4(uint32_t a, uint32_t* v) {
    asm volatile("ldmatrix.sync.aligned.m8n8.x4.shared.b16 {%0,%1,%2,%3}, [%4];" : "=r"(v[0]), "=r"(v[1]), "=r"(v[2]), "=r"(v[3]) : "r"(a));
}
__device__ __forceinline__ void mma_ones(float* c, const uint32_t* a) {
    const uint32_t one2 = 0x3F803F80u;
    asm volatile("mma.sync.aligned.m16n8k16.row.col.f32.bf16.bf16.f32 {%0,%1,%2,%3}, {%4,%5,%6,%7}, {%8,%8}, {%0,%1,%2,%3};"
                 : "+f"(c[0]), "+f"(c[1]), "+f"(c[2]), "+f"(c[3]) : "r"(a[0]), "r"(a[1]), "r"(a[2]), "r"(a[3]), "r"(one2));
}
__device__ __forceinline__ unsigned int ld_acquire(const unsigned int* p) { unsigned int v; asm volatile("ld.acquire.gpu.global.u32 %0, [%1];" : "=r"(v) : "l"(p) : "memory"); return v; }
__device__ __forceinline__ void wait_cnt(const unsigned int* p, unsigned int target) {
    for (int i = 0; i < WAIT_ITERS; i++) {
        if ((int)(ld_acquire(p) - target) >= 0) return;
        __nanosleep(40);
    }
    __trap();
}
__device__ __forceinline__ uint32_t v_tid() { uint32_t r; asm volatile("mov.u32 %0, %%tid.x;" : "=r"(r)); return r; }
__device__ __forceinline__ uint32_t v_bid() { uint32_t r; asm volatile("mov.u32 %0, %%ctaid.x;" : "=r"(r)); return r; }
__device__ __forceinline__ uint32_t v_epoch() { uint32_t r; asm volatile("ld.shared.u32 %0, [%1];" : "=r"(r) : "r"(EPO)); return r; }
__device__ __forceinline__ void prefetch_l2(const void* p) { asm volatile("prefetch.global.L2 [%0];" :: "l"(p)); }

__host__ __device__ constexpr uint64_t mkdesc(uint32_t addr, uint32_t lbo, uint32_t sbo, uint32_t swz) {
    return (uint64_t)((addr & 0x3FFFF) >> 4) | ((uint64_t)((lbo >> 4) & 0x3FFF) << 16) | ((uint64_t)((sbo >> 4) & 0x3FFF) << 32) | ((uint64_t)swz << 62);
}

template<int SD> __device__ __forceinline__ void wg_rs64(float* d, const uint32_t* a, uint64_t bd) {
  if constexpr (SD) {
    asm volatile("{\n.reg .pred p;\nsetp.eq.b32 p, 0, 0;\n"
    "wgmma.mma_async.sync.aligned.m64n64k16.f32.bf16.bf16 {%0,%1,%2,%3,%4,%5,%6,%7,%8,%9,%10,%11,%12,%13,%14,%15,%16,%17,%18,%19,%20,%21,%22,%23,%24,%25,%26,%27,%28,%29,%30,%31}, {%32,%33,%34,%35}, %36, p, 1, 1, 1;\n}"
    : "+f"(d[0]),"+f"(d[1]),"+f"(d[2]),"+f"(d[3]),"+f"(d[4]),"+f"(d[5]),"+f"(d[6]),"+f"(d[7]),"+f"(d[8]),"+f"(d[9]),"+f"(d[10]),"+f"(d[11]),"+f"(d[12]),"+f"(d[13]),"+f"(d[14]),"+f"(d[15]),"+f"(d[16]),"+f"(d[17]),"+f"(d[18]),"+f"(d[19]),"+f"(d[20]),"+f"(d[21]),"+f"(d[22]),"+f"(d[23]),"+f"(d[24]),"+f"(d[25]),"+f"(d[26]),"+f"(d[27]),"+f"(d[28]),"+f"(d[29]),"+f"(d[30]),"+f"(d[31])
    : "r"(a[0]),"r"(a[1]),"r"(a[2]),"r"(a[3]), "l"(bd));
  } else {
    asm volatile("{\n.reg .pred p;\nsetp.ne.b32 p, 0, 0;\n"
    "wgmma.mma_async.sync.aligned.m64n64k16.f32.bf16.bf16 {%0,%1,%2,%3,%4,%5,%6,%7,%8,%9,%10,%11,%12,%13,%14,%15,%16,%17,%18,%19,%20,%21,%22,%23,%24,%25,%26,%27,%28,%29,%30,%31}, {%32,%33,%34,%35}, %36, p, 1, 1, 1;\n}"
    : "+f"(d[0]),"+f"(d[1]),"+f"(d[2]),"+f"(d[3]),"+f"(d[4]),"+f"(d[5]),"+f"(d[6]),"+f"(d[7]),"+f"(d[8]),"+f"(d[9]),"+f"(d[10]),"+f"(d[11]),"+f"(d[12]),"+f"(d[13]),"+f"(d[14]),"+f"(d[15]),"+f"(d[16]),"+f"(d[17]),"+f"(d[18]),"+f"(d[19]),"+f"(d[20]),"+f"(d[21]),"+f"(d[22]),"+f"(d[23]),"+f"(d[24]),"+f"(d[25]),"+f"(d[26]),"+f"(d[27]),"+f"(d[28]),"+f"(d[29]),"+f"(d[30]),"+f"(d[31])
    : "r"(a[0]),"r"(a[1]),"r"(a[2]),"r"(a[3]), "l"(bd));
  }
}
template<int SD> __device__ __forceinline__ void wg_ss64(float* d, uint64_t ad, uint64_t bd) {
  if constexpr (SD) {
    asm volatile("{\n.reg .pred p;\nsetp.eq.b32 p, 0, 0;\n"
    "wgmma.mma_async.sync.aligned.m64n64k16.f32.bf16.bf16 {%0,%1,%2,%3,%4,%5,%6,%7,%8,%9,%10,%11,%12,%13,%14,%15,%16,%17,%18,%19,%20,%21,%22,%23,%24,%25,%26,%27,%28,%29,%30,%31}, %32, %33, p, 1, 1, 0, 1;\n}"
    : "+f"(d[0]),"+f"(d[1]),"+f"(d[2]),"+f"(d[3]),"+f"(d[4]),"+f"(d[5]),"+f"(d[6]),"+f"(d[7]),"+f"(d[8]),"+f"(d[9]),"+f"(d[10]),"+f"(d[11]),"+f"(d[12]),"+f"(d[13]),"+f"(d[14]),"+f"(d[15]),"+f"(d[16]),"+f"(d[17]),"+f"(d[18]),"+f"(d[19]),"+f"(d[20]),"+f"(d[21]),"+f"(d[22]),"+f"(d[23]),"+f"(d[24]),"+f"(d[25]),"+f"(d[26]),"+f"(d[27]),"+f"(d[28]),"+f"(d[29]),"+f"(d[30]),"+f"(d[31])
    : "l"(ad), "l"(bd));
  } else {
    asm volatile("{\n.reg .pred p;\nsetp.ne.b32 p, 0, 0;\n"
    "wgmma.mma_async.sync.aligned.m64n64k16.f32.bf16.bf16 {%0,%1,%2,%3,%4,%5,%6,%7,%8,%9,%10,%11,%12,%13,%14,%15,%16,%17,%18,%19,%20,%21,%22,%23,%24,%25,%26,%27,%28,%29,%30,%31}, %32, %33, p, 1, 1, 0, 1;\n}"
    : "+f"(d[0]),"+f"(d[1]),"+f"(d[2]),"+f"(d[3]),"+f"(d[4]),"+f"(d[5]),"+f"(d[6]),"+f"(d[7]),"+f"(d[8]),"+f"(d[9]),"+f"(d[10]),"+f"(d[11]),"+f"(d[12]),"+f"(d[13]),"+f"(d[14]),"+f"(d[15]),"+f"(d[16]),"+f"(d[17]),"+f"(d[18]),"+f"(d[19]),"+f"(d[20]),"+f"(d[21]),"+f"(d[22]),"+f"(d[23]),"+f"(d[24]),"+f"(d[25]),"+f"(d[26]),"+f"(d[27]),"+f"(d[28]),"+f"(d[29]),"+f"(d[30]),"+f"(d[31])
    : "l"(ad), "l"(bd));
  }
}
template<int SD> __device__ __forceinline__ void wg_rs72(float* d, const uint32_t* a, uint64_t bd) {
  if constexpr (SD) {
    asm volatile("{\n.reg .pred p;\nsetp.eq.b32 p, 0, 0;\n"
    "wgmma.mma_async.sync.aligned.m64n72k16.f32.bf16.bf16 {%0,%1,%2,%3,%4,%5,%6,%7,%8,%9,%10,%11,%12,%13,%14,%15,%16,%17,%18,%19,%20,%21,%22,%23,%24,%25,%26,%27,%28,%29,%30,%31,%32,%33,%34,%35}, {%36,%37,%38,%39}, %40, p, 1, 1, 1;\n}"
    : "+f"(d[0]),"+f"(d[1]),"+f"(d[2]),"+f"(d[3]),"+f"(d[4]),"+f"(d[5]),"+f"(d[6]),"+f"(d[7]),"+f"(d[8]),"+f"(d[9]),"+f"(d[10]),"+f"(d[11]),"+f"(d[12]),"+f"(d[13]),"+f"(d[14]),"+f"(d[15]),"+f"(d[16]),"+f"(d[17]),"+f"(d[18]),"+f"(d[19]),"+f"(d[20]),"+f"(d[21]),"+f"(d[22]),"+f"(d[23]),"+f"(d[24]),"+f"(d[25]),"+f"(d[26]),"+f"(d[27]),"+f"(d[28]),"+f"(d[29]),"+f"(d[30]),"+f"(d[31]),"+f"(d[32]),"+f"(d[33]),"+f"(d[34]),"+f"(d[35])
    : "r"(a[0]),"r"(a[1]),"r"(a[2]),"r"(a[3]), "l"(bd));
  } else {
    asm volatile("{\n.reg .pred p;\nsetp.ne.b32 p, 0, 0;\n"
    "wgmma.mma_async.sync.aligned.m64n72k16.f32.bf16.bf16 {%0,%1,%2,%3,%4,%5,%6,%7,%8,%9,%10,%11,%12,%13,%14,%15,%16,%17,%18,%19,%20,%21,%22,%23,%24,%25,%26,%27,%28,%29,%30,%31,%32,%33,%34,%35}, {%36,%37,%38,%39}, %40, p, 1, 1, 1;\n}"
    : "+f"(d[0]),"+f"(d[1]),"+f"(d[2]),"+f"(d[3]),"+f"(d[4]),"+f"(d[5]),"+f"(d[6]),"+f"(d[7]),"+f"(d[8]),"+f"(d[9]),"+f"(d[10]),"+f"(d[11]),"+f"(d[12]),"+f"(d[13]),"+f"(d[14]),"+f"(d[15]),"+f"(d[16]),"+f"(d[17]),"+f"(d[18]),"+f"(d[19]),"+f"(d[20]),"+f"(d[21]),"+f"(d[22]),"+f"(d[23]),"+f"(d[24]),"+f"(d[25]),"+f"(d[26]),"+f"(d[27]),"+f"(d[28]),"+f"(d[29]),"+f"(d[30]),"+f"(d[31]),"+f"(d[32]),"+f"(d[33]),"+f"(d[34]),"+f"(d[35])
    : "r"(a[0]),"r"(a[1]),"r"(a[2]),"r"(a[3]), "l"(bd));
  }
}
template<int SD> __device__ __forceinline__ void wg_ss72(float* d, uint64_t ad, uint64_t bd) {
  if constexpr (SD) {
    asm volatile("{\n.reg .pred p;\nsetp.eq.b32 p, 0, 0;\n"
    "wgmma.mma_async.sync.aligned.m64n72k16.f32.bf16.bf16 {%0,%1,%2,%3,%4,%5,%6,%7,%8,%9,%10,%11,%12,%13,%14,%15,%16,%17,%18,%19,%20,%21,%22,%23,%24,%25,%26,%27,%28,%29,%30,%31,%32,%33,%34,%35}, %36, %37, p, 1, 1, 0, 1;\n}"
    : "+f"(d[0]),"+f"(d[1]),"+f"(d[2]),"+f"(d[3]),"+f"(d[4]),"+f"(d[5]),"+f"(d[6]),"+f"(d[7]),"+f"(d[8]),"+f"(d[9]),"+f"(d[10]),"+f"(d[11]),"+f"(d[12]),"+f"(d[13]),"+f"(d[14]),"+f"(d[15]),"+f"(d[16]),"+f"(d[17]),"+f"(d[18]),"+f"(d[19]),"+f"(d[20]),"+f"(d[21]),"+f"(d[22]),"+f"(d[23]),"+f"(d[24]),"+f"(d[25]),"+f"(d[26]),"+f"(d[27]),"+f"(d[28]),"+f"(d[29]),"+f"(d[30]),"+f"(d[31]),"+f"(d[32]),"+f"(d[33]),"+f"(d[34]),"+f"(d[35])
    : "l"(ad), "l"(bd));
  } else {
    asm volatile("{\n.reg .pred p;\nsetp.ne.b32 p, 0, 0;\n"
    "wgmma.mma_async.sync.aligned.m64n72k16.f32.bf16.bf16 {%0,%1,%2,%3,%4,%5,%6,%7,%8,%9,%10,%11,%12,%13,%14,%15,%16,%17,%18,%19,%20,%21,%22,%23,%24,%25,%26,%27,%28,%29,%30,%31,%32,%33,%34,%35}, %36, %37, p, 1, 1, 0, 1;\n}"
    : "+f"(d[0]),"+f"(d[1]),"+f"(d[2]),"+f"(d[3]),"+f"(d[4]),"+f"(d[5]),"+f"(d[6]),"+f"(d[7]),"+f"(d[8]),"+f"(d[9]),"+f"(d[10]),"+f"(d[11]),"+f"(d[12]),"+f"(d[13]),"+f"(d[14]),"+f"(d[15]),"+f"(d[16]),"+f"(d[17]),"+f"(d[18]),"+f"(d[19]),"+f"(d[20]),"+f"(d[21]),"+f"(d[22]),"+f"(d[23]),"+f"(d[24]),"+f"(d[25]),"+f"(d[26]),"+f"(d[27]),"+f"(d[28]),"+f"(d[29]),"+f"(d[30]),"+f"(d[31]),"+f"(d[32]),"+f"(d[33]),"+f"(d[34]),"+f"(d[35])
    : "l"(ad), "l"(bd));
  }
}
template<int SD> __device__ __forceinline__ void wg_tt64(float* d, uint64_t ad, uint64_t bd) {
  if constexpr (SD) {
    asm volatile("{\n.reg .pred p;\nsetp.eq.b32 p, 0, 0;\n"
    "wgmma.mma_async.sync.aligned.m64n64k16.f32.bf16.bf16 {%0,%1,%2,%3,%4,%5,%6,%7,%8,%9,%10,%11,%12,%13,%14,%15,%16,%17,%18,%19,%20,%21,%22,%23,%24,%25,%26,%27,%28,%29,%30,%31}, %32, %33, p, 1, 1, 1, 1;\n}"
    : "+f"(d[0]),"+f"(d[1]),"+f"(d[2]),"+f"(d[3]),"+f"(d[4]),"+f"(d[5]),"+f"(d[6]),"+f"(d[7]),"+f"(d[8]),"+f"(d[9]),"+f"(d[10]),"+f"(d[11]),"+f"(d[12]),"+f"(d[13]),"+f"(d[14]),"+f"(d[15]),"+f"(d[16]),"+f"(d[17]),"+f"(d[18]),"+f"(d[19]),"+f"(d[20]),"+f"(d[21]),"+f"(d[22]),"+f"(d[23]),"+f"(d[24]),"+f"(d[25]),"+f"(d[26]),"+f"(d[27]),"+f"(d[28]),"+f"(d[29]),"+f"(d[30]),"+f"(d[31])
    : "l"(ad), "l"(bd));
  } else {
    asm volatile("{\n.reg .pred p;\nsetp.ne.b32 p, 0, 0;\n"
    "wgmma.mma_async.sync.aligned.m64n64k16.f32.bf16.bf16 {%0,%1,%2,%3,%4,%5,%6,%7,%8,%9,%10,%11,%12,%13,%14,%15,%16,%17,%18,%19,%20,%21,%22,%23,%24,%25,%26,%27,%28,%29,%30,%31}, %32, %33, p, 1, 1, 1, 1;\n}"
    : "+f"(d[0]),"+f"(d[1]),"+f"(d[2]),"+f"(d[3]),"+f"(d[4]),"+f"(d[5]),"+f"(d[6]),"+f"(d[7]),"+f"(d[8]),"+f"(d[9]),"+f"(d[10]),"+f"(d[11]),"+f"(d[12]),"+f"(d[13]),"+f"(d[14]),"+f"(d[15]),"+f"(d[16]),"+f"(d[17]),"+f"(d[18]),"+f"(d[19]),"+f"(d[20]),"+f"(d[21]),"+f"(d[22]),"+f"(d[23]),"+f"(d[24]),"+f"(d[25]),"+f"(d[26]),"+f"(d[27]),"+f"(d[28]),"+f"(d[29]),"+f"(d[30]),"+f"(d[31])
    : "l"(ad), "l"(bd));
  }
}

template<int V> struct IC { static constexpr int v = V; };
template<int I, int N, class F> __device__ __forceinline__ void sfor(F&& f) {
    if constexpr (I < N) { f(IC<I>{}); sfor<I + 1, N>(f); }
}

enum { K_QKV = 0, K_H = 1 };

struct Ctx {
    uint32_t tph;
    uint32_t tid_;
    bool pf = false;
    __device__ __forceinline__ uint32_t tid() const { uint32_t r; asm volatile("mov.u32 %0, %1;" : "=r"(r) : "r"(tid_)); return r; }
};
__device__ __forceinline__ void release_slot(const Ctx& c, int slot) { if ((c.tid() & 31) == 0) mbar_arrive(bar(B_EMPTY + slot)); }

__device__ __forceinline__ void turn_wait(const Ctx& c) { asm volatile("bar.sync %0, 256;" :: "r"(4 + (c.tid() >> 7)) : "memory"); }
__device__ __forceinline__ void turn_pass(const Ctx& c) { asm volatile("bar.arrive %0, 256;" :: "r"(5 - (c.tid() >> 7)) : "memory"); }

template<int KIND, class PART, class POST>
__device__ __forceinline__ void run_step(Ctx& c, float* acc, const uint32_t* a, PART&& part, POST&& post, bool last = false) {
    constexpr int NST = (KIND == K_QKV) ? 6 : 3;
    constexpr int KPS = 36 / NST;
    sfor<0, NST>([&](auto ST) {
        constexpr int st = decltype(ST)::v;
        constexpr int slot = st % 3;
        mbar_wait(bar(B_FULL + slot), c.tph);
        uint32_t wgo = 0;
        if constexpr (st == NST - 1) wgo = (c.tid() >> 7) * 512;
        if (KIND == K_H && c.pf) prof(44 + st * 5);
        turn_wait(c);
        if (KIND == K_H && c.pf) prof(45 + st * 5);
        wg_fence();
        sfor<0, KPS>([&](auto KK) {
            constexpr int kk = decltype(KK)::v;
            constexpr int ks = st * KPS + kk;
            constexpr int SD = ks ? 1 : 0;
            if constexpr (KIND == K_QKV) {
                constexpr uint64_t bd = mkdesc(RING + slot * SLOT + kk * 2048, 12288, 1024, 1);
                if constexpr (ks < 32) wg_rs72<SD>(acc, a + ks * 4, bd);
                else wg_ss72<SD>(acc, mkdesc(XB + (ks - 32) * 32, 16, 1024, 1) + wgo, bd);
            } else {
                constexpr uint64_t bd = mkdesc(RING + slot * SLOT + kk * 2048, 16, 1024, 1);
                if constexpr (ks < 32) wg_rs64<SD>(acc, a + ks * 4, bd);
                else wg_ss64<SD>(acc, mkdesc(XB + (ks - 32) * 32, 16, 1024, 1) + wgo, bd);
            }
        });
        wg_commit();
        if (st < NST - 1 || !last || c.tid() < 128) turn_pass(c);
        if (KIND == K_H && c.pf) prof(46 + st * 5);
        part(ST);
        if (KIND == K_H && c.pf) prof(47 + st * 5);
        wg_wait<0>();
        if (KIND == K_H && c.pf) prof(48 + st * 5);
        release_slot(c, slot);
        if constexpr (slot == 2) c.tph ^= 1;
        post(ST);
    });
    if constexpr (KIND == K_QKV) reg_fence<36>(acc); else reg_fence<32>(acc);
}

__device__ __forceinline__ float phi(float t) {
    float e = ex2(t * 1.4426950408889634f);
    return (t > 0.f ? t + 1.0f : e) + 1e-6f;
}
__device__ __forceinline__ float gelu_h(float hx) {
    float u = hx * fmaf(hx * hx, 0.2854192650f, 1.5957691216f);
    return fmaf(hx, tanh_ap(u), hx);
}

struct Params {
    const __nv_bfloat16* x;
    const __nv_bfloat16* wqkv;
    const __nv_bfloat16* wo;
    const __nv_bfloat16* w1;
    const __nv_bfloat16* b1;
    const __nv_bfloat16* w2;
    const __nv_bfloat16* b2;
    __nv_bfloat16* out;
};

__global__ void __launch_bounds__(384, 1)
fused_kernel(const __grid_constant__ CUtensorMap tm_x, const __grid_constant__ CUtensorMap tm_w1,
             const __grid_constant__ CUtensorMap tm_w2, const __grid_constant__ CUtensorMap tm_wo,
             const __grid_constant__ CUtensorMap tm_o, const __grid_constant__ CUtensorMap tm_qkv,
             const __grid_constant__ CUtensorMap tm_qkve, const __grid_constant__ CUtensorMap tm_out,
             const __grid_constant__ CUtensorMap tm_ost, const Params p) {
    extern __shared__ __align__(1024) unsigned char smem_raw[];
    const int tid = threadIdx.x;
    const int bid = blockIdx.x;
    const bool is_main = bid < NMAIN;
    const int j = bid & 7;
    const int m = bid >> 3;

    if (tid == 0) {
        if ((uint32_t)__cvta_generic_to_shared(smem_raw) != SB) __trap();
        for (int i = 0; i < 3; i++) {
            mbar_init(bar(B_FULL + i), 1); mbar_init(bar(B_EMPTY + i), 8);
            mbar_init(bar(B_XFULL + i), 1);
        }
        mbar_init(bar(B_KVB), 2);
        mbar_init(bar(B_OFULL), 1); mbar_init(bar(B_O8FULL), 1); mbar_init(bar(B_OFREE), 8); mbar_init(bar(B_O8FREE), 8);
        asm volatile("fence.mbarrier_init.release.cluster;" ::: "memory");
        if (is_main) {
            for (int g = 0; g < 3; g++) {
                mbar_expect_tx(bar(B_XFULL + g), 49152);
                for (int kb = 3 * g; kb < 3 * g + 3; kb++) tma_2d(HA + kb * 16384, &tm_x, bar(B_XFULL + g), kb * 64, m * 128);
            }
            for (int st = 0; st < 3; st++) {
                mbar_expect_tx(bar(B_FULL + st), 96 * 144);
                tma_2d(RING + st * SLOT, &tm_qkv, bar(B_FULL + st), 576 + j * 72, st * 96);
                tma_2d(RING + st * SLOT + 12288, &tm_qkve, bar(B_FULL + st), 576 + j * 72 + 64, st * 96);
            }
        }
    }
    if (tid == 32) { sts32(EPO, g_epoch[bid]); sts32(EPO + 4, 0); }
    if (tid >= 40 && tid < 48) sts32(EVC + (tid - 40) * 4, 0);
    if (tid >= 64 && tid < 64 + 288 && is_main) {
        int i = tid - 64;
        uint32_t v = *reinterpret_cast<const uint32_t*>(p.b1 + j * 576 + 2 * i);
        sts32(B1S + 8 * i, __float_as_uint(0.5f * bf_lo(v))); sts32(B1S + 8 * i + 4, __float_as_uint(0.5f * bf_hi(v)));
    }
    if (tid >= 352) {
        int i = tid - 352;
        uint32_t v = *reinterpret_cast<const uint32_t*>(p.b2 + (is_main ? j : 8) * 64 + 2 * i);
        sts32(B2S + 8 * i, v << 16); sts32(B2S + 8 * i + 4, v & 0xffff0000u);
    }
    fence_async_smem();
    __syncthreads();
    uint32_t epoch;
    asm volatile("ld.shared.u32 %0, [%1];" : "=r"(epoch) : "r"(EPO));
    const uint32_t par = epoch & 1;

    if (tid >= 256) {
        asm volatile("setmaxnreg.dec.sync.aligned.u32 24;");
        const int hw = (tid >> 5) - 8, lane = tid & 31;
        if (hw == 0) {
            if (lane == 0) {
                uint32_t n = 0;
                if (is_main) {
                    n = 1;
                    #pragma unroll 1
                    for (int u = 3; u < 18; u++) {
                        const int st = u % 3, step = u / 6;
                        const int col = ((step == 2) ? 0 : (step + 1) * 576) + j * 72, row = (u % 6) * 96;
                        mbar_wait(bar(B_EMPTY + st), (n & 1) ^ 1);
                        mbar_expect_tx(bar(B_FULL + st), 96 * 144);
                        tma_2d(RING + st * SLOT, &tm_qkv, bar(B_FULL + st), col, row);
                        tma_2d(RING + st * SLOT + 12288, &tm_qkve, bar(B_FULL + st), col + 64, row);
                        if (st == 2) n++;
                    }
                }
                const int nsteps = is_main ? 19 : 1;
                #pragma unroll 1
                for (int s = 0; s < nsteps; s++, n++) {
                    const CUtensorMap* tm; int col, row;
                    if (!is_main) { tm = &tm_wo; col = 512; row = 0; }
                    else if (s < 9) { tm = &tm_w1; col = j * 576 + s * 64; row = 0; }
                    else if (s < 18) { tm = &tm_w2; col = (s == 9) ? 512 : (((j + s - 9) & 7) * 64); row = j * 576; }
                    else { tm = &tm_wo; col = j * 64; row = 0; }
                    #pragma unroll 1
                    for (int st = 0; st < 3; st++) {
                        mbar_wait(bar(B_EMPTY + st), (n & 1) ^ 1);
                        mbar_expect_tx(bar(B_FULL + st), SLOT);
                        tma_2d(RING + st * SLOT, tm, bar(B_FULL + st), col, row + st * 192);
                    }
                }
            }
        } else {
            if (is_main) {
                const int t = tid - 288;
                #pragma unroll 1
                for (int i = t; i < 36 * 6; i += 96) {
                    int r = i / 6, q = i - r * 6;
                    prefetch_l2(reinterpret_cast<const char*>(p.wqkv) + (36 * m + r) * 3456 + (q >> 1) * 1152 + j * 144 + (q & 1) * 128);
                }
                __nanosleep(PF1_NS);
                #pragma unroll 1
                for (int i = t; i < 36 * 9; i += 96) {
                    int r = i / 9, q = i - r * 9;
                    prefetch_l2(reinterpret_cast<const char*>(p.w1) + (36 * m + r) * 9216 + j * 1152 + q * 128);
                    __nanosleep(PF3_NS);
                }
                __nanosleep(PF2_NS);
                #pragma unroll 1
                for (int i = t; i < 36 * 9; i += 96)
                    prefetch_l2(reinterpret_cast<const char*>(p.w2) + (576 * j + 36 * m) * 1152 + i * 128);
                if (t < 41 && (bid * 41 + t) < 5184) prefetch_l2(reinterpret_cast<const char*>(p.wo) + (bid * 41 + t) * 128);
                if (hw != 2) {
                    if (lane == 0) wait_cnt(cnt_kv(j), (epoch + 1) * 16);
                    __syncwarp();
                    const float4* kv = reinterpret_cast<const float4*>(g_kv + (par * 8 + j) * 1440);
                    #pragma unroll 2
                    for (int i = lane + (hw == 1 ? 0 : 32); i < 360; i += 64) {
                        const float4 v = __ldcg(kv + i);
                        const int d = i / 5, e = (i - d * 5) * 4, h = d / 18;
                        const uint32_t base = KVB + (d >> 3) * 128 + (d & 7) * 16;
                        const int n0 = 8 + h * 18 + e;
                        sts32(base + (n0 >> 3) * 1280 + (n0 & 7) * 2, pack_bf16(v.x, v.y));
                        if (e < 16) sts32(base + ((n0 + 2) >> 3) * 1280 + ((n0 + 2) & 7) * 2, pack_bf16(v.z, v.w));
                        else asm volatile("st.shared.u16 [%0], %1;" :: "r"(base + h * 2), "h"((unsigned short)pack_bf16(v.z, 0.f)) : "memory");
                    }
                    fence_async_smem();
                    __syncwarp();
                    if (lane == 0) mbar_arrive(bar(B_KVB));
                }
            }
            if (hw == 1) {
                if (lane == 0) {
                    const int nit = is_main ? 1 : 4;
                    for (int it = 0; it < nit; it++) {
                        const int mt = is_main ? m : ((bid - NMAIN) * 4 + it);
                        const bool wf = is_main || it > 0;
                        const uint32_t fp = is_main ? 0 : ((it - 1) & 1);
                        wait_cnt(cnt_o(mt), (epoch + 1) * 8);
                        fence_async_all();
                        if (wf) mbar_wait(bar(B_OFREE), fp);
                        mbar_expect_tx(bar(B_OFULL), 131072);
                        #pragma unroll 1
                        for (int kb = 0; kb < 8; kb++) tma_2d(HA + kb * 16384, &tm_o, bar(B_OFULL), kb * 64, mt * 128);
                        if (wf) mbar_wait(bar(B_O8FREE), fp);
                        mbar_expect_tx(bar(B_O8FULL), 16384);
                        tma_2d(XB, &tm_o, bar(B_O8FULL), 512, mt * 128);
                    }
                    if (is_main) { wait_cnt(cnt_y(m, j), (epoch + 1) * 7); asm volatile("st.release.cta.shared.u32 [%0], %1;" :: "r"(EPO + 4), "r"(1) : "memory"); }
                }
            } else if (hw == 2) {
                if (!is_main) {
                    if (lane == 0) {
                        #pragma unroll 1
                        for (int it = 0; it < 4; it++) {
                            wait_cnt(cnt_y((bid - NMAIN) * 4 + it, 8), (epoch + 1) * 8);
                            asm volatile("st.release.cta.shared.u32 [%0], %1;" :: "r"(EPO + 4), "r"(it + 1) : "memory");
                        }
                    }
                } else {
                    #pragma unroll 1
                    for (int e = 0; e < 10; e++) {
                        int spin = 0;
                        while (true) {
                            uint32_t v;
                            asm volatile("ld.acquire.cta.shared.u32 %0, [%1];" : "=r"(v) : "r"(EVC + (lane & 7) * 4) : "memory");
                            if (__all_sync(0xffffffffu, v > (uint32_t)e)) break;
                            if (++spin > 20000000) __trap();
                            __nanosleep(20);
                        }
                        if (lane == 0) {
                            unsigned int* cp = (e == 0) ? cnt_kv(j) : (e == 1) ? cnt_o(m) : cnt_y(m, e == 2 ? 8 : ((j + e - 2) & 7));
                            if (e == 1) fence_async_all();
                            __threadfence();
                            asm volatile("red.relaxed.gpu.global.add.u32 [%0], 1;" :: "l"(cp) : "memory");
                        }
                        __syncwarp();
                    }
                }
            } else {
                {
                    const int t0 = is_main ? (m * 9 + j) : ((bid - NMAIN) * 4 * 9 + 8);
                    const int nt = is_main ? 1 : 4;
                    for (int t = 0; t < nt; t++) {
                        uint4* z = reinterpret_cast<uint4*>(g_yacc + (size_t)((par ^ 1) * 144 + t0 + t * 9) * YT_BYTES);
                        for (int i = lane; i < YT_BYTES / 16; i += 32) z[i] = make_uint4(0, 0, 0, 0);
                    }
                    if (is_main && m == 0) {
                        float* z = g_kv + ((par ^ 1) * 8 + j) * 1440;
                        for (int i = lane; i < 1440; i += 32) z[i] = 0.f;
                    }
                }
            }
        }
    } else {
        asm volatile("setmaxnreg.inc.sync.aligned.u32 240;");
        prof(0);
        Ctx c; c.tph = 0; c.tid_ = v_tid();
        float hc[32], pv[36];
        if (tid >> 7) turn_pass(c);
        auto event = [&](uint32_t ev) {
            __syncwarp();
            if (((c.tid() & 31) == 0)) asm volatile("st.release.cta.shared.u32 [%0], %1;" :: "r"(EVC + (c.tid() >> 3)), "r"(ev) : "memory");
        };
        auto warp_arrive = [&](uint32_t b) { __syncwarp(); if (((c.tid() & 31) == 0)) mbar_arrive(b); };

        auto lrow_off = [&]() { uint32_t t_ = c.tid(); return HA + ((t_ >> 5) * 16 + (t_ & 15)) * 128 + ((((t_ >> 4) & 1) ^ (t_ & 7)) << 4); };
        auto tail_off = [&]() { uint32_t t_ = c.tid(), g = (t_ >> 2) & 7; return XB + ((t_ >> 5) * 16 + g) * 128 + (g << 4) + (t_ & 3) * 4; };
        if (is_main) {
            uint32_t a[128];
            float rs0, rs1;
            uint32_t m00, m11;
            {
                uint32_t tl[16];
                const uint32_t lrow = lrow_off();
                float cs[2][4] = {{0.f, 0.f, 0.f, 0.f}, {0.f, 0.f, 0.f, 0.f}};
                sfor<0, 36>([&](auto KS) {
                    constexpr int ks = decltype(KS)::v;
                    if constexpr (ks % 12 == 0) mbar_wait(bar(B_XFULL + ks / 12), 0);
                    uint32_t* dst = (ks < 32) ? (a + (ks & 31) * 4) : (tl + (ks & 3) * 4);
                    ldsm4((lrow ^ ((ks % 4) << 5)) + (ks / 4) * 16384, dst);
                    mma_ones(cs[ks & 1], dst);
                });
                prof(2);
                float mean0 = (cs[0][0] + cs[1][0]) * (1.0f / 576.0f), mean1 = (cs[0][2] + cs[1][2]) * (1.0f / 576.0f);
                m00 = pack_bf16(mean0, mean0); m11 = pack_bf16(mean1, mean1);
                rs0 = mean0 - bf_lo(m00); rs1 = mean1 - bf_lo(m11);
                rs0 = -144.0f * rs0 * rs0; rs1 = -144.0f * rs1 * rs1;
                const uint32_t tb = tail_off();
                #pragma unroll
                for (int i = 0; i < 16; i++) {
                    const uint32_t w = sub_bf16x2(tl[i], (i & 1) ? m11 : m00);
                    sts32((tb ^ ((i >> 1) << 4)) + (i & 1) * 1024, w);
                    float lo = bf_lo(w), hi = bf_hi(w);
                    if (i & 1) rs1 = fmaf(lo, lo, fmaf(hi, hi, rs1)); else rs0 = fmaf(lo, lo, fmaf(hi, hi, rs0));
                }
                fence_async_smem();
                #pragma unroll
                for (int i = 0; i < 128; i++) a[i] = sub_bf16x2(a[i], (i & 1) ? m11 : m00);
                named_bar(2 + (tid >> 7), 128);
            }
            prof(3);
            auto cm_off = [&]() { uint32_t t_ = c.tid(); return (t_ >> 5) * 256 + (t_ & 31) * 4; };
            {
                float qc[36];
                #pragma unroll
                for (int i = 0; i < 36; i++) { qc[i] = 0.f; pv[i] = 0.f; }
                #pragma unroll 1
                for (int s = 0; s < 3; s++) {
                    run_step<K_QKV>(c, qc, a, [&](auto ST) {
                        constexpr int st = decltype(ST)::v;
                        if (s == 0) {
                            const uint32_t lrow = lrow_off();
                            sfor<(st * 32) / 6, ((st + 1) * 32) / 6>([&](auto I) {
                                constexpr int ks = decltype(I)::v;
                                uint32_t v[4];
                                ldsm4((lrow ^ ((ks % 4) << 5)) + (ks / 4) * 16384, v);
                                #pragma unroll
                                for (int r = 0; r < 4; r++) {
                                    uint32_t w = sub_bf16x2(v[r], (r & 1) ? m11 : m00);
                                    float lo = bf_lo(w), hi = bf_hi(w);
                                    if (r & 1) rs1 = fmaf(lo, lo, fmaf(hi, hi, rs1)); else rs0 = fmaf(lo, lo, fmaf(hi, hi, rs0));
                                }
                            });
                            if constexpr (st == 5) {
                                rs0 += __shfl_xor_sync(0xffffffffu, rs0, 1); rs1 += __shfl_xor_sync(0xffffffffu, rs1, 1);
                                rs0 += __shfl_xor_sync(0xffffffffu, rs0, 2); rs1 += __shfl_xor_sync(0xffffffffu, rs1, 2);
                                rs0 = rsqrtf(fmaxf(rs0 * (1.0f / 576.0f), 0.f) + 1e-5f);
                                rs1 = rsqrtf(fmaxf(rs1 * (1.0f / 576.0f), 0.f) + 1e-5f);
                                named_bar(1, 256);
                            }
                        } else {
                            const uint32_t cm = cm_off();
                            sfor<0, 9>([&](auto B) {
                                constexpr int b = decltype(B)::v;
                                if constexpr ((b * 6) / 9 == st) {
                                    const float v0 = pv[4 * b] * rs0, v1 = pv[4 * b + 1] * rs0, v2 = pv[4 * b + 2] * rs1, v3 = pv[4 * b + 3] * rs1;
                                    if (s == 1) {
                                        sts32(PKT + b * 2048 + cm, pack_bf16(phi(v0), phi(v1)));
                                        sts32(PKT + b * 2048 + cm + 128, pack_bf16(phi(v2), phi(v3)));
                                    } else {
                                        const uint32_t w0 = pack_bf16(v0, v1), w1 = pack_bf16(v2, v3);
                                        if constexpr (b <= 4) { sts32(VT + b * 2048 + cm, w0); sts32(VT + b * 2048 + cm + 128, w1); }
                                        if constexpr (b >= 4) { sts32(VT + (b + 2) * 2048 + cm, w0); sts32(VT + (b + 2) * 2048 + cm + 128, w1); }
                                        if constexpr (b == 0) {
                                            const uint32_t one = (cm & 12) ? 0u : 0x00003F80u;
                                            sts32(VT + 5 * 2048 + cm, one); sts32(VT + 5 * 2048 + cm + 128, one);
                                        }
                                        if constexpr (b == 8) {
                                            const uint32_t z = KVB + c.tid() * 16;
                                            sts128(z, 0, 0, 0, 0); sts128(z + 4096, 0, 0, 0, 0); sts128(z + 8192, 0, 0, 0, 0);
                                            if (z < KVB + 512) sts128(z + 12288, 0, 0, 0, 0);
                                            fence_async_smem();
                                        }
                                    }
                                }
                            });
                        }
                    }, [](auto) {});
                    reg_copy<36>(pv, qc);
                    prof(4 + s);
                }
            }
            {
                #pragma unroll
                for (int i = 0; i < 32; i++) hc[i] = 0.f;
                named_bar(1, 256);
                const uint32_t wgo = ((c.tid() >> 7) * 512);
                wg_fence();
                sfor<0, 8>([&](auto KS) {
                    constexpr int ks = decltype(KS)::v;
                    wg_tt64<(ks ? 1 : 0)>(hc, mkdesc(PKT + ks * 256, 128, 2048, 0) + wgo,
                                          mkdesc(VT + ks * 256, 128, 2048, 0) + wgo + (wgo >> 2));
                });
                wg_commit();
                const uint32_t pq = PQT + cm_off() + ((c.tid() >> 7) * 512) * 16;
                sfor<0, 9>([&](auto B) {
                    constexpr int b = decltype(B)::v;
                    sts32(pq + b * 1024, pack_bf16(phi(pv[4 * b] * rs0), phi(pv[4 * b + 1] * rs0)));
                    sts32(pq + b * 1024 + 128, pack_bf16(phi(pv[4 * b + 2] * rs1), phi(pv[4 * b + 3] * rs1)));
                });
                fence_async_smem();
                wg_wait<0>();
                reg_fence<32>(hc);
                reg_copy<24>(pv, hc);
            }
            prof(7);
            rs0 *= 0.5f; rs1 *= 0.5f;
            auto gelun = [&](auto B0, auto B1, uint32_t bofs, uint32_t* w) {
                constexpr int b0 = decltype(B0)::v, nb = decltype(B1)::v - b0;
                float2 bv[nb];
                #pragma unroll
                for (int i = 0; i < nb; i++) bv[i] = lds64f(bofs + (b0 + i) * 32);
                #pragma unroll
                for (int i = 0; i < nb; i++) {
                    const int b = b0 + i;
                    w[2 * i]     = pack_bf16(gelu_h(fmaf(pv[4 * b], rs0, bv[i].x)), gelu_h(fmaf(pv[4 * b + 1], rs0, bv[i].y)));
                    w[2 * i + 1] = pack_bf16(gelu_h(fmaf(pv[4 * b + 2], rs1, bv[i].x)), gelu_h(fmaf(pv[4 * b + 3], rs1, bv[i].y)));
                }
            };
            auto spill_off = [&]() { uint32_t t_ = c.tid(); return HA + (t_ >> 7) * 8192 + (t_ & 127) * 8; };
            auto reload = [&](auto S0, auto S1) {
                const uint32_t spill = spill_off();
                sfor<decltype(S0)::v * 8, decltype(S1)::v * 8>([&](auto Q) {
                    constexpr int q = decltype(Q)::v;
                    lds64(spill + (q / 8) * 16384 + (q % 8) * 1024, a + q * 2);
                });
            };
            #pragma unroll 1
            for (int idx = 0; idx < 18; idx++) {
                run_step<K_H>(c, hc, a, [&](auto ST) {
                    constexpr int st = decltype(ST)::v;
                    if (idx >= 10) {
                        if constexpr (st < 2) {
                            const uint32_t b_ = v_bid();
                            const uint32_t chunk = (idx == 10) ? 8 : ((b_ + idx - 10) & 7);
                            unsigned char* yp = g_yacc + ((v_epoch() & 1) * 144 + (b_ >> 3) * 9 + chunk) * YT_BYTES + c.tid() * 16;
                            sfor<2 * st, 2 * st + 2>([&](auto Q) {
                                constexpr int q = decltype(Q)::v;
                                asm volatile("red.global.add.noftz.v4.bf16x2 [%0], {%1,%2,%3,%4};" :: "l"(yp + q * 4096),
                                             "r"(pack_bf16(pv[8 * q], pv[8 * q + 1])), "r"(pack_bf16(pv[8 * q + 2], pv[8 * q + 3])),
                                             "r"(pack_bf16(pv[8 * q + 4], pv[8 * q + 5])), "r"(pack_bf16(pv[8 * q + 6], pv[8 * q + 7])) : "memory");
                            });
                            if constexpr (st == 1) event(idx - 7);
                        }
                    } else if (idx >= 1) {
                        const uint32_t bofs = B1S + (idx - 1) * 256 + (c.tid() & 3) * 8;
                        if (idx < 9) {
                            if constexpr (st == 0) {
                                if (idx == OSTEP_AT + 1) {
                                    if ((c.tid() & 31) == 0) asm volatile("cp.async.bulk.wait_group 0;" ::: "memory");
                                    event(2);
                                }
                            }
                            const uint32_t spill = spill_off() + (idx - 1) * 16384;
                            constexpr int b0 = st * 3, b1 = (st == 2 ? 8 : st * 3 + 3);
                            uint32_t w[6];
                            gelun(IC<b0>{}, IC<b1>{}, bofs, w);
                            #pragma unroll
                            for (int b = b0; b < b1; b++) sts64(spill + b * 1024, w[2 * (b - b0)], w[2 * (b - b0) + 1]);
                        } else {
                            if constexpr (st < 2) {
                                const uint32_t tb = tail_off();
                                uint32_t w[8];
                                gelun(IC<st * 4>{}, IC<st * 4 + 4>{}, bofs, w);
                                #pragma unroll
                                for (int i = 0; i < 4; i++) { sts32(tb ^ ((st * 4 + i) << 4), w[2 * i]); sts32((tb ^ ((st * 4 + i) << 4)) + 1024, w[2 * i + 1]); }
                            }
                            if constexpr (st == 1) { fence_async_smem(); named_bar(2 + (c.tid() >> 7), 128); }
                        }
                    } else {
                        if constexpr (st < 2) {
                            constexpr int hf = st;
                            const int t_ = c.tid(), wg = t_ >> 7, t = t_ & 3;
                            float* dst = g_kv + ((v_epoch() & 1) * 8 + (v_bid() & 7)) * 1440;
                            const int d = wg * 32 + ((t_ >> 5) & 3) * 16 + ((t_ >> 2) & 7) + hf * 8;
                            const bool dv = wg ? (d >= 36 && d < 72) : (d < 36);
                            const int e00 = wg * 24 + 2 * t - (d / 18) * 18;
                            float* dp = dst + d * 20 + e00;
                            #pragma unroll
                            for (int i = 0; i < 6; i++) {
                                const int e = e00 + i * 8;
                                const bool blk = wg ? (i >= 1) : (i <= 4);
                                if (dv && blk && e >= 0 && e < 18)
                                    asm volatile("red.global.add.v2.f32 [%0], {%1,%2};" :: "l"(dp + i * 8), "f"(pv[4 * i + 2 * hf]), "f"(pv[4 * i + 2 * hf + 1]) : "memory");
                            }
                            if (dv && t == 0) atomicAdd(dst + d * 20 + 18, wg ? pv[2 * hf] : pv[20 + 2 * hf]);
                            if constexpr (st == 1) event(1);
                        }
                    }
                }, [&](auto ST) {
                    constexpr int st = decltype(ST)::v;
                    if (idx == 8) {
                        reload(IC<3 * st>{}, IC<(st == 2 ? 8 : 3 * st + 3)>{});
                        if constexpr (st == 2) warp_arrive(bar(B_OFREE));
                    }
                });
                reg_copy<32>(pv, hc);
                prof(8 + idx);
                if (idx == OSTEP_AT) {
                    mbar_wait(bar(B_KVB), 0);
                    prof(34);
                    const uint32_t pqo = (c.tid() >> 7) * 576;
                    const int t_ = c.tid(), b_ = v_bid(), t = t_ & 3, l4 = t_ & 28;
                    const uint32_t op = OST + ((t_ >> 5) * 16 + ((t_ >> 2) & 7)) * 144 + t * 4;
                    float r3[2];
                    sfor<0, 2>([&](auto PS) {
                        constexpr int ps = decltype(PS)::v;
                        wg_fence();
                        sfor<0, 5>([&](auto KS) {
                            constexpr int ks = decltype(KS)::v;
                            wg_ss64<(ks ? 1 : 0)>(hc, mkdesc(PQT + ks * 2048, ks == 4 ? 0 : 1024, 128, 0) + pqo, mkdesc(KVB + ps * 8 * 1280 + ks * 256, 128, 1280, 0));
                        });
                        wg_commit();
                        wg_wait<0>();
                        reg_fence<32>(hc);
                        #pragma unroll
                        for (int hf = 0; hf < 2; hf++) {
                            if constexpr (ps == 0) {
                                float r[4];
                                r[0] = rcp(__shfl_sync(0xffffffffu, hc[2 * hf], l4) + 1e-6f);
                                r[1] = rcp(__shfl_sync(0xffffffffu, hc[1 + 2 * hf], l4) + 1e-6f);
                                r[2] = rcp(__shfl_sync(0xffffffffu, hc[2 * hf], l4 + 1) + 1e-6f);
                                r[3] = rcp(__shfl_sync(0xffffffffu, hc[1 + 2 * hf], l4 + 1) + 1e-6f);
                                r3[hf] = r[3];
                                #pragma unroll
                                for (int i = 0; i < 7; i++) {
                                    float rr = (i < 2) ? r[0] : (i == 2) ? (t < 1 ? r[0] : r[1]) : (i == 3) ? r[1] : (i == 4) ? (t < 2 ? r[1] : r[2])
                                             : (i == 5) ? r[2] : (t < 3 ? r[2] : r[3]);
                                    sts32(op + hf * 8 * 144 + i * 16, pack_bf16(hc[4 * i + 4 + 2 * hf] * rr, hc[4 * i + 5 + 2 * hf] * rr));
                                }
                            } else {
                                #pragma unroll
                                for (int i = 0; i < 2; i++)
                                    sts32(op + hf * 8 * 144 + 112 + i * 16, pack_bf16(hc[4 * i + 2 * hf] * r3[hf], hc[4 * i + 1 + 2 * hf] * r3[hf]));
                            }
                        }
                    });
                    fence_async_smem();
                    __syncwarp();
                    if ((t_ & 31) == 0) {
                        asm volatile("cp.async.bulk.tensor.2d.global.shared::cta.bulk_group [%0, {%2, %3}], [%1];"
                                     :: "l"(&tm_ost), "r"(OST + (t_ >> 5) * 2304), "r"((b_ & 7) * 72), "r"((b_ >> 3) * 128 + (t_ >> 5) * 16) : "memory");
                        asm volatile("cp.async.bulk.commit_group;" ::: "memory");
                    }
                }
            }
        }
        if (is_main) warp_arrive(bar(B_O8FREE));
        else {
            #pragma unroll
            for (int i = 0; i < 32; i++) { asm volatile("mov.b32 %0, 0;" : "=f"(hc[i])); asm volatile("mov.b32 %0, 0;" : "=f"(pv[i])); }
        }
        auto add_b2 = [&]() {
            #pragma unroll
            for (int b = 0; b < 8; b++) {
                float2 bv = lds64f(B2S + b * 32 + (c.tid() & 3) * 8);
                pv[4 * b] += bv.x; pv[4 * b + 1] += bv.y; pv[4 * b + 2] += bv.x; pv[4 * b + 3] += bv.y;
            }
        };
        auto load_xy = [&](int ftile, int nrdy, uint32_t* xr, uint32_t* yv) {
            const int mt = ftile / 9, ch = ftile - mt * 9;
            const uint32_t t_ = c.tid();
            const __nv_bfloat16* xp = p.x + (size_t)(mt * 128 + (t_ >> 5) * 16 + ((t_ >> 2) & 7)) * DM + ch * 64 + 2 * (t_ & 3);
            #pragma unroll
            for (int i = 0; i < 8; i++) {
                asm volatile("ld.global.nc.u32 %0, [%1];" : "=r"(xr[2 * i]) : "l"(xp + i * 8));
                asm volatile("ld.global.nc.u32 %0, [%1];" : "=r"(xr[2 * i + 1]) : "l"(xp + 8 * DM + i * 8));
            }
            prof(26);
            smem_wait_gt(EPO + 4, nrdy);
            prof(27);
            const unsigned char* yp = g_yacc + ((v_epoch() & 1) * 144 + ftile) * YT_BYTES + t_ * 16;
            #pragma unroll
            for (int q = 0; q < YT_BYTES / 4096; q++)
                asm volatile("ld.global.cg.v4.u32 {%0,%1,%2,%3}, [%4];" : "=r"(yv[4 * q]), "=r"(yv[4 * q + 1]), "=r"(yv[4 * q + 2]), "=r"(yv[4 * q + 3]) : "l"(yp + q * 4096) : "memory");
        };
        auto gate = [&](const uint32_t* yv) {
            #pragma unroll
            for (int i = 0; i < 16; i++) { pv[2 * i] += bf_lo(yv[i]); pv[2 * i + 1] += bf_hi(yv[i]); }
            #pragma unroll
            for (int i = 0; i < 32; i++) { const float h = 0.5f * pv[i]; pv[i] = fmaf(h, tanh_ap(h), h); }
        };
        auto store_out = [&](int ftile, const uint32_t* xr) {
            const uint32_t tb = tail_off();
            #pragma unroll
            for (int b = 0; b < 8; b++) {
                sts32(tb ^ (b << 4), pack_bf16(fmaf(hc[4 * b], pv[4 * b], bf_lo(xr[2 * b])), fmaf(hc[4 * b + 1], pv[4 * b + 1], bf_hi(xr[2 * b]))));
                sts32((tb ^ (b << 4)) + 1024, pack_bf16(fmaf(hc[4 * b + 2], pv[4 * b + 2], bf_lo(xr[2 * b + 1])), fmaf(hc[4 * b + 3], pv[4 * b + 3], bf_hi(xr[2 * b + 1]))));
            }
            fence_async_smem();
            __syncwarp();
            const uint32_t t_ = c.tid();
            if ((t_ & 31) == 0) {
                const int mt = ftile / 9, ch = ftile - mt * 9;
                asm volatile("cp.async.bulk.tensor.2d.global.shared::cta.bulk_group [%0, {%2, %3}], [%1];"
                             :: "l"(&tm_out), "r"(XB + (t_ >> 5) * 2048), "r"(ch * 64), "r"(mt * 128 + (int)(t_ >> 5) * 16) : "memory");
                asm volatile("cp.async.bulk.commit_group;" ::: "memory");
                asm volatile("cp.async.bulk.wait_group.read 0;" ::: "memory");
            }
            __syncwarp();
        };
        const int njob = is_main ? 1 : 4;
        #pragma unroll 1
        for (int job = 0; job < njob; job++) {
            const uint32_t jpar = job & 1;
            const uint32_t b_ = v_bid();
            const bool mainf = b_ < NMAIN;
            const int ftile = (b_ >> 3) * 9 + (b_ & 7);
            uint32_t oa[128];
            {
                mbar_wait(bar(B_OFULL), jpar);
                const uint32_t lrow = lrow_off();
                sfor<0, 32>([&](auto KS) {
                    constexpr int ks = decltype(KS)::v;
                    ldsm4((lrow ^ ((ks % 4) << 5)) + (ks / 4) * 16384, oa + ks * 4);
                });
                warp_arrive(bar(B_OFREE));
                if (job) c.tph ^= 1;
            }
            c.pf = false;
            run_step<K_H>(c, hc, oa, [&](auto ST) {
                constexpr int st = decltype(ST)::v;
                if (mainf) {
                    if constexpr (st == 0) add_b2();
                    else if constexpr (st == 1) load_xy(ftile, 0, oa, oa + 16);
                    else { prof(28); gate(oa + 16); prof(29); }
                }
                if constexpr (st == 1) mbar_wait(bar(B_O8FULL), jpar);
            }, [](auto) {}, job == njob - 1);
            prof(30);
            if (mainf) {
                named_bar(2 + (c.tid() >> 7), 128);
                store_out(ftile, oa);
            } else {
                warp_arrive(bar(B_O8FREE));
                uint4* sp = reinterpret_cast<uint4*>(g_s8) + ((b_ - NMAIN) * 4 + job) * 1024 + c.tid();
                #pragma unroll
                for (int q = 0; q < 4; q++)
                    sp[q * 256] = make_uint4(pack_bf16(hc[8 * q], hc[8 * q + 1]), pack_bf16(hc[8 * q + 2], hc[8 * q + 3]),
                                             pack_bf16(hc[8 * q + 4], hc[8 * q + 5]), pack_bf16(hc[8 * q + 6], hc[8 * q + 7]));
                prof(8 + job);
            }
        }
        if (!is_main) {
            named_bar(2 + (c.tid() >> 7), 128);
            #pragma unroll 1
            for (int job = 0; job < 4; job++) {
                const int tile = (v_bid() - NMAIN) * 4 + job;
                uint32_t xr[16], yv[YT_BYTES / 1024];
                const uint4* sp = reinterpret_cast<const uint4*>(g_s8) + tile * 1024 + c.tid();
                #pragma unroll
                for (int q = 0; q < 4; q++) {
                    const uint4 u = __ldcg(sp + q * 256);
                    hc[8 * q] = bf_lo(u.x); hc[8 * q + 1] = bf_hi(u.x); hc[8 * q + 2] = bf_lo(u.y); hc[8 * q + 3] = bf_hi(u.y);
                    hc[8 * q + 4] = bf_lo(u.z); hc[8 * q + 5] = bf_hi(u.z); hc[8 * q + 6] = bf_lo(u.w); hc[8 * q + 7] = bf_hi(u.w);
                }
                #pragma unroll
                for (int i = 0; i < 32; i++) pv[i] = 0.f;
                add_b2();
                load_xy(tile * 9 + 8, job, xr, yv);
                gate(yv);
                store_out(tile * 9 + 8, xr);
                prof(12 + job);
            }
        }
        prof(40);
        if (c.tid() == 0) g_epoch[v_bid()] = v_epoch() + 1;
    }
}

typedef CUresult (*EncodeFn)(CUtensorMap*, CUtensorMapDataType, cuuint32_t, void*, const cuuint64_t*, const cuuint64_t*,
                             const cuuint32_t*, const cuuint32_t*, CUtensorMapInterleave, CUtensorMapSwizzle,
                             CUtensorMapL2promotion, CUtensorMapFloatOOBfill);

void make_map(EncodeFn enc, CUtensorMap* tm, const void* base, int rows, int cols, int box_rows, int box_cols = 64, bool swz = true) {
    cuuint64_t gdim[2] = {(cuuint64_t)cols, (cuuint64_t)rows};
    cuuint64_t gstr[1] = {(cuuint64_t)cols * 2};
    cuuint32_t box[2] = {(cuuint32_t)box_cols, (cuuint32_t)box_rows};
    cuuint32_t estr[2] = {1, 1};
    enc(tm, CU_TENSOR_MAP_DATA_TYPE_BFLOAT16, 2, const_cast<void*>(base), gdim, gstr, box, estr, CU_TENSOR_MAP_INTERLEAVE_NONE,
        swz ? CU_TENSOR_MAP_SWIZZLE_128B : CU_TENSOR_MAP_SWIZZLE_NONE, CU_TENSOR_MAP_L2_PROMOTION_L2_128B, CU_TENSOR_MAP_FLOAT_OOB_FILL_NONE);
}

}

extern "C" void kernel_launch(void* const* d_in, const int* in_sizes, int n_in, void* d_out, int out_size) {
    static EncodeFn enc = nullptr;
    static void* o_ptr = nullptr;
    if (!enc) {
        void* fn = nullptr;
        cudaDriverEntryPointQueryResult qr;
        cudaGetDriverEntryPoint("cuTensorMapEncodeTiled", &fn, cudaEnableDefault, &qr);
        enc = (EncodeFn)fn;
        cudaGetSymbolAddress(&o_ptr, g_o);
        cudaFuncSetAttribute(fused_kernel, cudaFuncAttributeMaxDynamicSharedMemorySize, SMEM_BYTES);
    }
    Params p;
    p.x = (const __nv_bfloat16*)d_in[0];
    p.wqkv = (const __nv_bfloat16*)d_in[1];
    p.wo = (const __nv_bfloat16*)d_in[2];
    p.w1 = (const __nv_bfloat16*)d_in[4];
    p.b1 = (const __nv_bfloat16*)d_in[5];
    p.w2 = (const __nv_bfloat16*)d_in[6];
    p.b2 = (const __nv_bfloat16*)d_in[7];
    p.out = (__nv_bfloat16*)d_out;
    CUtensorMap tm_x, tm_w1, tm_w2, tm_wo, tm_o, tm_qkv, tm_qkve, tm_out, tm_ost;
    make_map(enc, &tm_ost, o_ptr, SEQ, DM, 16, 72, false);
    make_map(enc, &tm_out, p.out, SEQ, DM, 16);
    make_map(enc, &tm_qkv, p.wqkv, DM, 3 * DM, 96);
    make_map(enc, &tm_qkve, p.wqkv, DM, 3 * DM, 96, 8);
    make_map(enc, &tm_x, p.x, SEQ, DM, 128);
    make_map(enc, &tm_w1, p.w1, DM, FF, 192);
    make_map(enc, &tm_w2, p.w2, FF, DM, 192);
    make_map(enc, &tm_wo, p.wo, DM, DM, 192);
    make_map(enc, &tm_o, o_ptr, SEQ, DM, 128);
    fused_kernel<<<NMAIN + NAUX, 384, SMEM_BYTES>>>(tm_x, tm_w1, tm_w2, tm_wo, tm_o, tm_qkv, tm_qkve, tm_out, tm_ost, p);
}
```

```cpp
#include <cuda_runtime.h>
#include <cuda.h>
#include <cuda_bf16.h>
#include <stdint.h>

#define OSTEP_AT 4
#define KNOB_A 1
#define KNOB_B 0
#define PF1_NS 1000
#define PF2_NS 2000
#define PFIDX 3
#define PF3_NS 800
#define YF32 0

namespace {
constexpr int WAIT_ITERS = 3000000;

constexpr int SEQ = 2048, DM = 576, FF = 4608;
constexpr int NMAIN = 128, NAUX = 4;

constexpr uint32_t SB    = 0x400;
constexpr uint32_t HA    = SB;
constexpr uint32_t XB    = SB + 131072;
constexpr uint32_t RING  = SB + 147456;
constexpr uint32_t SLOT  = 24576;
constexpr uint32_t MISC  = SB + 221184;
constexpr uint32_t BARS  = MISC;
constexpr uint32_t B1S   = MISC + 512;
constexpr uint32_t B2S   = MISC + 2816;
constexpr uint32_t EPO   = MISC + 3072;
constexpr uint32_t EVC   = MISC + 3104;
constexpr uint32_t SMEM_BYTES = 221184 + 3200 + 512;
constexpr uint32_t PKT   = HA + 32768;
constexpr uint32_t VT    = HA + 51200;
constexpr uint32_t OST   = HA + 79872;
constexpr uint32_t PQT   = HA + 98304;
constexpr uint32_t KVB   = HA + 116736;

enum { B_FULL = 0, B_EMPTY = 3, B_XFULL = 6, B_OFULL = 9, B_O8FULL = 10, B_OFREE = 11, B_O8FREE = 12, B_KVB = 13, B_INIT = 14, B_COUNT = 15 };
__device__ __forceinline__ constexpr uint32_t bar(int i) { return BARS + 8u * i; }

constexpr int YT_BYTES = YF32 ? 32768 : 16384;
__device__ __align__(1024) __nv_bfloat16 g_o[SEQ * DM];
__device__ __align__(1024) unsigned char g_yacc[2 * 16 * 9 * YT_BYTES];
__device__ __align__(128) float g_kv[2 * 8 * 72 * 20];
__device__ __align__(128) unsigned int g_s8[16 * 4096];
__device__ __align__(128) unsigned int g_cnt[(8 + 16 + 16 * 9) * 8];
__device__ unsigned int g_epoch[NMAIN + NAUX];
__device__ __forceinline__ unsigned int* cnt_kv(int j) { return g_cnt + j * 8; }
__device__ __forceinline__ unsigned int* cnt_o(int m) { return g_cnt + (8 + m) * 8; }
__device__ __forceinline__ unsigned int* cnt_y(int m, int c) { return g_cnt + (24 + m * 9 + c) * 8; }

__device__ __forceinline__ void mbar_init(uint32_t b, uint32_t cnt) { asm volatile("mbarrier.init.shared::cta.b64 [%0], %1;" :: "r"(b), "r"(cnt)); }
__device__ __forceinline__ void mbar_expect_tx(uint32_t b, uint32_t bytes) { asm volatile("mbarrier.arrive.expect_tx.shared::cta.b64 _, [%0], %1;" :: "r"(b), "r"(bytes) : "memory"); }
__device__ __forceinline__ void mbar_arrive(uint32_t b) { asm volatile("mbarrier.arrive.shared::cta.b64 _, [%0];" :: "r"(b) : "memory"); }
__device__ __forceinline__ void prof(int) {}
__device__ __forceinline__ void mbar_wait(uint32_t b, uint32_t parity) {
    asm volatile("{\n.reg .pred p;\n.reg .u32 c;\nmov.u32 c, 0;\n"
                 "WAIT_LOOP:\nmbarrier.try_wait.parity.shared::cta.b64 p, [%0], %1;\n@p bra WAIT_DONE;\n"
                 "add.u32 c, c, 1;\nsetp.lt.u32 p, c, 4000000;\n@p bra WAIT_LOOP;\ntrap;\nWAIT_DONE:\n}"
                 :: "r"(b), "r"(parity) : "memory");
}
__device__ __forceinline__ void smem_wait_gt(uint32_t addr, uint32_t val) {
    asm volatile("{\n.reg .pred p;\n.reg .u32 c, v;\nmov.u32 c, 0;\n"
                 "SW_LOOP:\nld.acquire.cta.shared.u32 v, [%0];\nsetp.gt.u32 p, v, %1;\n@p bra SW_DONE;\n"
                 "add.u32 c, c, 1;\nsetp.lt.u32 p, c, 100000000;\n@p bra SW_LOOP;\ntrap;\nSW_DONE:\n}"
                 :: "r"(addr), "r"(val) : "memory");
}
__device__ __forceinline__ void tma_2d(uint32_t dst, const CUtensorMap* tm, uint32_t b, int c0, int c1) {
    asm volatile("cp.async.bulk.tensor.2d.shared::cluster.global.mbarrier::complete_tx::bytes [%0], [%1, {%3, %4}], [%2];"
                 :: "r"(dst), "l"(tm), "r"(b), "r"(c0), "r"(c1) : "memory");
}
__device__ __forceinline__ void fence_async_smem() { asm volatile("fence.proxy.async.shared::cta;" ::: "memory"); }
__device__ __forceinline__ void fence_async_all() { asm volatile("fence.proxy.async;" ::: "memory"); }
__device__ __forceinline__ void named_bar(int id, int n) { asm volatile("bar.sync %0, %1;" :: "r"(id), "r"(n) : "memory"); }
__device__ __forceinline__ void wg_fence() { asm volatile("wgmma.fence.sync.aligned;" ::: "memory"); }
__device__ __forceinline__ void wg_commit() { asm volatile("wgmma.commit_group.sync.aligned;" ::: "memory"); }
template<int N> __device__ __forceinline__ void wg_wait() { asm volatile("wgmma.wait_group.sync.aligned %0;" :: "n"(N) : "memory"); }
template<int N> __device__ __forceinline__ void reg_fence(float* d) {
    #pragma unroll
    for (int i = 0; i < N; i++) asm volatile("" : "+f"(d[i]) :: "memory");
}
template<int N> __device__ __forceinline__ void reg_copy(float* d, const float* s) {
    #pragma unroll
    for (int i = 0; i < N; i++) asm volatile("mov.b32 %0, %1;" : "=f"(d[i]) : "f"(s[i]));
}
__device__ __forceinline__ uint32_t pack_bf16(float lo, float hi) { uint32_t r; asm("cvt.rn.bf16x2.f32 %0, %1, %2;" : "=r"(r) : "f"(hi), "f"(lo)); return r; }
__device__ __forceinline__ float bf_lo(uint32_t v) { return __uint_as_float(v << 16); }
__device__ __forceinline__ float bf_hi(uint32_t v) { return __uint_as_float(v & 0xffff0000u); }
__device__ __forceinline__ uint32_t sub_bf16x2(uint32_t a, uint32_t b) { uint32_t r; asm("sub.rn.bf16x2 %0, %1, %2;" : "=r"(r) : "r"(a), "r"(b)); return r; }
__device__ __forceinline__ float ex2(float x) { float r; asm("ex2.approx.ftz.f32 %0, %1;" : "=f"(r) : "f"(x)); return r; }
__device__ __forceinline__ float rcp(float x) { float r; asm("rcp.approx.ftz.f32 %0, %1;" : "=f"(r) : "f"(x)); return r; }
__device__ __forceinline__ float tanh_ap(float x) { float r; asm("tanh.approx.f32 %0, %1;" : "=f"(r) : "f"(x)); return r; }
__device__ __forceinline__ void sts32(uint32_t a, uint32_t v) { asm volatile("st.shared.b32 [%0], %1;" :: "r"(a), "r"(v)); }
__device__ __forceinline__ void sts128(uint32_t a, uint32_t x, uint32_t y, uint32_t z, uint32_t w) { asm volatile("st.shared.v4.b32 [%0], {%1,%2,%3,%4};" :: "r"(a), "r"(x), "r"(y), "r"(z), "r"(w)); }
__device__ __forceinline__ void sts64(uint32_t a, uint32_t x, uint32_t y) { asm volatile("st.shared.v2.b32 [%0], {%1,%2};" :: "r"(a), "r"(x), "r"(y)); }
__device__ __forceinline__ void lds64(uint32_t a, uint32_t* v) { asm volatile("ld.shared.v2.b32 {%0,%1}, [%2];" : "=r"(v[0]), "=r"(v[1]) : "r"(a)); }
__device__ __forceinline__ void lds128(uint32_t a, uint32_t* v) { asm volatile("ld.shared.v4.b32 {%0,%1,%2,%3}, [%4];" : "=r"(v[0]), "=r"(v[1]), "=r"(v[2]), "=r"(v[3]) : "r"(a) : "memory"); }
__device__ __forceinline__ float2 lds64f(uint32_t a) { float2 v; asm("ld.shared.v2.f32 {%0,%1}, [%2];" : "=f"(v.x), "=f"(v.y) : "r"(a)); return v; }
__device__ __forceinline__ void ldsm4(uint32_t a, uint32_t* v) {
    asm volatile("ldmatrix.sync.aligned.m8n8.x4.shared.b16 {%0,%1,%2,%3}, [%4];" : "=r"(v[0]), "=r"(v[1]), "=r"(v[2]), "=r"(v[3]) : "r"(a));
}
__device__ __forceinline__ void mma_ones(float* c, const uint32_t* a) {
    const uint32_t one2 = 0x3F803F80u;
    asm volatile("mma.sync.aligned.m16n8k16.row.col.f32.bf16.bf16.f32 {%0,%1,%2,%3}, {%4,%5,%6,%7}, {%8,%8}, {%0,%1,%2,%3};"
                 : "+f"(c[0]), "+f"(c[1]), "+f"(c[2]), "+f"(c[3]) : "r"(a[0]), "r"(a[1]), "r"(a[2]), "r"(a[3]), "r"(one2));
}
__device__ __forceinline__ unsigned int ld_acquire(const unsigned int* p) { unsigned int v; asm volatile("ld.acquire.gpu.global.u32 %0, [%1];" : "=r"(v) : "l"(p) : "memory"); return v; }
__device__ __forceinline__ void wait_cnt(const unsigned int* p, unsigned int target) {
    for (int i = 0; i < WAIT_ITERS; i++) {
        if ((int)(ld_acquire(p) - target) >= 0) return;
        __nanosleep(40);
    }
    __trap();
}
__device__ __forceinline__ uint32_t v_tid() { uint32_t r; asm volatile("mov.u32 %0, %%tid.x;" : "=r"(r)); return r; }
__device__ __forceinline__ uint32_t v_bid() { uint32_t r; asm volatile("mov.u32 %0, %%ctaid.x;" : "=r"(r)); return r; }
__device__ __forceinline__ uint32_t v_epoch() { uint32_t r; asm volatile("ld.shared.u32 %0, [%1];" : "=r"(r) : "r"(EPO)); return r; }
__device__ __forceinline__ void prefetch_l2(const void* p) { asm volatile("prefetch.global.L2 [%0];" :: "l"(p)); }

__host__ __device__ constexpr uint64_t mkdesc(uint32_t addr, uint32_t lbo, uint32_t sbo, uint32_t swz) {
    return (uint64_t)((addr & 0x3FFFF) >> 4) | ((uint64_t)((lbo >> 4) & 0x3FFF) << 16) | ((uint64_t)((sbo >> 4) & 0x3FFF) << 32) | ((uint64_t)swz << 62);
}

template<int SD> __device__ __forceinline__ void wg_rs64(float* d, const uint32_t* a, uint64_t bd) {
  if constexpr (SD) {
    asm volatile("{\n.reg .pred p;\nsetp.eq.b32 p, 0, 0;\n"
    "wgmma.mma_async.sync.aligned.m64n64k16.f32.bf16.bf16 {%0,%1,%2,%3,%4,%5,%6,%7,%8,%9,%10,%11,%12,%13,%14,%15,%16,%17,%18,%19,%20,%21,%22,%23,%24,%25,%26,%27,%28,%29,%30,%31}, {%32,%33,%34,%35}, %36, p, 1, 1, 1;\n}"
    : "+f"(d[0]),"+f"(d[1]),"+f"(d[2]),"+f"(d[3]),"+f"(d[4]),"+f"(d[5]),"+f"(d[6]),"+f"(d[7]),"+f"(d[8]),"+f"(d[9]),"+f"(d[10]),"+f"(d[11]),"+f"(d[12]),"+f"(d[13]),"+f"(d[14]),"+f"(d[15]),"+f"(d[16]),"+f"(d[17]),"+f"(d[18]),"+f"(d[19]),"+f"(d[20]),"+f"(d[21]),"+f"(d[22]),"+f"(d[23]),"+f"(d[24]),"+f"(d[25]),"+f"(d[26]),"+f"(d[27]),"+f"(d[28]),"+f"(d[29]),"+f"(d[30]),"+f"(d[31])
    : "r"(a[0]),"r"(a[1]),"r"(a[2]),"r"(a[3]), "l"(bd));
  } else {
    asm volatile("{\n.reg .pred p;\nsetp.ne.b32 p, 0, 0;\n"
    "wgmma.mma_async.sync.aligned.m64n64k16.f32.bf16.bf16 {%0,%1,%2,%3,%4,%5,%6,%7,%8,%9,%10,%11,%12,%13,%14,%15,%16,%17,%18,%19,%20,%21,%22,%23,%24,%25,%26,%27,%28,%29,%30,%31}, {%32,%33,%34,%35}, %36, p, 1, 1, 1;\n}"
    : "+f"(d[0]),"+f"(d[1]),"+f"(d[2]),"+f"(d[3]),"+f"(d[4]),"+f"(d[5]),"+f"(d[6]),"+f"(d[7]),"+f"(d[8]),"+f"(d[9]),"+f"(d[10]),"+f"(d[11]),"+f"(d[12]),"+f"(d[13]),"+f"(d[14]),"+f"(d[15]),"+f"(d[16]),"+f"(d[17]),"+f"(d[18]),"+f"(d[19]),"+f"(d[20]),"+f"(d[21]),"+f"(d[22]),"+f"(d[23]),"+f"(d[24]),"+f"(d[25]),"+f"(d[26]),"+f"(d[27]),"+f"(d[28]),"+f"(d[29]),"+f"(d[30]),"+f"(d[31])
    : "r"(a[0]),"r"(a[1]),"r"(a[2]),"r"(a[3]), "l"(bd));
  }
}
template<int SD> __device__ __forceinline__ void wg_ss64(float* d, uint64_t ad, uint64_t bd) {
  if constexpr (SD) {
    asm volatile("{\n.reg .pred p;\nsetp.eq.b32 p, 0, 0;\n"
    "wgmma.mma_async.sync.aligned.m64n64k16.f32.bf16.bf16 {%0,%1,%2,%3,%4,%5,%6,%7,%8,%9,%10,%11,%12,%13,%14,%15,%16,%17,%18,%19,%20,%21,%22,%23,%24,%25,%26,%27,%28,%29,%30,%31}, %32, %33, p, 1, 1, 0, 1;\n}"
    : "+f"(d[0]),"+f"(d[1]),"+f"(d[2]),"+f"(d[3]),"+f"(d[4]),"+f"(d[5]),"+f"(d[6]),"+f"(d[7]),"+f"(d[8]),"+f"(d[9]),"+f"(d[10]),"+f"(d[11]),"+f"(d[12]),"+f"(d[13]),"+f"(d[14]),"+f"(d[15]),"+f"(d[16]),"+f"(d[17]),"+f"(d[18]),"+f"(d[19]),"+f"(d[20]),"+f"(d[21]),"+f"(d[22]),"+f"(d[23]),"+f"(d[24]),"+f"(d[25]),"+f"(d[26]),"+f"(d[27]),"+f"(d[28]),"+f"(d[29]),"+f"(d[30]),"+f"(d[31])
    : "l"(ad), "l"(bd));
  } else {
    asm volatile("{\n.reg .pred p;\nsetp.ne.b32 p, 0, 0;\n"
    "wgmma.mma_async.sync.aligned.m64n64k16.f32.bf16.bf16 {%0,%1,%2,%3,%4,%5,%6,%7,%8,%9,%10,%11,%12,%13,%14,%15,%16,%17,%18,%19,%20,%21,%22,%23,%24,%25,%26,%27,%28,%29,%30,%31}, %32, %33, p, 1, 1, 0, 1;\n}"
    : "+f"(d[0]),"+f"(d[1]),"+f"(d[2]),"+f"(d[3]),"+f"(d[4]),"+f"(d[5]),"+f"(d[6]),"+f"(d[7]),"+f"(d[8]),"+f"(d[9]),"+f"(d[10]),"+f"(d[11]),"+f"(d[12]),"+f"(d[13]),"+f"(d[14]),"+f"(d[15]),"+f"(d[16]),"+f"(d[17]),"+f"(d[18]),"+f"(d[19]),"+f"(d[20]),"+f"(d[21]),"+f"(d[22]),"+f"(d[23]),"+f"(d[24]),"+f"(d[25]),"+f"(d[26]),"+f"(d[27]),"+f"(d[28]),"+f"(d[29]),"+f"(d[30]),"+f"(d[31])
    : "l"(ad), "l"(bd));
  }
}
template<int SD> __device__ __forceinline__ void wg_rs72(float* d, const uint32_t* a, uint64_t bd) {
  if constexpr (SD) {
    asm volatile("{\n.reg .pred p;\nsetp.eq.b32 p, 0, 0;\n"
    "wgmma.mma_async.sync.aligned.m64n72k16.f32.bf16.bf16 {%0,%1,%2,%3,%4,%5,%6,%7,%8,%9,%10,%11,%12,%13,%14,%15,%16,%17,%18,%19,%20,%21,%22,%23,%24,%25,%26,%27,%28,%29,%30,%31,%32,%33,%34,%35}, {%36,%37,%38,%39}, %40, p, 1, 1, 1;\n}"
    : "+f"(d[0]),"+f"(d[1]),"+f"(d[2]),"+f"(d[3]),"+f"(d[4]),"+f"(d[5]),"+f"(d[6]),"+f"(d[7]),"+f"(d[8]),"+f"(d[9]),"+f"(d[10]),"+f"(d[11]),"+f"(d[12]),"+f"(d[13]),"+f"(d[14]),"+f"(d[15]),"+f"(d[16]),"+f"(d[17]),"+f"(d[18]),"+f"(d[19]),"+f"(d[20]),"+f"(d[21]),"+f"(d[22]),"+f"(d[23]),"+f"(d[24]),"+f"(d[25]),"+f"(d[26]),"+f"(d[27]),"+f"(d[28]),"+f"(d[29]),"+f"(d[30]),"+f"(d[31]),"+f"(d[32]),"+f"(d[33]),"+f"(d[34]),"+f"(d[35])
    : "r"(a[0]),"r"(a[1]),"r"(a[2]),"r"(a[3]), "l"(bd));
  } else {
    asm volatile("{\n.reg .pred p;\nsetp.ne.b32 p, 0, 0;\n"
    "wgmma.mma_async.sync.aligned.m64n72k16.f32.bf16.bf16 {%0,%1,%2,%3,%4,%5,%6,%7,%8,%9,%10,%11,%12,%13,%14,%15,%16,%17,%18,%19,%20,%21,%22,%23,%24,%25,%26,%27,%28,%29,%30,%31,%32,%33,%34,%35}, {%36,%37,%38,%39}, %40, p, 1, 1, 1;\n}"
    : "+f"(d[0]),"+f"(d[1]),"+f"(d[2]),"+f"(d[3]),"+f"(d[4]),"+f"(d[5]),"+f"(d[6]),"+f"(d[7]),"+f"(d[8]),"+f"(d[9]),"+f"(d[10]),"+f"(d[11]),"+f"(d[12]),"+f"(d[13]),"+f"(d[14]),"+f"(d[15]),"+f"(d[16]),"+f"(d[17]),"+f"(d[18]),"+f"(d[19]),"+f"(d[20]),"+f"(d[21]),"+f"(d[22]),"+f"(d[23]),"+f"(d[24]),"+f"(d[25]),"+f"(d[26]),"+f"(d[27]),"+f"(d[28]),"+f"(d[29]),"+f"(d[30]),"+f"(d[31]),"+f"(d[32]),"+f"(d[33]),"+f"(d[34]),"+f"(d[35])
    : "r"(a[0]),"r"(a[1]),"r"(a[2]),"r"(a[3]), "l"(bd));
  }
}
template<int SD> __device__ __forceinline__ void wg_ss72(float* d, uint64_t ad, uint64_t bd) {
  if constexpr (SD) {
    asm volatile("{\n.reg .pred p;\nsetp.eq.b32 p, 0, 0;\n"
    "wgmma.mma_async.sync.aligned.m64n72k16.f32.bf16.bf16 {%0,%1,%2,%3,%4,%5,%6,%7,%8,%9,%10,%11,%12,%13,%14,%15,%16,%17,%18,%19,%20,%21,%22,%23,%24,%25,%26,%27,%28,%29,%30,%31,%32,%33,%34,%35}, %36, %37, p, 1, 1, 0, 1;\n}"
    : "+f"(d[0]),"+f"(d[1]),"+f"(d[2]),"+f"(d[3]),"+f"(d[4]),"+f"(d[5]),"+f"(d[6]),"+f"(d[7]),"+f"(d[8]),"+f"(d[9]),"+f"(d[10]),"+f"(d[11]),"+f"(d[12]),"+f"(d[13]),"+f"(d[14]),"+f"(d[15]),"+f"(d[16]),"+f"(d[17]),"+f"(d[18]),"+f"(d[19]),"+f"(d[20]),"+f"(d[21]),"+f"(d[22]),"+f"(d[23]),"+f"(d[24]),"+f"(d[25]),"+f"(d[26]),"+f"(d[27]),"+f"(d[28]),"+f"(d[29]),"+f"(d[30]),"+f"(d[31]),"+f"(d[32]),"+f"(d[33]),"+f"(d[34]),"+f"(d[35])
    : "l"(ad), "l"(bd));
  } else {
    asm volatile("{\n.reg .pred p;\nsetp.ne.b32 p, 0, 0;\n"
    "wgmma.mma_async.sync.aligned.m64n72k16.f32.bf16.bf16 {%0,%1,%2,%3,%4,%5,%6,%7,%8,%9,%10,%11,%12,%13,%14,%15,%16,%17,%18,%19,%20,%21,%22,%23,%24,%25,%26,%27,%28,%29,%30,%31,%32,%33,%34,%35}, %36, %37, p, 1, 1, 0, 1;\n}"
    : "+f"(d[0]),"+f"(d[1]),"+f"(d[2]),"+f"(d[3]),"+f"(d[4]),"+f"(d[5]),"+f"(d[6]),"+f"(d[7]),"+f"(d[8]),"+f"(d[9]),"+f"(d[10]),"+f"(d[11]),"+f"(d[12]),"+f"(d[13]),"+f"(d[14]),"+f"(d[15]),"+f"(d[16]),"+f"(d[17]),"+f"(d[18]),"+f"(d[19]),"+f"(d[20]),"+f"(d[21]),"+f"(d[22]),"+f"(d[23]),"+f"(d[24]),"+f"(d[25]),"+f"(d[26]),"+f"(d[27]),"+f"(d[28]),"+f"(d[29]),"+f"(d[30]),"+f"(d[31]),"+f"(d[32]),"+f"(d[33]),"+f"(d[34]),"+f"(d[35])
    : "l"(ad), "l"(bd));
  }
}
template<int SD> __device__ __forceinline__ void wg_tt64(float* d, uint64_t ad, uint64_t bd) {
  if constexpr (SD) {
    asm volatile("{\n.reg .pred p;\nsetp.eq.b32 p, 0, 0;\n"
    "wgmma.mma_async.sync.aligned.m64n64k16.f32.bf16.bf16 {%0,%1,%2,%3,%4,%5,%6,%7,%8,%9,%10,%11,%12,%13,%14,%15,%16,%17,%18,%19,%20,%21,%22,%23,%24,%25,%26,%27,%28,%29,%30,%31}, %32, %33, p, 1, 1, 1, 1;\n}"
    : "+f"(d[0]),"+f"(d[1]),"+f"(d[2]),"+f"(d[3]),"+f"(d[4]),"+f"(d[5]),"+f"(d[6]),"+f"(d[7]),"+f"(d[8]),"+f"(d[9]),"+f"(d[10]),"+f"(d[11]),"+f"(d[12]),"+f"(d[13]),"+f"(d[14]),"+f"(d[15]),"+f"(d[16]),"+f"(d[17]),"+f"(d[18]),"+f"(d[19]),"+f"(d[20]),"+f"(d[21]),"+f"(d[22]),"+f"(d[23]),"+f"(d[24]),"+f"(d[25]),"+f"(d[26]),"+f"(d[27]),"+f"(d[28]),"+f"(d[29]),"+f"(d[30]),"+f"(d[31])
    : "l"(ad), "l"(bd));
  } else {
    asm volatile("{\n.reg .pred p;\nsetp.ne.b32 p, 0, 0;\n"
    "wgmma.mma_async.sync.aligned.m64n64k16.f32.bf16.bf16 {%0,%1,%2,%3,%4,%5,%6,%7,%8,%9,%10,%11,%12,%13,%14,%15,%16,%17,%18,%19,%20,%21,%22,%23,%24,%25,%26,%27,%28,%29,%30,%31}, %32, %33, p, 1, 1, 1, 1;\n}"
    : "+f"(d[0]),"+f"(d[1]),"+f"(d[2]),"+f"(d[3]),"+f"(d[4]),"+f"(d[5]),"+f"(d[6]),"+f"(d[7]),"+f"(d[8]),"+f"(d[9]),"+f"(d[10]),"+f"(d[11]),"+f"(d[12]),"+f"(d[13]),"+f"(d[14]),"+f"(d[15]),"+f"(d[16]),"+f"(d[17]),"+f"(d[18]),"+f"(d[19]),"+f"(d[20]),"+f"(d[21]),"+f"(d[22]),"+f"(d[23]),"+f"(d[24]),"+f"(d[25]),"+f"(d[26]),"+f"(d[27]),"+f"(d[28]),"+f"(d[29]),"+f"(d[30]),"+f"(d[31])
    : "l"(ad), "l"(bd));
  }
}

template<int V> struct IC { static constexpr int v = V; };
template<int I, int N, class F> __device__ __forceinline__ void sfor(F&& f) {
    if constexpr (I < N) { f(IC<I>{}); sfor<I + 1, N>(f); }
}

enum { K_QKV = 0, K_H = 1 };

struct Ctx {
    uint32_t tph;
    uint32_t tid_;
    bool pf = false;
    __device__ __forceinline__ uint32_t tid() const { uint32_t r; asm volatile("mov.u32 %0, %1;" : "=r"(r) : "r"(tid_)); return r; }
};
__device__ __forceinline__ void release_slot(const Ctx& c, int slot) { if ((c.tid() & 31) == 0) mbar_arrive(bar(B_EMPTY + slot)); }

__device__ __forceinline__ void turn_wait(const Ctx& c) { asm volatile("bar.sync %0, 256;" :: "r"(4 + (c.tid() >> 7)) : "memory"); }
__device__ __forceinline__ void turn_pass(const Ctx& c) { asm volatile("bar.arrive %0, 256;" :: "r"(5 - (c.tid() >> 7)) : "memory"); }

template<int KIND, class PART, class POST>
__device__ __forceinline__ void run_step(Ctx& c, float* acc, const uint32_t* a, PART&& part, POST&& post, bool last = false) {
    constexpr int NST = (KIND == K_QKV) ? 6 : 3;
    constexpr int KPS = 36 / NST;
    sfor<0, NST>([&](auto ST) {
        constexpr int st = decltype(ST)::v;
        constexpr int slot = st % 3;
        mbar_wait(bar(B_FULL + slot), c.tph);
        uint32_t wgo = 0;
        if constexpr (st == NST - 1) wgo = (c.tid() >> 7) * 512;
        if (KIND == K_H && c.pf) prof(44 + st * 5);
        turn_wait(c);
        if (KIND == K_H && c.pf) prof(45 + st * 5);
        wg_fence();
        sfor<0, KPS>([&](auto KK) {
            constexpr int kk = decltype(KK)::v;
            constexpr int ks = st * KPS + kk;
            constexpr int SD = ks ? 1 : 0;
            if constexpr (KIND == K_QKV) {
                constexpr uint64_t bd = mkdesc(RING + slot * SLOT + kk * 2048, 12288, 1024, 1);
                if constexpr (ks < 32) wg_rs72<SD>(acc, a + ks * 4, bd);
                else wg_ss72<SD>(acc, mkdesc(XB + (ks - 32) * 32, 16, 1024, 1) + wgo, bd);
            } else {
                constexpr uint64_t bd = mkdesc(RING + slot * SLOT + kk * 2048, 16, 1024, 1);
                if constexpr (ks < 32) wg_rs64<SD>(acc, a + ks * 4, bd);
                else wg_ss64<SD>(acc, mkdesc(XB + (ks - 32) * 32, 16, 1024, 1) + wgo, bd);
            }
        });
        wg_commit();
        if (st < NST - 1 || !last || c.tid() < 128) turn_pass(c);
        if (KIND == K_H && c.pf) prof(46 + st * 5);
        part(ST);
        if (KIND == K_H && c.pf) prof(47 + st * 5);
        wg_wait<0>();
        if (KIND == K_H && c.pf) prof(48 + st * 5);
        release_slot(c, slot);
        if constexpr (slot == 2) c.tph ^= 1;
        post(ST);
    });
    if constexpr (KIND == K_QKV) reg_fence<36>(acc); else reg_fence<32>(acc);
}

__device__ __forceinline__ float phi(float t) {
    float e = ex2(t * 1.4426950408889634f);
    return (t > 0.f ? t + 1.0f : e) + 1e-6f;
}
__device__ __forceinline__ float gelu_h(float hx) {
    float u = hx * fmaf(hx * hx, 0.2854192650f, 1.5957691216f);
    return fmaf(hx, tanh_ap(u), hx);
}

struct Params {
    const __nv_bfloat16* x;
    const __nv_bfloat16* wqkv;
    const __nv_bfloat16* wo;
    const __nv_bfloat16* w1;
    const __nv_bfloat16* b1;
    const __nv_bfloat16* w2;
    const __nv_bfloat16* b2;
    __nv_bfloat16* out;
};

__global__ void __launch_bounds__(384, 1)
fused_kernel(const __grid_constant__ CUtensorMap tm_x, const __grid_constant__ CUtensorMap tm_w1,
             const __grid_constant__ CUtensorMap tm_w2, const __grid_constant__ CUtensorMap tm_wo,
             const __grid_constant__ CUtensorMap tm_o, const __grid_constant__ CUtensorMap tm_qkv,
             const __grid_constant__ CUtensorMap tm_qkve, const __grid_constant__ CUtensorMap tm_ost, const Params p) {
    extern __shared__ __align__(1024) unsigned char smem_raw[];
    const int tid = threadIdx.x;
    const int bid = blockIdx.x;
    const bool is_main = bid < NMAIN;
    const int j = bid & 7;
    const int m = bid >> 3;

    if (tid == 0) {
        if ((uint32_t)__cvta_generic_to_shared(smem_raw) != SB) __trap();
        for (int i = 0; i < 3; i++) {
            mbar_init(bar(B_FULL + i), 1); mbar_init(bar(B_EMPTY + i), 8);
            mbar_init(bar(B_XFULL + i), 1);
        }
        mbar_init(bar(B_KVB), 2); mbar_init(bar(B_INIT), 1);
        mbar_init(bar(B_OFULL), 1); mbar_init(bar(B_O8FULL), 1); mbar_init(bar(B_OFREE), 8); mbar_init(bar(B_O8FREE), 8);
        asm volatile("fence.mbarrier_init.release.cluster;" ::: "memory");
    }
    if (tid == 256) { asm volatile("prefetch.tensormap [%0];" :: "l"(&tm_x) : "memory"); asm volatile("prefetch.tensormap [%0];" :: "l"(&tm_qkv) : "memory"); asm volatile("prefetch.tensormap [%0];" :: "l"(&tm_qkve) : "memory"); }
    if (tid >= 40 && tid < 48) sts32(EVC + (tid - 40) * 4, 0);
    if (tid == 48) sts32(EPO + 4, 0);
    __syncthreads();

    if (tid >= 256) {
        asm volatile("setmaxnreg.dec.sync.aligned.u32 24;");
        const int hw = (tid >> 5) - 8, lane = tid & 31;
        uint32_t epoch = 0;
        if (hw > 0) {
            epoch = g_epoch[bid];
            if (hw == 3) {
                if (lane == 0) sts32(EPO, epoch);
                if (is_main) {
                    #pragma unroll 1
                    for (int i = lane; i < 288; i += 32) {
                        uint32_t v = *reinterpret_cast<const uint32_t*>(p.b1 + j * 576 + 2 * i);
                        sts32(B1S + 8 * i, __float_as_uint(0.5f * bf_lo(v))); sts32(B1S + 8 * i + 4, __float_as_uint(0.5f * bf_hi(v)));
                    }
                }
                uint32_t v = *reinterpret_cast<const uint32_t*>(p.b2 + (is_main ? j : 8) * 64 + 2 * lane);
                sts32(B2S + 8 * lane, v << 16); sts32(B2S + 8 * lane + 4, v & 0xffff0000u);
                __syncwarp();
                if (lane == 0) mbar_arrive(bar(B_INIT));
            }
        }
        const uint32_t par = epoch & 1;
        if (hw == 0) {
            if (lane == 0) {
                uint32_t n = 0;
                if (is_main) {
                    #pragma unroll 1
                    for (int kb = 0; kb < 9; kb++) {
                        if (kb % 3 == 0) mbar_expect_tx(bar(B_XFULL + kb / 3), 49152);
                        tma_2d(HA + kb * 16384, &tm_x, bar(B_XFULL + kb / 3), kb * 64, m * 128);
                    }
                    #pragma unroll 1
                    for (int u = 0; u < 18; u++) {
                        const int st = u % 3, step = u / 6;
                        const int col = ((step == 2) ? 0 : (step + 1) * 576) + j * 72, row = (u % 6) * 96;
                        mbar_wait(bar(B_EMPTY + st), (n & 1) ^ 1);
                        mbar_expect_tx(bar(B_FULL + st), 96 * 144);
                        tma_2d(RING + st * SLOT, &tm_qkv, bar(B_FULL + st), col, row);
                        tma_2d(RING + st * SLOT + 12288, &tm_qkve, bar(B_FULL + st), col + 64, row);
                        if (st == 2) n++;
                    }
                }
                const int nsteps = is_main ? 19 : 1;
                #pragma unroll 1
                for (int s = 0; s < nsteps; s++, n++) {
                    const CUtensorMap* tm; int col, row;
                    if (!is_main) { tm = &tm_wo; col = 512; row = 0; }
                    else if (s < 9) { tm = &tm_w1; col = j * 576 + s * 64; row = 0; }
                    else if (s < 18) { tm = &tm_w2; col = (s == 9) ? 512 : (((j + s - 9) & 7) * 64); row = j * 576; }
                    else { tm = &tm_wo; col = j * 64; row = 0; }
                    #pragma unroll 1
                    for (int st = 0; st < 3; st++) {
                        mbar_wait(bar(B_EMPTY + st), (n & 1) ^ 1);
                        mbar_expect_tx(bar(B_FULL + st), SLOT);
                        tma_2d(RING + st * SLOT, tm, bar(B_FULL + st), col, row + st * 192);
                    }
                }
            }
        } else {
            if (is_main) {
                const int t = tid - 288;
                #pragma unroll 1
                for (int i = t; i < 36 * 6; i += 96) {
                    int r = i / 6, q = i - r * 6;
                    prefetch_l2(reinterpret_cast<const char*>(p.wqkv) + (36 * m + r) * 3456 + (q >> 1) * 1152 + j * 144 + (q & 1) * 128);
                }
                __nanosleep(PF1_NS);
                #pragma unroll 1
                for (int i = t; i < 36 * 9; i += 96) {
                    int r = i / 9, q = i - r * 9;
                    prefetch_l2(reinterpret_cast<const char*>(p.w1) + (36 * m + r) * 9216 + j * 1152 + q * 128);
                    __nanosleep(PF3_NS);
                }
                __nanosleep(PF2_NS);
                #pragma unroll 1
                for (int i = t; i < 36 * 9; i += 96)
                    prefetch_l2(reinterpret_cast<const char*>(p.w2) + (576 * j + 36 * m) * 1152 + i * 128);
                if (t < 41 && (bid * 41 + t) < 5184) prefetch_l2(reinterpret_cast<const char*>(p.wo) + (bid * 41 + t) * 128);
                if (hw != 2) {
                    if (lane == 0) wait_cnt(cnt_kv(j), (epoch + 1) * 16);
                    __syncwarp();
                    const float4* kv = reinterpret_cast<const float4*>(g_kv + (par * 8 + j) * 1440);
                    #pragma unroll 2
                    for (int i = lane + (hw == 1 ? 0 : 32); i < 360; i += 64) {
                        const float4 v = __ldcg(kv + i);
                        const int d = i / 5, e = (i - d * 5) * 4, h = d / 18;
                        const uint32_t base = KVB + (d >> 3) * 128 + (d & 7) * 16;
                        const int n0 = 8 + h * 18 + e;
                        sts32(base + (n0 >> 3) * 1280 + (n0 & 7) * 2, pack_bf16(v.x, v.y));
                        if (e < 16) sts32(base + ((n0 + 2) >> 3) * 1280 + ((n0 + 2) & 7) * 2, pack_bf16(v.z, v.w));
                        else asm volatile("st.shared.u16 [%0], %1;" :: "r"(base + h * 2), "h"((unsigned short)pack_bf16(v.z, 0.f)) : "memory");
                    }
                    fence_async_smem();
                    __syncwarp();
                    if (lane == 0) mbar_arrive(bar(B_KVB));
                }
            }
            if (hw == 1) {
                if (lane == 0) {
                    const int nit = is_main ? 1 : 4;
                    for (int it = 0; it < nit; it++) {
                        const int mt = is_main ? m : ((bid - NMAIN) * 4 + it);
                        const bool wf = is_main || it > 0;
                        const uint32_t fp = is_main ? 0 : ((it - 1) & 1);
                        wait_cnt(cnt_o(mt), (epoch + 1) * 8);
                        fence_async_all();
                        if (wf) mbar_wait(bar(B_OFREE), fp);
                        mbar_expect_tx(bar(B_OFULL), 131072);
                        #pragma unroll 1
                        for (int kb = 0; kb < 8; kb++) tma_2d(HA + kb * 16384, &tm_o, bar(B_OFULL), kb * 64, mt * 128);
                        if (wf) mbar_wait(bar(B_O8FREE), fp);
                        mbar_expect_tx(bar(B_O8FULL), 16384);
                        tma_2d(XB, &tm_o, bar(B_O8FULL), 512, mt * 128);
                    }
                    if (is_main) { wait_cnt(cnt_y(m, j), (epoch + 1) * 7); asm volatile("st.release.cta.shared.u32 [%0], %1;" :: "r"(EPO + 4), "r"(1) : "memory"); }
                }
            } else if (hw == 2) {
                if (!is_main) {
                    if (lane == 0) {
                        #pragma unroll 1
                        for (int it = 0; it < 4; it++) {
                            wait_cnt(cnt_y((bid - NMAIN) * 4 + it, 8), (epoch + 1) * 8);
                            asm volatile("st.release.cta.shared.u32 [%0], %1;" :: "r"(EPO + 4), "r"(it + 1) : "memory");
                        }
                    }
                } else {
                    #pragma unroll 1
                    for (int e = 0; e < 10; e++) {
                        int spin = 0;
                        while (true) {
                            uint32_t v;
                            asm volatile("ld.acquire.cta.shared.u32 %0, [%1];" : "=r"(v) : "r"(EVC + (lane & 7) * 4) : "memory");
                            if (__all_sync(0xffffffffu, v > (uint32_t)e)) break;
                            if (++spin > 20000000) __trap();
                            __nanosleep(20);
                        }
                        if (lane == 0) {
                            unsigned int* cp = (e == 0) ? cnt_kv(j) : (e == 1) ? cnt_o(m) : cnt_y(m, e == 2 ? 8 : ((j + e - 2) & 7));
                            if (e == 1) fence_async_all();
                            __threadfence();
                            asm volatile("red.relaxed.gpu.global.add.u32 [%0], 1;" :: "l"(cp) : "memory");
                        }
                        __syncwarp();
                    }
                }
            } else {
                {
                    const int t0 = is_main ? (m * 9 + j) : ((bid - NMAIN) * 4 * 9 + 8);
                    const int nt = is_main ? 1 : 4;
                    for (int t = 0; t < nt; t++) {
                        uint4* z = reinterpret_cast<uint4*>(g_yacc + (size_t)((par ^ 1) * 144 + t0 + t * 9) * YT_BYTES);
                        for (int i = lane; i < YT_BYTES / 16; i += 32) z[i] = make_uint4(0, 0, 0, 0);
                    }
                    if (is_main && m == 0) {
                        float* z = g_kv + ((par ^ 1) * 8 + j) * 1440;
                        for (int i = lane; i < 1440; i += 32) z[i] = 0.f;
                    }
                }
            }
        }
    } else {
        asm volatile("setmaxnreg.inc.sync.aligned.u32 240;");
        prof(0);
        Ctx c; c.tph = 0; c.tid_ = v_tid();
        float hc[32], pv[36];
        if (tid >> 7) turn_pass(c);
        auto event = [&](uint32_t ev) {
            __syncwarp();
            if (((c.tid() & 31) == 0)) asm volatile("st.release.cta.shared.u32 [%0], %1;" :: "r"(EVC + (c.tid() >> 3)), "r"(ev) : "memory");
        };
        auto warp_arrive = [&](uint32_t b) { __syncwarp(); if (((c.tid() & 31) == 0)) mbar_arrive(b); };

        auto lrow_off = [&]() { uint32_t t_ = c.tid(); return HA + ((t_ >> 5) * 16 + (t_ & 15)) * 128 + ((((t_ >> 4) & 1) ^ (t_ & 7)) << 4); };
        auto tail_off = [&]() { uint32_t t_ = c.tid(), g = (t_ >> 2) & 7; return XB + ((t_ >> 5) * 16 + g) * 128 + (g << 4) + (t_ & 3) * 4; };
        if (is_main) {
            uint32_t a[128];
            float rs0, rs1;
            uint32_t m00, m11;
            {
                uint32_t tl[16];
                const uint32_t lrow = lrow_off();
                float cs[2][4] = {{0.f, 0.f, 0.f, 0.f}, {0.f, 0.f, 0.f, 0.f}};
                sfor<0, 36>([&](auto KS) {
                    constexpr int ks = decltype(KS)::v;
                    if constexpr (ks % 12 == 0) mbar_wait(bar(B_XFULL + ks / 12), 0);
                    uint32_t* dst = (ks < 32) ? (a + (ks & 31) * 4) : (tl + (ks & 3) * 4);
                    ldsm4((lrow ^ ((ks % 4) << 5)) + (ks / 4) * 16384, dst);
                    mma_ones(cs[ks & 1], dst);
                });
                prof(2);
                float mean0 = (cs[0][0] + cs[1][0]) * (1.0f / 576.0f), mean1 = (cs[0][2] + cs[1][2]) * (1.0f / 576.0f);
                m00 = pack_bf16(mean0, mean0); m11 = pack_bf16(mean1, mean1);
                rs0 = mean0 - bf_lo(m00); rs1 = mean1 - bf_lo(m11);
                rs0 = -144.0f * rs0 * rs0; rs1 = -144.0f * rs1 * rs1;
                const uint32_t tb = tail_off();
                #pragma unroll
                for (int i = 0; i < 16; i++) {
                    const uint32_t w = sub_bf16x2(tl[i], (i & 1) ? m11 : m00);
                    sts32((tb ^ ((i >> 1) << 4)) + (i & 1) * 1024, w);
                    float lo = bf_lo(w), hi = bf_hi(w);
                    if (i & 1) rs1 = fmaf(lo, lo, fmaf(hi, hi, rs1)); else rs0 = fmaf(lo, lo, fmaf(hi, hi, rs0));
                }
                fence_async_smem();
                #pragma unroll
                for (int i = 0; i < 128; i++) a[i] = sub_bf16x2(a[i], (i & 1) ? m11 : m00);
                named_bar(2 + (tid >> 7), 128);
            }
            prof(3);
            auto cm_off = [&]() { uint32_t t_ = c.tid(); return (t_ >> 5) * 256 + (t_ & 31) * 4; };
            {
                float qc[36];
                #pragma unroll
                for (int i = 0; i < 36; i++) { qc[i] = 0.f; pv[i] = 0.f; }
                #pragma unroll 1
                for (int s = 0; s < 3; s++) {
                    run_step<K_QKV>(c, qc, a, [&](auto ST) {
                        constexpr int st = decltype(ST)::v;
                        if (s == 0) {
                            const uint32_t lrow = lrow_off();
                            sfor<(st * 32) / 6, ((st + 1) * 32) / 6>([&](auto I) {
                                constexpr int ks = decltype(I)::v;
                                uint32_t v[4];
                                ldsm4((lrow ^ ((ks % 4) << 5)) + (ks / 4) * 16384, v);
                                #pragma unroll
                                for (int r = 0; r < 4; r++) {
                                    uint32_t w = sub_bf16x2(v[r], (r & 1) ? m11 : m00);
                                    float lo = bf_lo(w), hi = bf_hi(w);
                                    if (r & 1) rs1 = fmaf(lo, lo, fmaf(hi, hi, rs1)); else rs0 = fmaf(lo, lo, fmaf(hi, hi, rs0));
                                }
                            });
                            if constexpr (st == 5) {
                                rs0 += __shfl_xor_sync(0xffffffffu, rs0, 1); rs1 += __shfl_xor_sync(0xffffffffu, rs1, 1);
                                rs0 += __shfl_xor_sync(0xffffffffu, rs0, 2); rs1 += __shfl_xor_sync(0xffffffffu, rs1, 2);
                                rs0 = rsqrtf(fmaxf(rs0 * (1.0f / 576.0f), 0.f) + 1e-5f);
                                rs1 = rsqrtf(fmaxf(rs1 * (1.0f / 576.0f), 0.f) + 1e-5f);
                                named_bar(1, 256);
                            }
                        } else {
                            const uint32_t cm = cm_off();
                            sfor<0, 9>([&](auto B) {
                                constexpr int b = decltype(B)::v;
                                if constexpr ((b * 6) / 9 == st) {
                                    const float v0 = pv[4 * b] * rs0, v1 = pv[4 * b + 1] * rs0, v2 = pv[4 * b + 2] * rs1, v3 = pv[4 * b + 3] * rs1;
                                    if (s == 1) {
                                        sts32(PKT + b * 2048 + cm, pack_bf16(phi(v0), phi(v1)));
                                        sts32(PKT + b * 2048 + cm + 128, pack_bf16(phi(v2), phi(v3)));
                                    } else {
                                        const uint32_t w0 = pack_bf16(v0, v1), w1 = pack_bf16(v2, v3);
                                        if constexpr (b <= 4) { sts32(VT + b * 2048 + cm, w0); sts32(VT + b * 2048 + cm + 128, w1); }
                                        if constexpr (b >= 4) { sts32(VT + (b + 2) * 2048 + cm, w0); sts32(VT + (b + 2) * 2048 + cm + 128, w1); }
                                        if constexpr (b == 0) {
                                            const uint32_t one = (cm & 12) ? 0u : 0x00003F80u;
                                            sts32(VT + 5 * 2048 + cm, one); sts32(VT + 5 * 2048 + cm + 128, one);
                                        }
                                        if constexpr (b == 8) {
                                            const uint32_t z = KVB + c.tid() * 16;
                                            sts128(z, 0, 0, 0, 0); sts128(z + 4096, 0, 0, 0, 0); sts128(z + 8192, 0, 0, 0, 0);
                                            if (z < KVB + 512) sts128(z + 12288, 0, 0, 0, 0);
                                            fence_async_smem();
                                        }
                                    }
                                }
                            });
                        }
                    }, [](auto) {});
                    reg_copy<36>(pv, qc);
                    prof(4 + s);
                }
            }
            {
                #pragma unroll
                for (int i = 0; i < 32; i++) hc[i] = 0.f;
                named_bar(1, 256);
                const uint32_t wgo = ((c.tid() >> 7) * 512);
                wg_fence();
                sfor<0, 8>([&](auto KS) {
                    constexpr int ks = decltype(KS)::v;
                    wg_tt64<(ks ? 1 : 0)>(hc, mkdesc(PKT + ks * 256, 128, 2048, 0) + wgo,
                                          mkdesc(VT + ks * 256, 128, 2048, 0) + wgo + (wgo >> 2));
                });
                wg_commit();
                const uint32_t pq = PQT + cm_off() + ((c.tid() >> 7) * 512) * 16;
                sfor<0, 9>([&](auto B) {
                    constexpr int b = decltype(B)::v;
                    sts32(pq + b * 1024, pack_bf16(phi(pv[4 * b] * rs0), phi(pv[4 * b + 1] * rs0)));
                    sts32(pq + b * 1024 + 128, pack_bf16(phi(pv[4 * b + 2] * rs1), phi(pv[4 * b + 3] * rs1)));
                });
                fence_async_smem();
                wg_wait<0>();
                reg_fence<32>(hc);
                reg_copy<24>(pv, hc);
            }
            prof(7);
            rs0 *= 0.5f; rs1 *= 0.5f;
            mbar_wait(bar(B_INIT), 0);
            auto gelun = [&](auto B0, auto B1, uint32_t bofs, uint32_t* w) {
                constexpr int b0 = decltype(B0)::v, nb = decltype(B1)::v - b0;
                float2 bv[nb];
                #pragma unroll
                for (int i = 0; i < nb; i++) bv[i] = lds64f(bofs + (b0 + i) * 32);
                #pragma unroll
                for (int i = 0; i < nb; i++) {
                    const int b = b0 + i;
                    w[2 * i]     = pack_bf16(gelu_h(fmaf(pv[4 * b], rs0, bv[i].x)), gelu_h(fmaf(pv[4 * b + 1], rs0, bv[i].y)));
                    w[2 * i + 1] = pack_bf16(gelu_h(fmaf(pv[4 * b + 2], rs1, bv[i].x)), gelu_h(fmaf(pv[4 * b + 3], rs1, bv[i].y)));
                }
            };
            auto spill_off = [&]() { uint32_t t_ = c.tid(); return HA + (t_ >> 7) * 8192 + (t_ & 127) * 8; };
            auto reload = [&](auto S0, auto S1) {
                const uint32_t spill = spill_off();
                sfor<decltype(S0)::v * 8, decltype(S1)::v * 8>([&](auto Q) {
                    constexpr int q = decltype(Q)::v;
                    lds64(spill + (q / 8) * 16384 + (q % 8) * 1024, a + q * 2);
                });
            };
            #pragma unroll 1
            for (int idx = 0; idx < 18; idx++) {
                run_step<K_H>(c, hc, a, [&](auto ST) {
                    constexpr int st = decltype(ST)::v;
                    if (idx >= 10) {
                        if constexpr (st < 2) {
                            const uint32_t b_ = v_bid();
                            const uint32_t chunk = (idx == 10) ? 8 : ((b_ + idx - 10) & 7);
                            unsigned char* yp = g_yacc + ((v_epoch() & 1) * 144 + (b_ >> 3) * 9 + chunk) * YT_BYTES + c.tid() * 16;
                            sfor<2 * st, 2 * st + 2>([&](auto Q) {
                                constexpr int q = decltype(Q)::v;
                                asm volatile("red.global.add.noftz.v4.bf16x2 [%0], {%1,%2,%3,%4};" :: "l"(yp + q * 4096),
                                             "r"(pack_bf16(pv[8 * q], pv[8 * q + 1])), "r"(pack_bf16(pv[8 * q + 2], pv[8 * q + 3])),
                                             "r"(pack_bf16(pv[8 * q + 4], pv[8 * q + 5])), "r"(pack_bf16(pv[8 * q + 6], pv[8 * q + 7])) : "memory");
                            });
                            if constexpr (st == 1) event(idx - 7);
                        }
                    } else if (idx >= 1) {
                        const uint32_t bofs = B1S + (idx - 1) * 256 + (c.tid() & 3) * 8;
                        if (idx < 9) {
                            if constexpr (st == 0) {
                                if (idx == OSTEP_AT + 1) {
                                    if ((c.tid() & 31) == 0) asm volatile("cp.async.bulk.wait_group 0;" ::: "memory");
                                    event(2);
                                }
                            }
                            const uint32_t spill = spill_off() + (idx - 1) * 16384;
                            constexpr int b0 = st * 3, b1 = (st == 2 ? 8 : st * 3 + 3);
                            uint32_t w[6];
                            gelun(IC<b0>{}, IC<b1>{}, bofs, w);
                            #pragma unroll
                            for (int b = b0; b < b1; b++) sts64(spill + b * 1024, w[2 * (b - b0)], w[2 * (b - b0) + 1]);
                        } else {
                            if constexpr (st < 2) {
                                const uint32_t tb = tail_off();
                                uint32_t w[8];
                                gelun(IC<st * 4>{}, IC<st * 4 + 4>{}, bofs, w);
                                #pragma unroll
                                for (int i = 0; i < 4; i++) { sts32(tb ^ ((st * 4 + i) << 4), w[2 * i]); sts32((tb ^ ((st * 4 + i) << 4)) + 1024, w[2 * i + 1]); }
                            }
                            if constexpr (st == 1) { fence_async_smem(); named_bar(2 + (c.tid() >> 7), 128); }
                        }
                    } else {
                        if constexpr (st < 2) {
                            constexpr int hf = st;
                            const int t_ = c.tid(), wg = t_ >> 7, t = t_ & 3;
                            float* dst = g_kv + ((v_epoch() & 1) * 8 + (v_bid() & 7)) * 1440;
                            const int d = wg * 32 + ((t_ >> 5) & 3) * 16 + ((t_ >> 2) & 7) + hf * 8;
                            const bool dv = wg ? (d >= 36 && d < 72) : (d < 36);
                            const int e00 = wg * 24 + 2 * t - (d / 18) * 18;
                            float* dp = dst + d * 20 + e00;
                            #pragma unroll
                            for (int i = 0; i < 6; i++) {
                                const int e = e00 + i * 8;
                                const bool blk = wg ? (i >= 1) : (i <= 4);
                                if (dv && blk && e >= 0 && e < 18)
                                    asm volatile("red.global.add.v2.f32 [%0], {%1,%2};" :: "l"(dp + i * 8), "f"(pv[4 * i + 2 * hf]), "f"(pv[4 * i + 2 * hf + 1]) : "memory");
                            }
                            if (dv && t == 0) atomicAdd(dst + d * 20 + 18, wg ? pv[2 * hf] : pv[20 + 2 * hf]);
                            if constexpr (st == 1) event(1);
                        }
                    }
                }, [&](auto ST) {
                    constexpr int st = decltype(ST)::v;
                    if (idx == 8) {
                        reload(IC<3 * st>{}, IC<(st == 2 ? 8 : 3 * st + 3)>{});
                        if constexpr (st == 2) warp_arrive(bar(B_OFREE));
                    }
                });
                reg_copy<32>(pv, hc);
                prof(8 + idx);
                if (idx == OSTEP_AT) {
                    mbar_wait(bar(B_KVB), 0);
                    prof(34);
                    const uint32_t pqo = (c.tid() >> 7) * 576;
                    const int t_ = c.tid(), b_ = v_bid(), t = t_ & 3, l4 = t_ & 28;
                    const uint32_t op = OST + ((t_ >> 5) * 16 + ((t_ >> 2) & 7)) * 144 + t * 4;
                    float r3[2];
                    sfor<0, 2>([&](auto PS) {
                        constexpr int ps = decltype(PS)::v;
                        wg_fence();
                        sfor<0, 5>([&](auto KS) {
                            constexpr int ks = decltype(KS)::v;
                            wg_ss64<(ks ? 1 : 0)>(hc, mkdesc(PQT + ks * 2048, ks == 4 ? 0 : 1024, 128, 0) + pqo, mkdesc(KVB + ps * 8 * 1280 + ks * 256, 128, 1280, 0));
                        });
                        wg_commit();
                        wg_wait<0>();
                        reg_fence<32>(hc);
                        #pragma unroll
                        for (int hf = 0; hf < 2; hf++) {
                            if constexpr (ps == 0) {
                                float r[4];
                                r[0] = rcp(__shfl_sync(0xffffffffu, hc[2 * hf], l4) + 1e-6f);
                                r[1] = rcp(__shfl_sync(0xffffffffu, hc[1 + 2 * hf], l4) + 1e-6f);
                                r[2] = rcp(__shfl_sync(0xffffffffu, hc[2 * hf], l4 + 1) + 1e-6f);
                                r[3] = rcp(__shfl_sync(0xffffffffu, hc[1 + 2 * hf], l4 + 1) + 1e-6f);
                                r3[hf] = r[3];
                                #pragma unroll
                                for (int i = 0; i < 7; i++) {
                                    float rr = (i < 2) ? r[0] : (i == 2) ? (t < 1 ? r[0] : r[1]) : (i == 3) ? r[1] : (i == 4) ? (t < 2 ? r[1] : r[2])
                                             : (i == 5) ? r[2] : (t < 3 ? r[2] : r[3]);
                                    sts32(op + hf * 8 * 144 + i * 16, pack_bf16(hc[4 * i + 4 + 2 * hf] * rr, hc[4 * i + 5 + 2 * hf] * rr));
                                }
                            } else {
                                #pragma unroll
                                for (int i = 0; i < 2; i++)
                                    sts32(op + hf * 8 * 144 + 112 + i * 16, pack_bf16(hc[4 * i + 2 * hf] * r3[hf], hc[4 * i + 1 + 2 * hf] * r3[hf]));
                            }
                        }
                    });
                    fence_async_smem();
                    __syncwarp();
                    if ((t_ & 31) == 0) {
                        asm volatile("cp.async.bulk.tensor.2d.global.shared::cta.bulk_group [%0, {%2, %3}], [%1];"
                                     :: "l"(&tm_ost), "r"(OST + (t_ >> 5) * 2304), "r"((b_ & 7) * 72), "r"((b_ >> 3) * 128 + (t_ >> 5) * 16) : "memory");
                        asm volatile("cp.async.bulk.commit_group;" ::: "memory");
                    }
                }
            }
        }
        if (is_main) warp_arrive(bar(B_O8FREE));
        else {
            mbar_wait(bar(B_INIT), 0);
            #pragma unroll
            for (int i = 0; i < 32; i++) { asm volatile("mov.b32 %0, 0;" : "=f"(hc[i])); asm volatile("mov.b32 %0, 0;" : "=f"(pv[i])); }
        }
        auto add_b2 = [&]() {
            #pragma unroll
            for (int b = 0; b < 8; b++) {
                float2 bv = lds64f(B2S + b * 32 + (c.tid() & 3) * 8);
                pv[4 * b] += bv.x; pv[4 * b + 1] += bv.y; pv[4 * b + 2] += bv.x; pv[4 * b + 3] += bv.y;
            }
        };
        auto load_xy = [&](int ftile, int nrdy, uint32_t* xr, uint32_t* yv) {
            const int mt = ftile / 9, ch = ftile - mt * 9;
            const uint32_t t_ = c.tid();
            const __nv_bfloat16* xp = p.x + (size_t)(mt * 128 + (t_ >> 5) * 16 + ((t_ >> 2) & 7)) * DM + ch * 64 + 2 * (t_ & 3);
            #pragma unroll
            for (int i = 0; i < 8; i++) {
                asm volatile("ld.global.nc.u32 %0, [%1];" : "=r"(xr[2 * i]) : "l"(xp + i * 8));
                asm volatile("ld.global.nc.u32 %0, [%1];" : "=r"(xr[2 * i + 1]) : "l"(xp + 8 * DM + i * 8));
            }
            prof(26);
            smem_wait_gt(EPO + 4, nrdy);
            prof(27);
            const unsigned char* yp = g_yacc + ((v_epoch() & 1) * 144 + ftile) * YT_BYTES + t_ * 16;
            #pragma unroll
            for (int q = 0; q < YT_BYTES / 4096; q++)
                asm volatile("ld.global.cg.v4.u32 {%0,%1,%2,%3}, [%4];" : "=r"(yv[4 * q]), "=r"(yv[4 * q + 1]), "=r"(yv[4 * q + 2]), "=r"(yv[4 * q + 3]) : "l"(yp + q * 4096) : "memory");
        };
        auto gate = [&](const uint32_t* yv) {
            #pragma unroll
            for (int i = 0; i < 16; i++) { pv[2 * i] += bf_lo(yv[i]); pv[2 * i + 1] += bf_hi(yv[i]); }
            #pragma unroll
            for (int i = 0; i < 32; i++) { const float h = 0.5f * pv[i]; pv[i] = fmaf(h, tanh_ap(h), h); }
        };
        auto store_out = [&](int ftile, const uint32_t* xr) {
            const int mt = ftile / 9, ch = ftile - mt * 9;
            const uint32_t t_ = c.tid();
            __nv_bfloat16* op = p.out + (size_t)(mt * 128 + (t_ >> 5) * 16 + ((t_ >> 2) & 7)) * DM + ch * 64 + 2 * (t_ & 3);
            #pragma unroll
            for (int b = 0; b < 8; b++) {
                *reinterpret_cast<uint32_t*>(op + b * 8) =
                    pack_bf16(fmaf(hc[4 * b], pv[4 * b], bf_lo(xr[2 * b])), fmaf(hc[4 * b + 1], pv[4 * b + 1], bf_hi(xr[2 * b])));
                *reinterpret_cast<uint32_t*>(op + 8 * DM + b * 8) =
                    pack_bf16(fmaf(hc[4 * b + 2], pv[4 * b + 2], bf_lo(xr[2 * b + 1])), fmaf(hc[4 * b + 3], pv[4 * b + 3], bf_hi(xr[2 * b + 1])));
            }
        };
        const int njob = is_main ? 1 : 4;
        #pragma unroll 1
        for (int job = 0; job < njob; job++) {
            const uint32_t jpar = job & 1;
            const uint32_t b_ = v_bid();
            const bool mainf = b_ < NMAIN;
            const int ftile = (b_ >> 3) * 9 + (b_ & 7);
            uint32_t oa[128];
            {
                mbar_wait(bar(B_OFULL), jpar);
                const uint32_t lrow = lrow_off();
                sfor<0, 32>([&](auto KS) {
                    constexpr int ks = decltype(KS)::v;
                    ldsm4((lrow ^ ((ks % 4) << 5)) + (ks / 4) * 16384, oa + ks * 4);
                });
                warp_arrive(bar(B_OFREE));
                if (job) c.tph ^= 1;
            }
            c.pf = false;
            run_step<K_H>(c, hc, oa, [&](auto ST) {
                constexpr int st = decltype(ST)::v;
                if (mainf) {
                    if constexpr (st == 0) add_b2();
                    else if constexpr (st == 1) load_xy(ftile, 0, oa, oa + 16);
                    else { prof(28); gate(oa + 16); prof(29); }
                }
                if constexpr (st == 1) mbar_wait(bar(B_O8FULL), jpar);
            }, [](auto) {}, job == njob - 1);
            prof(30);
            if (mainf) {
                store_out(ftile, oa);
            } else {
                warp_arrive(bar(B_O8FREE));
                uint4* sp = reinterpret_cast<uint4*>(g_s8) + ((b_ - NMAIN) * 4 + job) * 1024 + c.tid();
                #pragma unroll
                for (int q = 0; q < 4; q++)
                    sp[q * 256] = make_uint4(pack_bf16(hc[8 * q], hc[8 * q + 1]), pack_bf16(hc[8 * q + 2], hc[8 * q + 3]),
                                             pack_bf16(hc[8 * q + 4], hc[8 * q + 5]), pack_bf16(hc[8 * q + 6], hc[8 * q + 7]));
                prof(8 + job);
            }
        }
        if (!is_main) {
            #pragma unroll 1
            for (int job = 0; job < 4; job++) {
                const int tile = (v_bid() - NMAIN) * 4 + job;
                uint32_t xr[16], yv[YT_BYTES / 1024];
                const uint4* sp = reinterpret_cast<const uint4*>(g_s8) + tile * 1024 + c.tid();
                #pragma unroll
                for (int q = 0; q < 4; q++) {
                    const uint4 u = __ldcg(sp + q * 256);
                    hc[8 * q] = bf_lo(u.x); hc[8 * q + 1] = bf_hi(u.x); hc[8 * q + 2] = bf_lo(u.y); hc[8 * q + 3] = bf_hi(u.y);
                    hc[8 * q + 4] = bf_lo(u.z); hc[8 * q + 5] = bf_hi(u.z); hc[8 * q + 6] = bf_lo(u.w); hc[8 * q + 7] = bf_hi(u.w);
                }
                #pragma unroll
                for (int i = 0; i < 32; i++) pv[i] = 0.f;
                add_b2();
                load_xy(tile * 9 + 8, job, xr, yv);
                gate(yv);
                store_out(tile * 9 + 8, xr);
                prof(12 + job);
            }
        }
        prof(40);
        if (c.tid() == 0) g_epoch[v_bid()] = v_epoch() + 1;
    }
}

typedef CUresult (*EncodeFn)(CUtensorMap*, CUtensorMapDataType, cuuint32_t, void*, const cuuint64_t*, const cuuint64_t*,
                             const cuuint32_t*, const cuuint32_t*, CUtensorMapInterleave, CUtensorMapSwizzle,
                             CUtensorMapL2promotion, CUtensorMapFloatOOBfill);

void make_map(EncodeFn enc, CUtensorMap* tm, const void* base, int rows, int cols, int box_rows, int box_cols = 64, bool swz = true) {
    cuuint64_t gdim[2] = {(cuuint64_t)cols, (cuuint64_t)rows};
    cuuint64_t gstr[1] = {(cuuint64_t)cols * 2};
    cuuint32_t box[2] = {(cuuint32_t)box_cols, (cuuint32_t)box_rows};
    cuuint32_t estr[2] = {1, 1};
    enc(tm, CU_TENSOR_MAP_DATA_TYPE_BFLOAT16, 2, const_cast<void*>(base), gdim, gstr, box, estr, CU_TENSOR_MAP_INTERLEAVE_NONE,
        swz ? CU_TENSOR_MAP_SWIZZLE_128B : CU_TENSOR_MAP_SWIZZLE_NONE, CU_TENSOR_MAP_L2_PROMOTION_L2_128B, CU_TENSOR_MAP_FLOAT_OOB_FILL_NONE);
}

}

extern "C" void kernel_launch(void* const* d_in, const int* in_sizes, int n_in, void* d_out, int out_size) {
    static EncodeFn enc = nullptr;
    static void* o_ptr = nullptr;
    if (!enc) {
        void* fn = nullptr;
        cudaDriverEntryPointQueryResult qr;
        cudaGetDriverEntryPoint("cuTensorMapEncodeTiled", &fn, cudaEnableDefault, &qr);
        enc = (EncodeFn)fn;
        cudaGetSymbolAddress(&o_ptr, g_o);
        cudaFuncSetAttribute(fused_kernel, cudaFuncAttributeMaxDynamicSharedMemorySize, SMEM_BYTES);
    }
    Params p;
    p.x = (const __nv_bfloat16*)d_in[0];
    p.wqkv = (const __nv_bfloat16*)d_in[1];
    p.wo = (const __nv_bfloat16*)d_in[2];
    p.w1 = (const __nv_bfloat16*)d_in[4];
    p.b1 = (const __nv_bfloat16*)d_in[5];
    p.w2 = (const __nv_bfloat16*)d_in[6];
    p.b2 = (const __nv_bfloat16*)d_in[7];
    p.out = (__nv_bfloat16*)d_out;
    CUtensorMap tm_x, tm_w1, tm_w2, tm_wo, tm_o, tm_qkv, tm_qkve, tm_ost;
    make_map(enc, &tm_ost, o_ptr, SEQ, DM, 16, 72, false);
    make_map(enc, &tm_qkv, p.wqkv, DM, 3 * DM, 96);
    make_map(enc, &tm_qkve, p.wqkv, DM, 3 * DM, 96, 8);
    make_map(enc, &tm_x, p.x, SEQ, DM, 128);
    make_map(enc, &tm_w1, p.w1, DM, FF, 192);
    make_map(enc, &tm_w2, p.w2, FF, DM, 192);
    make_map(enc, &tm_wo, p.wo, DM, DM, 192);
    make_map(enc, &tm_o, o_ptr, SEQ, DM, 128);
    fused_kernel<<<NMAIN + NAUX, 384, SMEM_BYTES>>>(tm_x, tm_w1, tm_w2, tm_wo, tm_o, tm_qkv, tm_qkve, tm_ost, p);
}
```

```cpp
#include <cuda_runtime.h>
#include <cuda.h>
#include <cuda_bf16.h>
#include <stdint.h>

#define OSTEP_AT 4
#define KNOB_A 1
#define KNOB_B 0
#define PF1_NS 1500
#define PF2_NS 2000
#define PFIDX 3
#define PF3_NS 800
#define EARLY_REL 0
#define PF0_NS 1200
#define YF32 0

namespace {
constexpr int WAIT_ITERS = 3000000;

constexpr int SEQ = 2048, DM = 576, FF = 4608;
constexpr int NMAIN = 128, NAUX = 4;

constexpr uint32_t SB    = 0x400;
constexpr uint32_t HA    = SB;
constexpr uint32_t XB    = SB + 131072;
constexpr uint32_t RING  = SB + 147456;
constexpr uint32_t SLOT  = 24576;
constexpr uint32_t MISC  = SB + 221184;
constexpr uint32_t BARS  = MISC;
constexpr uint32_t B1S   = MISC + 512;
constexpr uint32_t B2S   = MISC + 2816;
constexpr uint32_t EPO   = MISC + 3072;
constexpr uint32_t EVC   = MISC + 3104;
constexpr uint32_t SMEM_BYTES = 221184 + 3200 + 512;
constexpr uint32_t PKT   = HA + 32768;
constexpr uint32_t VT    = HA + 51200;
constexpr uint32_t OST   = HA + 79872;
constexpr uint32_t PQT   = HA + 98304;
constexpr uint32_t KVB   = HA + 116736;

enum { B_FULL = 0, B_EMPTY = 3, B_XFULL = 6, B_OFULL = 9, B_O8FULL = 10, B_OFREE = 11, B_O8FREE = 12, B_KVB = 13, B_INIT = 14, B_COUNT = 15 };
__device__ __forceinline__ constexpr uint32_t bar(int i) { return BARS + 8u * i; }

constexpr int YT_BYTES = YF32 ? 32768 : 16384;
__device__ __align__(1024) __nv_bfloat16 g_o[SEQ * DM];
__device__ __align__(1024) unsigned char g_yacc[2 * 16 * 9 * YT_BYTES];
__device__ __align__(128) float g_kv[2 * 8 * 72 * 20];
__device__ __align__(128) unsigned int g_s8[16 * 4096];
__device__ __align__(128) unsigned int g_cnt[(8 + 16 + 16 * 9) * 8];
__device__ unsigned int g_epoch[NMAIN + NAUX];
__device__ __forceinline__ unsigned int* cnt_kv(int j) { return g_cnt + j * 8; }
__device__ __forceinline__ unsigned int* cnt_o(int m) { return g_cnt + (8 + m) * 8; }
__device__ __forceinline__ unsigned int* cnt_y(int m, int c) { return g_cnt + (24 + m * 9 + c) * 8; }

__device__ __forceinline__ void mbar_init(uint32_t b, uint32_t cnt) { asm volatile("mbarrier.init.shared::cta.b64 [%0], %1;" :: "r"(b), "r"(cnt)); }
__device__ __forceinline__ void mbar_expect_tx(uint32_t b, uint32_t bytes) { asm volatile("mbarrier.arrive.expect_tx.shared::cta.b64 _, [%0], %1;" :: "r"(b), "r"(bytes) : "memory"); }
__device__ __forceinline__ void mbar_arrive(uint32_t b) { asm volatile("mbarrier.arrive.shared::cta.b64 _, [%0];" :: "r"(b) : "memory"); }
__device__ __forceinline__ void prof(int) {}
__device__ __forceinline__ void mbar_wait(uint32_t b, uint32_t parity) {
    asm volatile("{\n.reg .pred p;\n.reg .u32 c;\nmov.u32 c, 0;\n"
                 "WAIT_LOOP:\nmbarrier.try_wait.parity.shared::cta.b64 p, [%0], %1;\n@p bra WAIT_DONE;\n"
                 "add.u32 c, c, 1;\nsetp.lt.u32 p, c, 4000000;\n@p bra WAIT_LOOP;\ntrap;\nWAIT_DONE:\n}"
                 :: "r"(b), "r"(parity) : "memory");
}
__device__ __forceinline__ void smem_wait_gt(uint32_t addr, uint32_t val) {
    asm volatile("{\n.reg .pred p;\n.reg .u32 c, v;\nmov.u32 c, 0;\n"
                 "SW_LOOP:\nld.acquire.cta.shared.u32 v, [%0];\nsetp.gt.u32 p, v, %1;\n@p bra SW_DONE;\n"
                 "add.u32 c, c, 1;\nsetp.lt.u32 p, c, 100000000;\n@p bra SW_LOOP;\ntrap;\nSW_DONE:\n}"
                 :: "r"(addr), "r"(val) : "memory");
}
__device__ __forceinline__ void tma_2d(uint32_t dst, const CUtensorMap* tm, uint32_t b, int c0, int c1) {
    asm volatile("cp.async.bulk.tensor.2d.shared::cluster.global.mbarrier::complete_tx::bytes [%0], [%1, {%3, %4}], [%2];"
                 :: "r"(dst), "l"(tm), "r"(b), "r"(c0), "r"(c1) : "memory");
}
__device__ __forceinline__ void fence_async_smem() { asm volatile("fence.proxy.async.shared::cta;" ::: "memory"); }
__device__ __forceinline__ void fence_async_all() { asm volatile("fence.proxy.async;" ::: "memory"); }
__device__ __forceinline__ void named_bar(int id, int n) { asm volatile("bar.sync %0, %1;" :: "r"(id), "r"(n) : "memory"); }
__device__ __forceinline__ void wg_fence() { asm volatile("wgmma.fence.sync.aligned;" ::: "memory"); }
__device__ __forceinline__ void wg_commit() { asm volatile("wgmma.commit_group.sync.aligned;" ::: "memory"); }
template<int N> __device__ __forceinline__ void wg_wait() { asm volatile("wgmma.wait_group.sync.aligned %0;" :: "n"(N) : "memory"); }
template<int N> __device__ __forceinline__ void reg_fence(float* d) {
    #pragma unroll
    for (int i = 0; i < N; i++) asm volatile("" : "+f"(d[i]) :: "memory");
}
template<int N> __device__ __forceinline__ void reg_copy(float* d, const float* s) {
    #pragma unroll
    for (int i = 0; i < N; i++) asm volatile("mov.b32 %0, %1;" : "=f"(d[i]) : "f"(s[i]));
}
__device__ __forceinline__ uint32_t pack_bf16(float lo, float hi) { uint32_t r; asm("cvt.rn.bf16x2.f32 %0, %1, %2;" : "=r"(r) : "f"(hi), "f"(lo)); return r; }
__device__ __forceinline__ float bf_lo(uint32_t v) { return __uint_as_float(v << 16); }
__device__ __forceinline__ float bf_hi(uint32_t v) { return __uint_as_float(v & 0xffff0000u); }
__device__ __forceinline__ uint32_t sub_bf16x2(uint32_t a, uint32_t b) { uint32_t r; asm("sub.rn.bf16x2 %0, %1, %2;" : "=r"(r) : "r"(a), "r"(b)); return r; }
__device__ __forceinline__ float ex2(float x) { float r; asm("ex2.approx.ftz.f32 %0, %1;" : "=f"(r) : "f"(x)); return r; }
__device__ __forceinline__ float rcp(float x) { float r; asm("rcp.approx.ftz.f32 %0, %1;" : "=f"(r) : "f"(x)); return r; }
__device__ __forceinline__ float tanh_ap(float x) { float r; asm("tanh.approx.f32 %0, %1;" : "=f"(r) : "f"(x)); return r; }
__device__ __forceinline__ void sts32(uint32_t a, uint32_t v) { asm volatile("st.shared.b32 [%0], %1;" :: "r"(a), "r"(v)); }
__device__ __forceinline__ void sts128(uint32_t a, uint32_t x, uint32_t y, uint32_t z, uint32_t w) { asm volatile("st.shared.v4.b32 [%0], {%1,%2,%3,%4};" :: "r"(a), "r"(x), "r"(y), "r"(z), "r"(w)); }
__device__ __forceinline__ void sts64(uint32_t a, uint32_t x, uint32_t y) { asm volatile("st.shared.v2.b32 [%0], {%1,%2};" :: "r"(a), "r"(x), "r"(y)); }
__device__ __forceinline__ void lds64(uint32_t a, uint32_t* v) { asm volatile("ld.shared.v2.b32 {%0,%1}, [%2];" : "=r"(v[0]), "=r"(v[1]) : "r"(a)); }
__device__ __forceinline__ void lds128(uint32_t a, uint32_t* v) { asm volatile("ld.shared.v4.b32 {%0,%1,%2,%3}, [%4];" : "=r"(v[0]), "=r"(v[1]), "=r"(v[2]), "=r"(v[3]) : "r"(a) : "memory"); }
__device__ __forceinline__ float2 lds64f(uint32_t a) { float2 v; asm("ld.shared.v2.f32 {%0,%1}, [%2];" : "=f"(v.x), "=f"(v.y) : "r"(a)); return v; }
__device__ __forceinline__ void ldsm4(uint32_t a, uint32_t* v) {
    asm volatile("ldmatrix.sync.aligned.m8n8.x4.shared.b16 {%0,%1,%2,%3}, [%4];" : "=r"(v[0]), "=r"(v[1]), "=r"(v[2]), "=r"(v[3]) : "r"(a));
}
__device__ __forceinline__ void mma_ones(float* c, const uint32_t* a) {
    const uint32_t one2 = 0x3F803F80u;
    asm volatile("mma.sync.aligned.m16n8k16.row.col.f32.bf16.bf16.f32 {%0,%1,%2,%3}, {%4,%5,%6,%7}, {%8,%8}, {%0,%1,%2,%3};"
                 : "+f"(c[0]), "+f"(c[1]), "+f"(c[2]), "+f"(c[3]) : "r"(a[0]), "r"(a[1]), "r"(a[2]), "r"(a[3]), "r"(one2));
}
__device__ __forceinline__ void mma_bf16(float* c, const uint32_t* a, uint32_t b0, uint32_t b1) {
    asm volatile("mma.sync.aligned.m16n8k16.row.col.f32.bf16.bf16.f32 {%0,%1,%2,%3}, {%4,%5,%6,%7}, {%8,%9}, {%0,%1,%2,%3};"
                 : "+f"(c[0]), "+f"(c[1]), "+f"(c[2]), "+f"(c[3]) : "r"(a[0]), "r"(a[1]), "r"(a[2]), "r"(a[3]), "r"(b0), "r"(b1));
}
__device__ __forceinline__ unsigned int ld_acquire(const unsigned int* p) { unsigned int v; asm volatile("ld.acquire.gpu.global.u32 %0, [%1];" : "=r"(v) : "l"(p) : "memory"); return v; }
__device__ __forceinline__ void wait_cnt(const unsigned int* p, unsigned int target) {
    for (int i = 0; i < WAIT_ITERS; i++) {
        if ((int)(ld_acquire(p) - target) >= 0) return;
        __nanosleep(40);
    }
    __trap();
}
__device__ __forceinline__ uint32_t v_tid() { uint32_t r; asm volatile("mov.u32 %0, %%tid.x;" : "=r"(r)); return r; }
__device__ __forceinline__ uint32_t v_bid() { uint32_t r; asm volatile("mov.u32 %0, %%ctaid.x;" : "=r"(r)); return r; }
__device__ __forceinline__ uint32_t v_epoch() { uint32_t r; asm volatile("ld.shared.u32 %0, [%1];" : "=r"(r) : "r"(EPO)); return r; }
__device__ __forceinline__ void prefetch_l2(const void* p) { asm volatile("prefetch.global.L2 [%0];" :: "l"(p)); }

__host__ __device__ constexpr uint64_t mkdesc(uint32_t addr, uint32_t lbo, uint32_t sbo, uint32_t swz) {
    return (uint64_t)((addr & 0x3FFFF) >> 4) | ((uint64_t)((lbo >> 4) & 0x3FFF) << 16) | ((uint64_t)((sbo >> 4) & 0x3FFF) << 32) | ((uint64_t)swz << 62);
}

template<int SD> __device__ __forceinline__ void wg_rs64(float* d, const uint32_t* a, uint64_t bd) {
  if constexpr (SD) {
    asm volatile("{\n.reg .pred p;\nsetp.eq.b32 p, 0, 0;\n"
    "wgmma.mma_async.sync.aligned.m64n64k16.f32.bf16.bf16 {%0,%1,%2,%3,%4,%5,%6,%7,%8,%9,%10,%11,%12,%13,%14,%15,%16,%17,%18,%19,%20,%21,%22,%23,%24,%25,%26,%27,%28,%29,%30,%31}, {%32,%33,%34,%35}, %36, p, 1, 1, 1;\n}"
    : "+f"(d[0]),"+f"(d[1]),"+f"(d[2]),"+f"(d[3]),"+f"(d[4]),"+f"(d[5]),"+f"(d[6]),"+f"(d[7]),"+f"(d[8]),"+f"(d[9]),"+f"(d[10]),"+f"(d[11]),"+f"(d[12]),"+f"(d[13]),"+f"(d[14]),"+f"(d[15]),"+f"(d[16]),"+f"(d[17]),"+f"(d[18]),"+f"(d[19]),"+f"(d[20]),"+f"(d[21]),"+f"(d[22]),"+f"(d[23]),"+f"(d[24]),"+f"(d[25]),"+f"(d[26]),"+f"(d[27]),"+f"(d[28]),"+f"(d[29]),"+f"(d[30]),"+f"(d[31])
    : "r"(a[0]),"r"(a[1]),"r"(a[2]),"r"(a[3]), "l"(bd));
  } else {
    asm volatile("{\n.reg .pred p;\nsetp.ne.b32 p, 0, 0;\n"
    "wgmma.mma_async.sync.aligned.m64n64k16.f32.bf16.bf16 {%0,%1,%2,%3,%4,%5,%6,%7,%8,%9,%10,%11,%12,%13,%14,%15,%16,%17,%18,%19,%20,%21,%22,%23,%24,%25,%26,%27,%28,%29,%30,%31}, {%32,%33,%34,%35}, %36, p, 1, 1, 1;\n}"
    : "+f"(d[0]),"+f"(d[1]),"+f"(d[2]),"+f"(d[3]),"+f"(d[4]),"+f"(d[5]),"+f"(d[6]),"+f"(d[7]),"+f"(d[8]),"+f"(d[9]),"+f"(d[10]),"+f"(d[11]),"+f"(d[12]),"+f"(d[13]),"+f"(d[14]),"+f"(d[15]),"+f"(d[16]),"+f"(d[17]),"+f"(d[18]),"+f"(d[19]),"+f"(d[20]),"+f"(d[21]),"+f"(d[22]),"+f"(d[23]),"+f"(d[24]),"+f"(d[25]),"+f"(d[26]),"+f"(d[27]),"+f"(d[28]),"+f"(d[29]),"+f"(d[30]),"+f"(d[31])
    : "r"(a[0]),"r"(a[1]),"r"(a[2]),"r"(a[3]), "l"(bd));
  }
}
template<int SD> __device__ __forceinline__ void wg_ss64(float* d, uint64_t ad, uint64_t bd) {
  if constexpr (SD) {
    asm volatile("{\n.reg .pred p;\nsetp.eq.b32 p, 0, 0;\n"
    "wgmma.mma_async.sync.aligned.m64n64k16.f32.bf16.bf16 {%0,%1,%2,%3,%4,%5,%6,%7,%8,%9,%10,%11,%12,%13,%14,%15,%16,%17,%18,%19,%20,%21,%22,%23,%24,%25,%26,%27,%28,%29,%30,%31}, %32, %33, p, 1, 1, 0, 1;\n}"
    : "+f"(d[0]),"+f"(d[1]),"+f"(d[2]),"+f"(d[3]),"+f"(d[4]),"+f"(d[5]),"+f"(d[6]),"+f"(d[7]),"+f"(d[8]),"+f"(d[9]),"+f"(d[10]),"+f"(d[11]),"+f"(d[12]),"+f"(d[13]),"+f"(d[14]),"+f"(d[15]),"+f"(d[16]),"+f"(d[17]),"+f"(d[18]),"+f"(d[19]),"+f"(d[20]),"+f"(d[21]),"+f"(d[22]),"+f"(d[23]),"+f"(d[24]),"+f"(d[25]),"+f"(d[26]),"+f"(d[27]),"+f"(d[28]),"+f"(d[29]),"+f"(d[30]),"+f"(d[31])
    : "l"(ad), "l"(bd));
  } else {
    asm volatile("{\n.reg .pred p;\nsetp.ne.b32 p, 0, 0;\n"
    "wgmma.mma_async.sync.aligned.m64n64k16.f32.bf16.bf16 {%0,%1,%2,%3,%4,%5,%6,%7,%8,%9,%10,%11,%12,%13,%14,%15,%16,%17,%18,%19,%20,%21,%22,%23,%24,%25,%26,%27,%28,%29,%30,%31}, %32, %33, p, 1, 1, 0, 1;\n}"
    : "+f"(d[0]),"+f"(d[1]),"+f"(d[2]),"+f"(d[3]),"+f"(d[4]),"+f"(d[5]),"+f"(d[6]),"+f"(d[7]),"+f"(d[8]),"+f"(d[9]),"+f"(d[10]),"+f"(d[11]),"+f"(d[12]),"+f"(d[13]),"+f"(d[14]),"+f"(d[15]),"+f"(d[16]),"+f"(d[17]),"+f"(d[18]),"+f"(d[19]),"+f"(d[20]),"+f"(d[21]),"+f"(d[22]),"+f"(d[23]),"+f"(d[24]),"+f"(d[25]),"+f"(d[26]),"+f"(d[27]),"+f"(d[28]),"+f"(d[29]),"+f"(d[30]),"+f"(d[31])
    : "l"(ad), "l"(bd));
  }
}
template<int SD> __device__ __forceinline__ void wg_rs72(float* d, const uint32_t* a, uint64_t bd) {
  if constexpr (SD) {
    asm volatile("{\n.reg .pred p;\nsetp.eq.b32 p, 0, 0;\n"
    "wgmma.mma_async.sync.aligned.m64n72k16.f32.bf16.bf16 {%0,%1,%2,%3,%4,%5,%6,%7,%8,%9,%10,%11,%12,%13,%14,%15,%16,%17,%18,%19,%20,%21,%22,%23,%24,%25,%26,%27,%28,%29,%30,%31,%32,%33,%34,%35}, {%36,%37,%38,%39}, %40, p, 1, 1, 1;\n}"
    : "+f"(d[0]),"+f"(d[1]),"+f"(d[2]),"+f"(d[3]),"+f"(d[4]),"+f"(d[5]),"+f"(d[6]),"+f"(d[7]),"+f"(d[8]),"+f"(d[9]),"+f"(d[10]),"+f"(d[11]),"+f"(d[12]),"+f"(d[13]),"+f"(d[14]),"+f"(d[15]),"+f"(d[16]),"+f"(d[17]),"+f"(d[18]),"+f"(d[19]),"+f"(d[20]),"+f"(d[21]),"+f"(d[22]),"+f"(d[23]),"+f"(d[24]),"+f"(d[25]),"+f"(d[26]),"+f"(d[27]),"+f"(d[28]),"+f"(d[29]),"+f"(d[30]),"+f"(d[31]),"+f"(d[32]),"+f"(d[33]),"+f"(d[34]),"+f"(d[35])
    : "r"(a[0]),"r"(a[1]),"r"(a[2]),"r"(a[3]), "l"(bd));
  } else {
    asm volatile("{\n.reg .pred p;\nsetp.ne.b32 p, 0, 0;\n"
    "wgmma.mma_async.sync.aligned.m64n72k16.f32.bf16.bf16 {%0,%1,%2,%3,%4,%5,%6,%7,%8,%9,%10,%11,%12,%13,%14,%15,%16,%17,%18,%19,%20,%21,%22,%23,%24,%25,%26,%27,%28,%29,%30,%31,%32,%33,%34,%35}, {%36,%37,%38,%39}, %40, p, 1, 1, 1;\n}"
    : "+f"(d[0]),"+f"(d[1]),"+f"(d[2]),"+f"(d[3]),"+f"(d[4]),"+f"(d[5]),"+f"(d[6]),"+f"(d[7]),"+f"(d[8]),"+f"(d[9]),"+f"(d[10]),"+f"(d[11]),"+f"(d[12]),"+f"(d[13]),"+f"(d[14]),"+f"(d[15]),"+f"(d[16]),"+f"(d[17]),"+f"(d[18]),"+f"(d[19]),"+f"(d[20]),"+f"(d[21]),"+f"(d[22]),"+f"(d[23]),"+f"(d[24]),"+f"(d[25]),"+f"(d[26]),"+f"(d[27]),"+f"(d[28]),"+f"(d[29]),"+f"(d[30]),"+f"(d[31]),"+f"(d[32]),"+f"(d[33]),"+f"(d[34]),"+f"(d[35])
    : "r"(a[0]),"r"(a[1]),"r"(a[2]),"r"(a[3]), "l"(bd));
  }
}
template<int SD> __device__ __forceinline__ void wg_ss72(float* d, uint64_t ad, uint64_t bd) {
  if constexpr (SD) {
    asm volatile("{\n.reg .pred p;\nsetp.eq.b32 p, 0, 0;\n"
    "wgmma.mma_async.sync.aligned.m64n72k16.f32.bf16.bf16 {%0,%1,%2,%3,%4,%5,%6,%7,%8,%9,%10,%11,%12,%13,%14,%15,%16,%17,%18,%19,%20,%21,%22,%23,%24,%25,%26,%27,%28,%29,%30,%31,%32,%33,%34,%35}, %36, %37, p, 1, 1, 0, 1;\n}"
    : "+f"(d[0]),"+f"(d[1]),"+f"(d[2]),"+f"(d[3]),"+f"(d[4]),"+f"(d[5]),"+f"(d[6]),"+f"(d[7]),"+f"(d[8]),"+f"(d[9]),"+f"(d[10]),"+f"(d[11]),"+f"(d[12]),"+f"(d[13]),"+f"(d[14]),"+f"(d[15]),"+f"(d[16]),"+f"(d[17]),"+f"(d[18]),"+f"(d[19]),"+f"(d[20]),"+f"(d[21]),"+f"(d[22]),"+f"(d[23]),"+f"(d[24]),"+f"(d[25]),"+f"(d[26]),"+f"(d[27]),"+f"(d[28]),"+f"(d[29]),"+f"(d[30]),"+f"(d[31]),"+f"(d[32]),"+f"(d[33]),"+f"(d[34]),"+f"(d[35])
    : "l"(ad), "l"(bd));
  } else {
    asm volatile("{\n.reg .pred p;\nsetp.ne.b32 p, 0, 0;\n"
    "wgmma.mma_async.sync.aligned.m64n72k16.f32.bf16.bf16 {%0,%1,%2,%3,%4,%5,%6,%7,%8,%9,%10,%11,%12,%13,%14,%15,%16,%17,%18,%19,%20,%21,%22,%23,%24,%25,%26,%27,%28,%29,%30,%31,%32,%33,%34,%35}, %36, %37, p, 1, 1, 0, 1;\n}"
    : "+f"(d[0]),"+f"(d[1]),"+f"(d[2]),"+f"(d[3]),"+f"(d[4]),"+f"(d[5]),"+f"(d[6]),"+f"(d[7]),"+f"(d[8]),"+f"(d[9]),"+f"(d[10]),"+f"(d[11]),"+f"(d[12]),"+f"(d[13]),"+f"(d[14]),"+f"(d[15]),"+f"(d[16]),"+f"(d[17]),"+f"(d[18]),"+f"(d[19]),"+f"(d[20]),"+f"(d[21]),"+f"(d[22]),"+f"(d[23]),"+f"(d[24]),"+f"(d[25]),"+f"(d[26]),"+f"(d[27]),"+f"(d[28]),"+f"(d[29]),"+f"(d[30]),"+f"(d[31]),"+f"(d[32]),"+f"(d[33]),"+f"(d[34]),"+f"(d[35])
    : "l"(ad), "l"(bd));
  }
}
template<int SD> __device__ __forceinline__ void wg_tt64(float* d, uint64_t ad, uint64_t bd) {
  if constexpr (SD) {
    asm volatile("{\n.reg .pred p;\nsetp.eq.b32 p, 0, 0;\n"
    "wgmma.mma_async.sync.aligned.m64n64k16.f32.bf16.bf16 {%0,%1,%2,%3,%4,%5,%6,%7,%8,%9,%10,%11,%12,%13,%14,%15,%16,%17,%18,%19,%20,%21,%22,%23,%24,%25,%26,%27,%28,%29,%30,%31}, %32, %33, p, 1, 1, 1, 1;\n}"
    : "+f"(d[0]),"+f"(d[1]),"+f"(d[2]),"+f"(d[3]),"+f"(d[4]),"+f"(d[5]),"+f"(d[6]),"+f"(d[7]),"+f"(d[8]),"+f"(d[9]),"+f"(d[10]),"+f"(d[11]),"+f"(d[12]),"+f"(d[13]),"+f"(d[14]),"+f"(d[15]),"+f"(d[16]),"+f"(d[17]),"+f"(d[18]),"+f"(d[19]),"+f"(d[20]),"+f"(d[21]),"+f"(d[22]),"+f"(d[23]),"+f"(d[24]),"+f"(d[25]),"+f"(d[26]),"+f"(d[27]),"+f"(d[28]),"+f"(d[29]),"+f"(d[30]),"+f"(d[31])
    : "l"(ad), "l"(bd));
  } else {
    asm volatile("{\n.reg .pred p;\nsetp.ne.b32 p, 0, 0;\n"
    "wgmma.mma_async.sync.aligned.m64n64k16.f32.bf16.bf16 {%0,%1,%2,%3,%4,%5,%6,%7,%8,%9,%10,%11,%12,%13,%14,%15,%16,%17,%18,%19,%20,%21,%22,%23,%24,%25,%26,%27,%28,%29,%30,%31}, %32, %33, p, 1, 1, 1, 1;\n}"
    : "+f"(d[0]),"+f"(d[1]),"+f"(d[2]),"+f"(d[3]),"+f"(d[4]),"+f"(d[5]),"+f"(d[6]),"+f"(d[7]),"+f"(d[8]),"+f"(d[9]),"+f"(d[10]),"+f"(d[11]),"+f"(d[12]),"+f"(d[13]),"+f"(d[14]),"+f"(d[15]),"+f"(d[16]),"+f"(d[17]),"+f"(d[18]),"+f"(d[19]),"+f"(d[20]),"+f"(d[21]),"+f"(d[22]),"+f"(d[23]),"+f"(d[24]),"+f"(d[25]),"+f"(d[26]),"+f"(d[27]),"+f"(d[28]),"+f"(d[29]),"+f"(d[30]),"+f"(d[31])
    : "l"(ad), "l"(bd));
  }
}

template<int V> struct IC { static constexpr int v = V; };
template<int I, int N, class F> __device__ __forceinline__ void sfor(F&& f) {
    if constexpr (I < N) { f(IC<I>{}); sfor<I + 1, N>(f); }
}

enum { K_QKV = 0, K_H = 1 };

struct Ctx {
    uint32_t tph;
    uint32_t tid_;
    bool pf = false;
    __device__ __forceinline__ uint32_t tid() const { uint32_t r; asm volatile("mov.u32 %0, %1;" : "=r"(r) : "r"(tid_)); return r; }
};
__device__ __forceinline__ void release_slot(const Ctx& c, int slot) { if ((c.tid() & 31) == 0) mbar_arrive(bar(B_EMPTY + slot)); }

__device__ __forceinline__ void turn_wait(const Ctx& c) { asm volatile("bar.sync %0, 256;" :: "r"(4 + (c.tid() >> 7)) : "memory"); }
__device__ __forceinline__ void turn_pass(const Ctx& c) { asm volatile("bar.arrive %0, 256;" :: "r"(5 - (c.tid() >> 7)) : "memory"); }

template<int KIND, class PART, class POST>
__device__ __forceinline__ void run_step(Ctx& c, float* acc, const uint32_t* a, PART&& part, POST&& post, bool last = false) {
    constexpr int NST = (KIND == K_QKV) ? 6 : 3;
    constexpr int KPS = 36 / NST;
    sfor<0, NST>([&](auto ST) {
        constexpr int st = decltype(ST)::v;
        constexpr int slot = st % 3;
        mbar_wait(bar(B_FULL + slot), c.tph);
        uint32_t wgo = 0;
        if constexpr (st == NST - 1) wgo = (c.tid() >> 7) * 512;
        if (KIND == K_H && c.pf) prof(44 + st * 5);
        turn_wait(c);
        if (KIND == K_H && c.pf) prof(45 + st * 5);
        wg_fence();
        sfor<0, KPS>([&](auto KK) {
            constexpr int kk = decltype(KK)::v;
            constexpr int ks = st * KPS + kk;
            constexpr int SD = ks ? 1 : 0;
            if constexpr (KIND == K_QKV) {
                constexpr uint64_t bd = mkdesc(RING + slot * SLOT + kk * 2048, 12288, 1024, 1);
                if constexpr (ks < 32) wg_rs72<SD>(acc, a + ks * 4, bd);
                else wg_ss72<SD>(acc, mkdesc(XB + (ks - 32) * 32, 16, 1024, 1) + wgo, bd);
            } else {
                constexpr uint64_t bd = mkdesc(RING + slot * SLOT + kk * 2048, 16, 1024, 1);
                if constexpr (ks < 32) wg_rs64<SD>(acc, a + ks * 4, bd);
                else wg_ss64<SD>(acc, mkdesc(XB + (ks - 32) * 32, 16, 1024, 1) + wgo, bd);
            }
        });
        wg_commit();
        if (st < NST - 1 || !last || c.tid() < 128) turn_pass(c);
        if (KIND == K_H && c.pf) prof(46 + st * 5);
        part(ST);
        if (KIND == K_H && c.pf) prof(47 + st * 5);
        wg_wait<0>();
        if (KIND == K_H && c.pf) prof(48 + st * 5);
        release_slot(c, slot);
        if constexpr (slot == 2) c.tph ^= 1;
        post(ST);
    });
    if constexpr (KIND == K_QKV) reg_fence<36>(acc); else reg_fence<32>(acc);
}

__device__ __forceinline__ float phi(float t) {
    float e = ex2(t * 1.4426950408889634f);
    return (t > 0.f ? t + 1.0f : e) + 1e-6f;
}
__device__ __forceinline__ float gelu_h(float hx) {
    float u = hx * fmaf(hx * hx, 0.2854192650f, 1.5957691216f);
    return fmaf(hx, tanh_ap(u), hx);
}

struct Params {
    const __nv_bfloat16* x;
    const __nv_bfloat16* wqkv;
    const __nv_bfloat16* wo;
    const __nv_bfloat16* w1;
    const __nv_bfloat16* b1;
    const __nv_bfloat16* w2;
    const __nv_bfloat16* b2;
    __nv_bfloat16* out;
};

__global__ void __launch_bounds__(384, 1)
fused_kernel(const __grid_constant__ CUtensorMap tm_x, const __grid_constant__ CUtensorMap tm_w1,
             const __grid_constant__ CUtensorMap tm_w2, const __grid_constant__ CUtensorMap tm_wo,
             const __grid_constant__ CUtensorMap tm_o, const __grid_constant__ CUtensorMap tm_qkv,
             const __grid_constant__ CUtensorMap tm_qkve, const __grid_constant__ CUtensorMap tm_ost, const Params p) {
    extern __shared__ __align__(1024) unsigned char smem_raw[];
    const int tid = threadIdx.x;
    const int bid = blockIdx.x;
    const bool is_main = bid < NMAIN;
    const int j = bid & 7;
    const int m = bid >> 3;

    if (tid == 0) {
        if ((uint32_t)__cvta_generic_to_shared(smem_raw) != SB) __trap();
        for (int i = 0; i < 3; i++) {
            mbar_init(bar(B_FULL + i), 1); mbar_init(bar(B_EMPTY + i), 8);
            mbar_init(bar(B_XFULL + i), 1);
        }
        mbar_init(bar(B_KVB), 2); mbar_init(bar(B_INIT), 1);
        mbar_init(bar(B_OFULL), 1); mbar_init(bar(B_O8FULL), 1); mbar_init(bar(B_OFREE), 8); mbar_init(bar(B_O8FREE), 8);
        asm volatile("fence.mbarrier_init.release.cluster;" ::: "memory");
    }
    if (tid == 256) { asm volatile("prefetch.tensormap [%0];" :: "l"(&tm_x) : "memory"); asm volatile("prefetch.tensormap [%0];" :: "l"(&tm_qkv) : "memory"); asm volatile("prefetch.tensormap [%0];" :: "l"(&tm_qkve) : "memory"); }
    if (tid >= 40 && tid < 48) sts32(EVC + (tid - 40) * 4, 0);
    if (tid == 48) sts32(EPO + 4, 0);
    __syncthreads();

    if (tid >= 256) {
        asm volatile("setmaxnreg.dec.sync.aligned.u32 24;");
        const int hw = (tid >> 5) - 8, lane = tid & 31;
        uint32_t epoch = 0;
        if (hw > 0) {
            epoch = g_epoch[bid];
            if (hw == 3) {
                if (lane == 0) sts32(EPO, epoch);
                if (is_main) {
                    #pragma unroll 1
                    for (int i = lane; i < 288; i += 32) {
                        uint32_t v = *reinterpret_cast<const uint32_t*>(p.b1 + j * 576 + 2 * i);
                        sts32(B1S + 8 * i, __float_as_uint(0.5f * bf_lo(v))); sts32(B1S + 8 * i + 4, __float_as_uint(0.5f * bf_hi(v)));
                    }
                }
                uint32_t v = *reinterpret_cast<const uint32_t*>(p.b2 + (is_main ? j : 8) * 64 + 2 * lane);
                sts32(B2S + 8 * lane, v << 16); sts32(B2S + 8 * lane + 4, v & 0xffff0000u);
                __syncwarp();
                if (lane == 0) mbar_arrive(bar(B_INIT));
            }
        }
        const uint32_t par = epoch & 1;
        if (hw == 0) {
            if (lane == 0) {
                uint32_t n = 0;
                if (is_main) {
                    #pragma unroll 1
                    for (int kb = 0; kb < 9; kb++) {
                        if (kb % 3 == 0) mbar_expect_tx(bar(B_XFULL + kb / 3), 49152);
                        tma_2d(HA + kb * 16384, &tm_x, bar(B_XFULL + kb / 3), kb * 64, m * 128);
                    }
                    #pragma unroll 1
                    for (int u = 0; u < 18; u++) {
                        const int st = u % 3, step = u / 6;
                        const int col = ((step == 2) ? 0 : (step + 1) * 576) + j * 72, row = (u % 6) * 96;
                        mbar_wait(bar(B_EMPTY + st), (n & 1) ^ 1);
                        mbar_expect_tx(bar(B_FULL + st), 96 * 144);
                        tma_2d(RING + st * SLOT, &tm_qkv, bar(B_FULL + st), col, row);
                        tma_2d(RING + st * SLOT + 12288, &tm_qkve, bar(B_FULL + st), col + 64, row);
                        if (st == 2) n++;
                    }
                }
                const int nsteps = is_main ? 19 : 1;
                #pragma unroll 1
                for (int s = 0; s < nsteps; s++, n++) {
                    const CUtensorMap* tm; int col, row;
                    if (!is_main) { tm = &tm_wo; col = 512; row = 0; }
                    else if (s < 9) { tm = &tm_w1; col = j * 576 + s * 64; row = 0; }
                    else if (s < 18) { tm = &tm_w2; col = (s == 9) ? 512 : (((j + s - 9) & 7) * 64); row = j * 576; }
                    else { tm = &tm_wo; col = j * 64; row = 0; }
                    #pragma unroll 1
                    for (int st = 0; st < 3; st++) {
                        mbar_wait(bar(B_EMPTY + st), (n & 1) ^ 1);
                        mbar_expect_tx(bar(B_FULL + st), SLOT);
                        tma_2d(RING + st * SLOT, tm, bar(B_FULL + st), col, row + st * 192);
                    }
                }
            }
        } else {
            if (is_main) {
                const int t = tid - 288;
                __nanosleep(PF0_NS);
                #pragma unroll 1
                for (int i = t; i < 36 * 6; i += 96) {
                    int r = i / 6, q = i - r * 6;
                    prefetch_l2(reinterpret_cast<const char*>(p.wqkv) + (36 * m + r) * 3456 + (q >> 1) * 1152 + j * 144 + (q & 1) * 128);
                }
                __nanosleep(PF1_NS);
                #pragma unroll 1
                for (int i = t; i < 36 * 9; i += 96) {
                    int r = i / 9, q = i - r * 9;
                    prefetch_l2(reinterpret_cast<const char*>(p.w1) + (36 * m + r) * 9216 + j * 1152 + q * 128);
                    __nanosleep(PF3_NS);
                }
                __nanosleep(PF2_NS);
                #pragma unroll 1
                for (int i = t; i < 36 * 9; i += 96)
                    prefetch_l2(reinterpret_cast<const char*>(p.w2) + (576 * j + 36 * m) * 1152 + i * 128);
                if (t < 41 && (bid * 41 + t) < 5184) prefetch_l2(reinterpret_cast<const char*>(p.wo) + (bid * 41 + t) * 128);
                if (hw != 2) {
                    if (lane == 0) wait_cnt(cnt_kv(j), (epoch + 1) * 16);
                    __syncwarp();
                    const float4* kv = reinterpret_cast<const float4*>(g_kv + (par * 8 + j) * 1440);
                    #pragma unroll 2
                    for (int i = lane + (hw == 1 ? 0 : 32); i < 360; i += 64) {
                        const float4 v = __ldcg(kv + i);
                        const int d = i / 5, e = (i - d * 5) * 4, h = d / 18;
                        const uint32_t base = KVB + (d >> 3) * 128 + (d & 7) * 16;
                        const int n0 = 8 + h * 18 + e;
                        sts32(base + (n0 >> 3) * 1280 + (n0 & 7) * 2, pack_bf16(v.x, v.y));
                        if (e < 16) sts32(base + ((n0 + 2) >> 3) * 1280 + ((n0 + 2) & 7) * 2, pack_bf16(v.z, v.w));
                        else asm volatile("st.shared.u16 [%0], %1;" :: "r"(base + h * 2), "h"((unsigned short)pack_bf16(v.z, 0.f)) : "memory");
                    }
                    fence_async_smem();
                    __syncwarp();
                    if (lane == 0) mbar_arrive(bar(B_KVB));
                }
            }
            if (hw == 1) {
                if (lane == 0) {
                    const int nit = is_main ? 1 : 4;
                    for (int it = 0; it < nit; it++) {
                        const int mt = is_main ? m : ((bid - NMAIN) * 4 + it);
                        const bool wf = is_main || it > 0;
                        const uint32_t fp = is_main ? 0 : ((it - 1) & 1);
                        wait_cnt(cnt_o(mt), (epoch + 1) * 8);
                        fence_async_all();
                        if (wf) mbar_wait(bar(B_OFREE), fp);
                        mbar_expect_tx(bar(B_OFULL), 131072);
                        #pragma unroll 1
                        for (int kb = 0; kb < 8; kb++) tma_2d(HA + kb * 16384, &tm_o, bar(B_OFULL), kb * 64, mt * 128);
                        if (wf) mbar_wait(bar(B_O8FREE), fp);
                        mbar_expect_tx(bar(B_O8FULL), 16384);
                        tma_2d(XB, &tm_o, bar(B_O8FULL), 512, mt * 128);
                    }
                    if (is_main) { wait_cnt(cnt_y(m, j), (epoch + 1) * 7); asm volatile("st.release.cta.shared.u32 [%0], %1;" :: "r"(EPO + 4), "r"(1) : "memory"); }
                }
            } else if (hw == 2) {
                if (!is_main) {
                    if (lane == 0) {
                        #pragma unroll 1
                        for (int it = 0; it < 4; it++) {
                            wait_cnt(cnt_y((bid - NMAIN) * 4 + it, 8), (epoch + 1) * 8);
                            asm volatile("st.release.cta.shared.u32 [%0], %1;" :: "r"(EPO + 4), "r"(it + 1) : "memory");
                        }
                    }
                } else {
                    #pragma unroll 1
                    for (int e = 0; e < 10; e++) {
                        int spin = 0;
                        while (true) {
                            uint32_t v;
                            asm volatile("ld.acquire.cta.shared.u32 %0, [%1];" : "=r"(v) : "r"(EVC + (lane & 7) * 4) : "memory");
                            if (__all_sync(0xffffffffu, v > (uint32_t)e)) break;
                            if (++spin > 20000000) __trap();
                            __nanosleep(20);
                        }
                        if (lane == 0) {
                            unsigned int* cp = (e == 0) ? cnt_kv(j) : (e == 1) ? cnt_o(m) : cnt_y(m, e == 2 ? 8 : ((j + e - 2) & 7));
                            if (e == 1) fence_async_all();
                            __threadfence();
                            asm volatile("red.relaxed.gpu.global.add.u32 [%0], 1;" :: "l"(cp) : "memory");
                        }
                        __syncwarp();
                    }
                }
            } else {
                {
                    const int t0 = is_main ? (m * 9 + j) : ((bid - NMAIN) * 4 * 9 + 8);
                    const int nt = is_main ? 1 : 4;
                    for (int t = 0; t < nt; t++) {
                        uint4* z = reinterpret_cast<uint4*>(g_yacc + (size_t)((par ^ 1) * 144 + t0 + t * 9) * YT_BYTES);
                        for (int i = lane; i < YT_BYTES / 16; i += 32) z[i] = make_uint4(0, 0, 0, 0);
                    }
                    if (is_main && m == 0) {
                        float* z = g_kv + ((par ^ 1) * 8 + j) * 1440;
                        for (int i = lane; i < 1440; i += 32) z[i] = 0.f;
                    }
                }
            }
        }
    } else {
        asm volatile("setmaxnreg.inc.sync.aligned.u32 240;");
        prof(0);
        Ctx c; c.tph = 0; c.tid_ = v_tid();
        float hc[32], pv[36];
        if (tid >> 7) turn_pass(c);
        auto event = [&](uint32_t ev) {
            __syncwarp();
            if (((c.tid() & 31) == 0)) asm volatile("st.release.cta.shared.u32 [%0], %1;" :: "r"(EVC + (c.tid() >> 3)), "r"(ev) : "memory");
        };
        auto warp_arrive = [&](uint32_t b) { __syncwarp(); if (((c.tid() & 31) == 0)) mbar_arrive(b); };

        auto lrow_off = [&]() { uint32_t t_ = c.tid(); return HA + ((t_ >> 5) * 16 + (t_ & 15)) * 128 + ((((t_ >> 4) & 1) ^ (t_ & 7)) << 4); };
        auto tail_off = [&]() { uint32_t t_ = c.tid(), g = (t_ >> 2) & 7; return XB + ((t_ >> 5) * 16 + g) * 128 + (g << 4) + (t_ & 3) * 4; };
        if (is_main) {
            uint32_t a[128];
            float rs0, rs1;
            {
                uint32_t tl[16];
                const uint32_t lrow = lrow_off();
                float cs[2][4] = {{0.f, 0.f, 0.f, 0.f}, {0.f, 0.f, 0.f, 0.f}};
                float sq[4][4] = {{0.f, 0.f, 0.f, 0.f}, {0.f, 0.f, 0.f, 0.f}, {0.f, 0.f, 0.f, 0.f}, {0.f, 0.f, 0.f, 0.f}};
                uint32_t s00 = 0, s11 = 0;
                auto frag = [&](auto KS) -> uint32_t* { constexpr int ks = decltype(KS)::v; return (ks < 32) ? (a + (ks & 31) * 4) : (tl + (ks & 3) * 4); };
                auto sqacc = [&](auto KS) {
                    constexpr int ks = decltype(KS)::v;
                    const uint32_t* f = frag(KS);
                    uint32_t v[4];
                    #pragma unroll
                    for (int r = 0; r < 4; r++) v[r] = sub_bf16x2(f[r], (r & 1) ? s11 : s00);
                    mma_bf16(sq[(ks & 1) * 2], v, v[0], v[2]);
                    mma_bf16(sq[(ks & 1) * 2 + 1], v, v[1], v[3]);
                };
                sfor<0, 36>([&](auto KS) {
                    constexpr int ks = decltype(KS)::v;
                    if constexpr (ks % 12 == 0) { mbar_wait(bar(B_XFULL + ks / 12), 0); prof(37 + ks / 12); }
                    ldsm4((lrow ^ ((ks % 4) << 5)) + (ks / 4) * 16384, frag(KS));
                    mma_ones(cs[ks & 1], frag(KS));
                    if constexpr (ks == 11) {
                        const float t0 = (cs[0][0] + cs[1][0]) * (1.0f / 192.0f), t1 = (cs[0][2] + cs[1][2]) * (1.0f / 192.0f);
                        s00 = pack_bf16(t0, t0); s11 = pack_bf16(t1, t1);
                        sfor<0, 12>(sqacc);
                    }
                    if constexpr (ks >= 12) sqacc(KS);
                });
                prof(2);
                const float mean0 = (cs[0][0] + cs[1][0]) * (1.0f / 576.0f), mean1 = (cs[0][2] + cs[1][2]) * (1.0f / 576.0f);
                const uint32_t m00 = pack_bf16(mean0, mean0), m11 = pack_bf16(mean1, mean1);
                const uint32_t tb = tail_off();
                #pragma unroll
                for (int i = 0; i < 16; i++) sts32((tb ^ ((i >> 1) << 4)) + (i & 1) * 1024, sub_bf16x2(tl[i], (i & 1) ? m11 : m00));
                fence_async_smem();
                #pragma unroll
                for (int i = 0; i < 128; i++) a[i] = sub_bf16x2(a[i], (i & 1) ? m11 : m00);
                {
                    const uint32_t l_ = c.tid() & 31, g_ = l_ >> 2, src = (l_ & 28) | (g_ >> 1);
                    rs0 = __shfl_sync(0xffffffffu, (g_ & 1) ? (sq[0][1] + sq[2][1]) : (sq[0][0] + sq[2][0]), src);
                    rs1 = __shfl_sync(0xffffffffu, (g_ & 1) ? (sq[1][3] + sq[3][3]) : (sq[1][2] + sq[3][2]), src);
                    const float d0 = mean0 - bf_lo(s00), d1 = mean1 - bf_lo(s11);
                    rs0 = rsqrtf(fmaxf(fmaf(rs0, 1.0f / 576.0f, -d0 * d0), 0.f) + 1e-5f);
                    rs1 = rsqrtf(fmaxf(fmaf(rs1, 1.0f / 576.0f, -d1 * d1), 0.f) + 1e-5f);
                }
                named_bar(1, 256);
            }
            prof(3);
            auto cm_off = [&]() { uint32_t t_ = c.tid(); return (t_ >> 5) * 256 + (t_ & 31) * 4; };
            {
                float qc[36];
                #pragma unroll
                for (int i = 0; i < 36; i++) { qc[i] = 0.f; pv[i] = 0.f; }
                #pragma unroll 1
                for (int s = 0; s < 3; s++) {
                    c.pf = (s == 0);
                    run_step<K_QKV>(c, qc, a, [&](auto ST) {
                        constexpr int st = decltype(ST)::v;
                        if (s > 0) {
                            const uint32_t cm = cm_off();
                            sfor<0, 9>([&](auto B) {
                                constexpr int b = decltype(B)::v;
                                if constexpr ((b * 6) / 9 == st) {
                                    const float v0 = pv[4 * b] * rs0, v1 = pv[4 * b + 1] * rs0, v2 = pv[4 * b + 2] * rs1, v3 = pv[4 * b + 3] * rs1;
                                    if (s == 1) {
                                        sts32(PKT + b * 2048 + cm, pack_bf16(phi(v0), phi(v1)));
                                        sts32(PKT + b * 2048 + cm + 128, pack_bf16(phi(v2), phi(v3)));
                                    } else {
                                        const uint32_t w0 = pack_bf16(v0, v1), w1 = pack_bf16(v2, v3);
                                        if constexpr (b <= 4) { sts32(VT + b * 2048 + cm, w0); sts32(VT + b * 2048 + cm + 128, w1); }
                                        if constexpr (b >= 4) { sts32(VT + (b + 2) * 2048 + cm, w0); sts32(VT + (b + 2) * 2048 + cm + 128, w1); }
                                        if constexpr (b == 0) {
                                            const uint32_t one = (cm & 12) ? 0u : 0x00003F80u;
                                            sts32(VT + 5 * 2048 + cm, one); sts32(VT + 5 * 2048 + cm + 128, one);
                                        }
                                        if constexpr (b == 8) {
                                            const uint32_t z = KVB + c.tid() * 16;
                                            sts128(z, 0, 0, 0, 0); sts128(z + 4096, 0, 0, 0, 0); sts128(z + 8192, 0, 0, 0, 0);
                                            if (z < KVB + 512) sts128(z + 12288, 0, 0, 0, 0);
                                            fence_async_smem();
                                        }
                                    }
                                }
                            });
                        }
                    }, [](auto) {});
                    reg_copy<36>(pv, qc);
                    prof(4 + s);
                }
            }
            {
                #pragma unroll
                for (int i = 0; i < 32; i++) hc[i] = 0.f;
                named_bar(1, 256);
                const uint32_t wgo = ((c.tid() >> 7) * 512);
                wg_fence();
                sfor<0, 8>([&](auto KS) {
                    constexpr int ks = decltype(KS)::v;
                    wg_tt64<(ks ? 1 : 0)>(hc, mkdesc(PKT + ks * 256, 128, 2048, 0) + wgo,
                                          mkdesc(VT + ks * 256, 128, 2048, 0) + wgo + (wgo >> 2));
                });
                wg_commit();
                const uint32_t pq = PQT + cm_off() + ((c.tid() >> 7) * 512) * 16;
                sfor<0, 9>([&](auto B) {
                    constexpr int b = decltype(B)::v;
                    sts32(pq + b * 1024, pack_bf16(phi(pv[4 * b] * rs0), phi(pv[4 * b + 1] * rs0)));
                    sts32(pq + b * 1024 + 128, pack_bf16(phi(pv[4 * b + 2] * rs1), phi(pv[4 * b + 3] * rs1)));
                });
                fence_async_smem();
                wg_wait<0>();
                reg_fence<32>(hc);
                reg_copy<24>(pv, hc);
            }
            prof(7);
            rs0 *= 0.5f; rs1 *= 0.5f;
            mbar_wait(bar(B_INIT), 0);
            auto gelun = [&](auto B0, auto B1, uint32_t bofs, uint32_t* w) {
                constexpr int b0 = decltype(B0)::v, nb = decltype(B1)::v - b0;
                float2 bv[nb];
                #pragma unroll
                for (int i = 0; i < nb; i++) bv[i] = lds64f(bofs + (b0 + i) * 32);
                #pragma unroll
                for (int i = 0; i < nb; i++) {
                    const int b = b0 + i;
                    w[2 * i]     = pack_bf16(gelu_h(fmaf(pv[4 * b], rs0, bv[i].x)), gelu_h(fmaf(pv[4 * b + 1], rs0, bv[i].y)));
                    w[2 * i + 1] = pack_bf16(gelu_h(fmaf(pv[4 * b + 2], rs1, bv[i].x)), gelu_h(fmaf(pv[4 * b + 3], rs1, bv[i].y)));
                }
            };
            auto spill_off = [&]() { uint32_t t_ = c.tid(); return HA + (t_ >> 7) * 8192 + (t_ & 127) * 8; };
            auto reload = [&](auto S0, auto S1) {
                const uint32_t spill = spill_off();
                sfor<decltype(S0)::v * 8, decltype(S1)::v * 8>([&](auto Q) {
                    constexpr int q = decltype(Q)::v;
                    lds64(spill + (q / 8) * 16384 + (q % 8) * 1024, a + q * 2);
                });
            };
            #pragma unroll 1
            for (int idx = 0; idx < 18; idx++) {
                run_step<K_H>(c, hc, a, [&](auto ST) {
                    constexpr int st = decltype(ST)::v;
                    if (idx >= 10) {
                        if constexpr (st < 2) {
                            const uint32_t b_ = v_bid();
                            const uint32_t chunk = (idx == 10) ? 8 : ((b_ + idx - 10) & 7);
                            unsigned char* yp = g_yacc + ((v_epoch() & 1) * 144 + (b_ >> 3) * 9 + chunk) * YT_BYTES + c.tid() * 16;
                            sfor<2 * st, 2 * st + 2>([&](auto Q) {
                                constexpr int q = decltype(Q)::v;
                                asm volatile("red.global.add.noftz.v4.bf16x2 [%0], {%1,%2,%3,%4};" :: "l"(yp + q * 4096),
                                             "r"(pack_bf16(pv[8 * q], pv[8 * q + 1])), "r"(pack_bf16(pv[8 * q + 2], pv[8 * q + 3])),
                                             "r"(pack_bf16(pv[8 * q + 4], pv[8 * q + 5])), "r"(pack_bf16(pv[8 * q + 6], pv[8 * q + 7])) : "memory");
                            });
                            if constexpr (st == 1) event(idx - 7);
                        }
                    } else if (idx >= 1) {
                        const uint32_t bofs = B1S + (idx - 1) * 256 + (c.tid() & 3) * 8;
                        if (idx < 9) {
                            if constexpr (st == 0) {
                                if (idx == OSTEP_AT + 1) {
                                    if ((c.tid() & 31) == 0) asm volatile("cp.async.bulk.wait_group 0;" ::: "memory");
                                    event(2);
                                }
                            }
                            const uint32_t spill = spill_off() + (idx - 1) * 16384;
                            constexpr int b0 = st * 3, b1 = (st == 2 ? 8 : st * 3 + 3);
                            uint32_t w[6];
                            gelun(IC<b0>{}, IC<b1>{}, bofs, w);
                            #pragma unroll
                            for (int b = b0; b < b1; b++) sts64(spill + b * 1024, w[2 * (b - b0)], w[2 * (b - b0) + 1]);
                        } else {
                            if constexpr (st < 2) {
                                const uint32_t tb = tail_off();
                                uint32_t w[8];
                                gelun(IC<st * 4>{}, IC<st * 4 + 4>{}, bofs, w);
                                #pragma unroll
                                for (int i = 0; i < 4; i++) { sts32(tb ^ ((st * 4 + i) << 4), w[2 * i]); sts32((tb ^ ((st * 4 + i) << 4)) + 1024, w[2 * i + 1]); }
                            }
                            if constexpr (st == 1) { fence_async_smem(); named_bar(2 + (c.tid() >> 7), 128); }
                        }
                    } else {
                        if constexpr (st < 2) {
                            constexpr int hf = st;
                            const int t_ = c.tid(), wg = t_ >> 7, t = t_ & 3;
                            float* dst = g_kv + ((v_epoch() & 1) * 8 + (v_bid() & 7)) * 1440;
                            const int d = wg * 32 + ((t_ >> 5) & 3) * 16 + ((t_ >> 2) & 7) + hf * 8;
                            const bool dv = wg ? (d >= 36 && d < 72) : (d < 36);
                            const int e00 = wg * 24 + 2 * t - (d / 18) * 18;
                            float* dp = dst + d * 20 + e00;
                            #pragma unroll
                            for (int i = 0; i < 6; i++) {
                                const int e = e00 + i * 8;
                                const bool blk = wg ? (i >= 1) : (i <= 4);
                                if (dv && blk && e >= 0 && e < 18)
                                    asm volatile("red.global.add.v2.f32 [%0], {%1,%2};" :: "l"(dp + i * 8), "f"(pv[4 * i + 2 * hf]), "f"(pv[4 * i + 2 * hf + 1]) : "memory");
                            }
                            if (dv && t == 0) atomicAdd(dst + d * 20 + 18, wg ? pv[2 * hf] : pv[20 + 2 * hf]);
                            if constexpr (st == 1) event(1);
                        }
                    }
                }, [&](auto ST) {
                    constexpr int st = decltype(ST)::v;
                    if (idx == 8) {
                        reload(IC<3 * st>{}, IC<(st == 2 ? 8 : 3 * st + 3)>{});
                        if constexpr (st == 2) warp_arrive(bar(B_OFREE));
                    }
                });
                reg_copy<32>(pv, hc);
                prof(8 + idx);
                if (idx == OSTEP_AT) {
                    mbar_wait(bar(B_KVB), 0);
                    prof(34);
                    const uint32_t pqo = (c.tid() >> 7) * 576;
                    const int t_ = c.tid(), b_ = v_bid(), t = t_ & 3, l4 = t_ & 28;
                    const uint32_t op = OST + ((t_ >> 5) * 16 + ((t_ >> 2) & 7)) * 144 + t * 4;
                    float r3[2];
                    sfor<0, 2>([&](auto PS) {
                        constexpr int ps = decltype(PS)::v;
                        wg_fence();
                        sfor<0, 5>([&](auto KS) {
                            constexpr int ks = decltype(KS)::v;
                            wg_ss64<(ks ? 1 : 0)>(hc, mkdesc(PQT + ks * 2048, ks == 4 ? 0 : 1024, 128, 0) + pqo, mkdesc(KVB + ps * 8 * 1280 + ks * 256, 128, 1280, 0));
                        });
                        wg_commit();
                        wg_wait<0>();
                        reg_fence<32>(hc);
                        #pragma unroll
                        for (int hf = 0; hf < 2; hf++) {
                            if constexpr (ps == 0) {
                                float r[4];
                                r[0] = rcp(__shfl_sync(0xffffffffu, hc[2 * hf], l4) + 1e-6f);
                                r[1] = rcp(__shfl_sync(0xffffffffu, hc[1 + 2 * hf], l4) + 1e-6f);
                                r[2] = rcp(__shfl_sync(0xffffffffu, hc[2 * hf], l4 + 1) + 1e-6f);
                                r[3] = rcp(__shfl_sync(0xffffffffu, hc[1 + 2 * hf], l4 + 1) + 1e-6f);
                                r3[hf] = r[3];
                                #pragma unroll
                                for (int i = 0; i < 7; i++) {
                                    float rr = (i < 2) ? r[0] : (i == 2) ? (t < 1 ? r[0] : r[1]) : (i == 3) ? r[1] : (i == 4) ? (t < 2 ? r[1] : r[2])
                                             : (i == 5) ? r[2] : (t < 3 ? r[2] : r[3]);
                                    sts32(op + hf * 8 * 144 + i * 16, pack_bf16(hc[4 * i + 4 + 2 * hf] * rr, hc[4 * i + 5 + 2 * hf] * rr));
                                }
                            } else {
                                #pragma unroll
                                for (int i = 0; i < 2; i++)
                                    sts32(op + hf * 8 * 144 + 112 + i * 16, pack_bf16(hc[4 * i + 2 * hf] * r3[hf], hc[4 * i + 1 + 2 * hf] * r3[hf]));
                            }
                        }
                    });
                    fence_async_smem();
                    __syncwarp();
                    if ((t_ & 31) == 0) {
                        asm volatile("cp.async.bulk.tensor.2d.global.shared::cta.bulk_group [%0, {%2, %3}], [%1];"
                                     :: "l"(&tm_ost), "r"(OST + (t_ >> 5) * 2304), "r"((b_ & 7) * 72), "r"((b_ >> 3) * 128 + (t_ >> 5) * 16) : "memory");
                        asm volatile("cp.async.bulk.commit_group;" ::: "memory");
                    }
                }
            }
        }
        if (is_main) warp_arrive(bar(B_O8FREE));
        else {
            mbar_wait(bar(B_INIT), 0);
            #pragma unroll
            for (int i = 0; i < 32; i++) { asm volatile("mov.b32 %0, 0;" : "=f"(hc[i])); asm volatile("mov.b32 %0, 0;" : "=f"(pv[i])); }
        }
        auto add_b2 = [&]() {
            #pragma unroll
            for (int b = 0; b < 8; b++) {
                float2 bv = lds64f(B2S + b * 32 + (c.tid() & 3) * 8);
                pv[4 * b] += bv.x; pv[4 * b + 1] += bv.y; pv[4 * b + 2] += bv.x; pv[4 * b + 3] += bv.y;
            }
        };
        auto load_xy = [&](int ftile, int nrdy, uint32_t* xr, uint32_t* yv) {
            const int mt = ftile / 9, ch = ftile - mt * 9;
            const uint32_t t_ = c.tid();
            const __nv_bfloat16* xp = p.x + (size_t)(mt * 128 + (t_ >> 5) * 16 + ((t_ >> 2) & 7)) * DM + ch * 64 + 2 * (t_ & 3);
            #pragma unroll
            for (int i = 0; i < 8; i++) {
                asm volatile("ld.global.nc.u32 %0, [%1];" : "=r"(xr[2 * i]) : "l"(xp + i * 8));
                asm volatile("ld.global.nc.u32 %0, [%1];" : "=r"(xr[2 * i + 1]) : "l"(xp + 8 * DM + i * 8));
            }
            prof(26);
            smem_wait_gt(EPO + 4, nrdy);
            prof(27);
            const unsigned char* yp = g_yacc + ((v_epoch() & 1) * 144 + ftile) * YT_BYTES + t_ * 16;
            #pragma unroll
            for (int q = 0; q < YT_BYTES / 4096; q++)
                asm volatile("ld.global.cg.v4.u32 {%0,%1,%2,%3}, [%4];" : "=r"(yv[4 * q]), "=r"(yv[4 * q + 1]), "=r"(yv[4 * q + 2]), "=r"(yv[4 * q + 3]) : "l"(yp + q * 4096) : "memory");
        };
        auto gate = [&](const uint32_t* yv) {
            #pragma unroll
            for (int i = 0; i < 16; i++) { pv[2 * i] += bf_lo(yv[i]); pv[2 * i + 1] += bf_hi(yv[i]); }
            #pragma unroll
            for (int i = 0; i < 32; i++) { const float h = 0.5f * pv[i]; pv[i] = fmaf(h, tanh_ap(h), h); }
        };
        auto store_out = [&](int ftile, const uint32_t* xr) {
            const int mt = ftile / 9, ch = ftile - mt * 9;
            const uint32_t t_ = c.tid();
            __nv_bfloat16* op = p.out + (size_t)(mt * 128 + (t_ >> 5) * 16 + ((t_ >> 2) & 7)) * DM + ch * 64 + 2 * (t_ & 3);
            #pragma unroll
            for (int b = 0; b < 8; b++) {
                *reinterpret_cast<uint32_t*>(op + b * 8) =
                    pack_bf16(fmaf(hc[4 * b], pv[4 * b], bf_lo(xr[2 * b])), fmaf(hc[4 * b + 1], pv[4 * b + 1], bf_hi(xr[2 * b])));
                *reinterpret_cast<uint32_t*>(op + 8 * DM + b * 8) =
                    pack_bf16(fmaf(hc[4 * b + 2], pv[4 * b + 2], bf_lo(xr[2 * b + 1])), fmaf(hc[4 * b + 3], pv[4 * b + 3], bf_hi(xr[2 * b + 1])));
            }
        };
        const int njob = is_main ? 1 : 4;
        #pragma unroll 1
        for (int job = 0; job < njob; job++) {
            const uint32_t jpar = job & 1;
            const uint32_t b_ = v_bid();
            const bool mainf = b_ < NMAIN;
            const int ftile = (b_ >> 3) * 9 + (b_ & 7);
            uint32_t oa[128];
            {
                mbar_wait(bar(B_OFULL), jpar);
                const uint32_t lrow = lrow_off();
                sfor<0, 32>([&](auto KS) {
                    constexpr int ks = decltype(KS)::v;
                    ldsm4((lrow ^ ((ks % 4) << 5)) + (ks / 4) * 16384, oa + ks * 4);
                });
                warp_arrive(bar(B_OFREE));
                if (job) c.tph ^= 1;
            }
            c.pf = false;
            run_step<K_H>(c, hc, oa, [&](auto ST) {
                constexpr int st = decltype(ST)::v;
                if (mainf) {
                    if constexpr (st == 0) add_b2();
                    else if constexpr (st == 1) load_xy(ftile, 0, oa, oa + 16);
                    else { prof(28); gate(oa + 16); prof(29); }
                }
                if constexpr (st == 1) mbar_wait(bar(B_O8FULL), jpar);
            }, [](auto) {}, job == njob - 1);
            prof(30);
            if (mainf) {
                store_out(ftile, oa);
            } else {
                warp_arrive(bar(B_O8FREE));
                uint4* sp = reinterpret_cast<uint4*>(g_s8) + ((b_ - NMAIN) * 4 + job) * 1024 + c.tid();
                #pragma unroll
                for (int q = 0; q < 4; q++)
                    sp[q * 256] = make_uint4(pack_bf16(hc[8 * q], hc[8 * q + 1]), pack_bf16(hc[8 * q + 2], hc[8 * q + 3]),
                                             pack_bf16(hc[8 * q + 4], hc[8 * q + 5]), pack_bf16(hc[8 * q + 6], hc[8 * q + 7]));
                prof(8 + job);
            }
        }
        if (!is_main) {
            #pragma unroll 1
            for (int job = 0; job < 4; job++) {
                const int tile = (v_bid() - NMAIN) * 4 + job;
                uint32_t xr[16], yv[YT_BYTES / 1024];
                const uint4* sp = reinterpret_cast<const uint4*>(g_s8) + tile * 1024 + c.tid();
                #pragma unroll
                for (int q = 0; q < 4; q++) {
                    const uint4 u = __ldcg(sp + q * 256);
                    hc[8 * q] = bf_lo(u.x); hc[8 * q + 1] = bf_hi(u.x); hc[8 * q + 2] = bf_lo(u.y); hc[8 * q + 3] = bf_hi(u.y);
                    hc[8 * q + 4] = bf_lo(u.z); hc[8 * q + 5] = bf_hi(u.z); hc[8 * q + 6] = bf_lo(u.w); hc[8 * q + 7] = bf_hi(u.w);
                }
                #pragma unroll
                for (int i = 0; i < 32; i++) pv[i] = 0.f;
                add_b2();
                load_xy(tile * 9 + 8, job, xr, yv);
                gate(yv);
                store_out(tile * 9 + 8, xr);
                prof(12 + job);
            }
        }
        prof(40);
        if (c.tid() == 0) g_epoch[v_bid()] = v_epoch() + 1;
    }
}

typedef CUresult (*EncodeFn)(CUtensorMap*, CUtensorMapDataType, cuuint32_t, void*, const cuuint64_t*, const cuuint64_t*,
                             const cuuint32_t*, const cuuint32_t*, CUtensorMapInterleave, CUtensorMapSwizzle,
                             CUtensorMapL2promotion, CUtensorMapFloatOOBfill);

void make_map(EncodeFn enc, CUtensorMap* tm, const void* base, int rows, int cols, int box_rows, int box_cols = 64, bool swz = true) {
    cuuint64_t gdim[2] = {(cuuint64_t)cols, (cuuint64_t)rows};
    cuuint64_t gstr[1] = {(cuuint64_t)cols * 2};
    cuuint32_t box[2] = {(cuuint32_t)box_cols, (cuuint32_t)box_rows};
    cuuint32_t estr[2] = {1, 1};
    enc(tm, CU_TENSOR_MAP_DATA_TYPE_BFLOAT16, 2, const_cast<void*>(base), gdim, gstr, box, estr, CU_TENSOR_MAP_INTERLEAVE_NONE,
        swz ? CU_TENSOR_MAP_SWIZZLE_128B : CU_TENSOR_MAP_SWIZZLE_NONE, CU_TENSOR_MAP_L2_PROMOTION_L2_128B, CU_TENSOR_MAP_FLOAT_OOB_FILL_NONE);
}

}

extern "C" void kernel_launch(void* const* d_in, const int* in_sizes, int n_in, void* d_out, int out_size) {
    static EncodeFn enc = nullptr;
    static void* o_ptr = nullptr;
    if (!enc) {
        void* fn = nullptr;
        cudaDriverEntryPointQueryResult qr;
        cudaGetDriverEntryPoint("cuTensorMapEncodeTiled", &fn, cudaEnableDefault, &qr);
        enc = (EncodeFn)fn;
        cudaGetSymbolAddress(&o_ptr, g_o);
        cudaFuncSetAttribute(fused_kernel, cudaFuncAttributeMaxDynamicSharedMemorySize, SMEM_BYTES);
    }
    Params p;
    p.x = (const __nv_bfloat16*)d_in[0];
    p.wqkv = (const __nv_bfloat16*)d_in[1];
    p.wo = (const __nv_bfloat16*)d_in[2];
    p.w1 = (const __nv_bfloat16*)d_in[4];
    p.b1 = (const __nv_bfloat16*)d_in[5];
    p.w2 = (const __nv_bfloat16*)d_in[6];
    p.b2 = (const __nv_bfloat16*)d_in[7];
    p.out = (__nv_bfloat16*)d_out;
    CUtensorMap tm_x, tm_w1, tm_w2, tm_wo, tm_o, tm_qkv, tm_qkve, tm_ost;
    make_map(enc, &tm_ost, o_ptr, SEQ, DM, 16, 72, false);
    make_map(enc, &tm_qkv, p.wqkv, DM, 3 * DM, 96);
    make_map(enc, &tm_qkve, p.wqkv, DM, 3 * DM, 96, 8);
    make_map(enc, &tm_x, p.x, SEQ, DM, 128);
    make_map(enc, &tm_w1, p.w1, DM, FF, 192);
    make_map(enc, &tm_w2, p.w2, FF, DM, 192);
    make_map(enc, &tm_wo, p.wo, DM, DM, 192);
    make_map(enc, &tm_o, o_ptr, SEQ, DM, 128);
    fused_kernel<<<NMAIN + NAUX, 384, SMEM_BYTES>>>(tm_x, tm_w1, tm_w2, tm_wo, tm_o, tm_qkv, tm_qkve, tm_ost, p);
}
```

```cpp
#include <cuda_runtime.h>
#include <cuda.h>
#include <cuda_bf16.h>
#include <stdint.h>

#define OSTEP_AT 4
#define KNOB_A 1
#define KNOB_B 0
#define PF1_NS 1500
#define PF2_NS 2000
#define PFIDX 3
#define PF3_NS 800
#define EARLY_REL 0
#define PF0_NS 1200
#define YF32 0

namespace {
constexpr int WAIT_ITERS = 3000000;

constexpr int SEQ = 2048, DM = 576, FF = 4608;
constexpr int NMAIN = 128, NAUX = 4;

constexpr uint32_t SB    = 0x400;
constexpr uint32_t HA    = SB;
constexpr uint32_t XB    = SB + 131072;
constexpr uint32_t RING  = SB + 147456;
constexpr uint32_t SLOT  = 24576;
constexpr uint32_t MISC  = SB + 221184;
constexpr uint32_t BARS  = MISC;
constexpr uint32_t B1S   = MISC + 512;
constexpr uint32_t B2S   = MISC + 2816;
constexpr uint32_t EPO   = MISC + 3072;
constexpr uint32_t EVC   = MISC + 3104;
constexpr uint32_t SMEM_BYTES = 221184 + 3200 + 512;
constexpr uint32_t PKT   = HA + 32768;
constexpr uint32_t VT    = HA + 51200;
constexpr uint32_t OST   = HA + 79872;
constexpr uint32_t PQT   = HA + 98304;
constexpr uint32_t KVB   = HA + 116736;

enum { B_FULL = 0, B_EMPTY = 3, B_XFULL = 6, B_OFULL = 9, B_O8FULL = 10, B_OFREE = 11, B_O8FREE = 12, B_KVB = 13, B_INIT = 14, B_COUNT = 15 };
__device__ __forceinline__ constexpr uint32_t bar(int i) { return BARS + 8u * i; }

constexpr int YT_BYTES = YF32 ? 32768 : 16384;
__device__ __align__(1024) __nv_bfloat16 g_o[SEQ * DM];
__device__ __align__(1024) unsigned char g_yacc[2 * 16 * 9 * YT_BYTES];
__device__ __align__(128) float g_kv[2 * 8 * 72 * 20];
__device__ __align__(128) unsigned int g_s8[16 * 4096];
__device__ __align__(128) unsigned int g_cnt[(8 + 16 + 16 * 9) * 8];
__device__ unsigned int g_epoch[NMAIN + NAUX];
__device__ __forceinline__ unsigned int* cnt_kv(int j) { return g_cnt + j * 8; }
__device__ __forceinline__ unsigned int* cnt_o(int m) { return g_cnt + (8 + m) * 8; }
__device__ __forceinline__ unsigned int* cnt_y(int m, int c) { return g_cnt + (24 + m * 9 + c) * 8; }

__device__ __forceinline__ void mbar_init(uint32_t b, uint32_t cnt) { asm volatile("mbarrier.init.shared::cta.b64 [%0], %1;" :: "r"(b), "r"(cnt)); }
__device__ __forceinline__ void mbar_expect_tx(uint32_t b, uint32_t bytes) { asm volatile("mbarrier.arrive.expect_tx.shared::cta.b64 _, [%0], %1;" :: "r"(b), "r"(bytes) : "memory"); }
__device__ __forceinline__ void mbar_arrive(uint32_t b) { asm volatile("mbarrier.arrive.shared::cta.b64 _, [%0];" :: "r"(b) : "memory"); }
__device__ __forceinline__ void prof(int) {}
__device__ __forceinline__ void mbar_wait(uint32_t b, uint32_t parity) {
    asm volatile("{\n.reg .pred p;\n.reg .u32 c;\nmov.u32 c, 0;\n"
                 "WAIT_LOOP:\nmbarrier.try_wait.parity.shared::cta.b64 p, [%0], %1;\n@p bra WAIT_DONE;\n"
                 "add.u32 c, c, 1;\nsetp.lt.u32 p, c, 4000000;\n@p bra WAIT_LOOP;\ntrap;\nWAIT_DONE:\n}"
                 :: "r"(b), "r"(parity) : "memory");
}
__device__ __forceinline__ void smem_wait_gt(uint32_t addr, uint32_t val) {
    asm volatile("{\n.reg .pred p;\n.reg .u32 c, v;\nmov.u32 c, 0;\n"
                 "SW_LOOP:\nld.acquire.cta.shared.u32 v, [%0];\nsetp.gt.u32 p, v, %1;\n@p bra SW_DONE;\n"
                 "add.u32 c, c, 1;\nsetp.lt.u32 p, c, 100000000;\n@p bra SW_LOOP;\ntrap;\nSW_DONE:\n}"
                 :: "r"(addr), "r"(val) : "memory");
}
__device__ __forceinline__ void tma_2d(uint32_t dst, const CUtensorMap* tm, uint32_t b, int c0, int c1) {
    asm volatile("cp.async.bulk.tensor.2d.shared::cluster.global.mbarrier::complete_tx::bytes [%0], [%1, {%3, %4}], [%2];"
                 :: "r"(dst), "l"(tm), "r"(b), "r"(c0), "r"(c1) : "memory");
}
__device__ __forceinline__ void fence_async_smem() { asm volatile("fence.proxy.async.shared::cta;" ::: "memory"); }
__device__ __forceinline__ void fence_async_all() { asm volatile("fence.proxy.async;" ::: "memory"); }
__device__ __forceinline__ void named_bar(int id, int n) { asm volatile("bar.sync %0, %1;" :: "r"(id), "r"(n) : "memory"); }
__device__ __forceinline__ void wg_fence() { asm volatile("wgmma.fence.sync.aligned;" ::: "memory"); }
__device__ __forceinline__ void wg_commit() { asm volatile("wgmma.commit_group.sync.aligned;" ::: "memory"); }
template<int N> __device__ __forceinline__ void wg_wait() { asm volatile("wgmma.wait_group.sync.aligned %0;" :: "n"(N) : "memory"); }
template<int N> __device__ __forceinline__ void reg_fence(float* d) {
    #pragma unroll
    for (int i = 0; i < N; i++) asm volatile("" : "+f"(d[i]) :: "memory");
}
template<int N> __device__ __forceinline__ void reg_copy(float* d, const float* s) {
    #pragma unroll
    for (int i = 0; i < N; i++) asm volatile("mov.b32 %0, %1;" : "=f"(d[i]) : "f"(s[i]));
}
__device__ __forceinline__ uint32_t pack_bf16(float lo, float hi) { uint32_t r; asm("cvt.rn.bf16x2.f32 %0, %1, %2;" : "=r"(r) : "f"(hi), "f"(lo)); return r; }
__device__ __forceinline__ float bf_lo(uint32_t v) { return __uint_as_float(v << 16); }
__device__ __forceinline__ float bf_hi(uint32_t v) { return __uint_as_float(v & 0xffff0000u); }
__device__ __forceinline__ uint32_t sub_bf16x2(uint32_t a, uint32_t b) { uint32_t r; asm("sub.rn.bf16x2 %0, %1, %2;" : "=r"(r) : "r"(a), "r"(b)); return r; }
__device__ __forceinline__ float ex2(float x) { float r; asm("ex2.approx.ftz.f32 %0, %1;" : "=f"(r) : "f"(x)); return r; }
__device__ __forceinline__ float rcp(float x) { float r; asm("rcp.approx.ftz.f32 %0, %1;" : "=f"(r) : "f"(x)); return r; }
__device__ __forceinline__ float tanh_ap(float x) { float r; asm("tanh.approx.f32 %0, %1;" : "=f"(r) : "f"(x)); return r; }
__device__ __forceinline__ void sts32(uint32_t a, uint32_t v) { asm volatile("st.shared.b32 [%0], %1;" :: "r"(a), "r"(v)); }
__device__ __forceinline__ void sts128(uint32_t a, uint32_t x, uint32_t y, uint32_t z, uint32_t w) { asm volatile("st.shared.v4.b32 [%0], {%1,%2,%3,%4};" :: "r"(a), "r"(x), "r"(y), "r"(z), "r"(w)); }
__device__ __forceinline__ void sts64(uint32_t a, uint32_t x, uint32_t y) { asm volatile("st.shared.v2.b32 [%0], {%1,%2};" :: "r"(a), "r"(x), "r"(y)); }
__device__ __forceinline__ void lds64(uint32_t a, uint32_t* v) { asm volatile("ld.shared.v2.b32 {%0,%1}, [%2];" : "=r"(v[0]), "=r"(v[1]) : "r"(a)); }
__device__ __forceinline__ void lds128(uint32_t a, uint32_t* v) { asm volatile("ld.shared.v4.b32 {%0,%1,%2,%3}, [%4];" : "=r"(v[0]), "=r"(v[1]), "=r"(v[2]), "=r"(v[3]) : "r"(a) : "memory"); }
__device__ __forceinline__ float2 lds64f(uint32_t a) { float2 v; asm("ld.shared.v2.f32 {%0,%1}, [%2];" : "=f"(v.x), "=f"(v.y) : "r"(a)); return v; }
__device__ __forceinline__ void ldsm4(uint32_t a, uint32_t* v) {
    asm volatile("ldmatrix.sync.aligned.m8n8.x4.shared.b16 {%0,%1,%2,%3}, [%4];" : "=r"(v[0]), "=r"(v[1]), "=r"(v[2]), "=r"(v[3]) : "r"(a));
}
__device__ __forceinline__ void mma_ones(float* c, const uint32_t* a) {
    const uint32_t one2 = 0x3F803F80u;
    asm volatile("mma.sync.aligned.m16n8k16.row.col.f32.bf16.bf16.f32 {%0,%1,%2,%3}, {%4,%5,%6,%7}, {%8,%8}, {%0,%1,%2,%3};"
                 : "+f"(c[0]), "+f"(c[1]), "+f"(c[2]), "+f"(c[3]) : "r"(a[0]), "r"(a[1]), "r"(a[2]), "r"(a[3]), "r"(one2));
}
__device__ __forceinline__ void mma_bf16(float* c, const uint32_t* a, uint32_t b0, uint32_t b1) {
    asm volatile("mma.sync.aligned.m16n8k16.row.col.f32.bf16.bf16.f32 {%0,%1,%2,%3}, {%4,%5,%6,%7}, {%8,%9}, {%0,%1,%2,%3};"
                 : "+f"(c[0]), "+f"(c[1]), "+f"(c[2]), "+f"(c[3]) : "r"(a[0]), "r"(a[1]), "r"(a[2]), "r"(a[3]), "r"(b0), "r"(b1));
}
__device__ __forceinline__ unsigned int ld_acquire(const unsigned int* p) { unsigned int v; asm volatile("ld.acquire.gpu.global.u32 %0, [%1];" : "=r"(v) : "l"(p) : "memory"); return v; }
__device__ __forceinline__ void wait_cnt(const unsigned int* p, unsigned int target) {
    for (int i = 0; i < WAIT_ITERS; i++) {
        if ((int)(ld_acquire(p) - target) >= 0) return;
        __nanosleep(40);
    }
    __trap();
}
__device__ __forceinline__ uint32_t v_tid() { uint32_t r; asm volatile("mov.u32 %0, %%tid.x;" : "=r"(r)); return r; }
__device__ __forceinline__ uint32_t v_bid() { uint32_t r; asm volatile("mov.u32 %0, %%ctaid.x;" : "=r"(r)); return r; }
__device__ __forceinline__ uint32_t v_epoch() { uint32_t r; asm volatile("ld.shared.u32 %0, [%1];" : "=r"(r) : "r"(EPO)); return r; }
__device__ __forceinline__ void prefetch_l2(const void* p) { asm volatile("prefetch.global.L2 [%0];" :: "l"(p)); }

__host__ __device__ constexpr uint64_t mkdesc(uint32_t addr, uint32_t lbo, uint32_t sbo, uint32_t swz) {
    return (uint64_t)((addr & 0x3FFFF) >> 4) | ((uint64_t)((lbo >> 4) & 0x3FFF) << 16) | ((uint64_t)((sbo >> 4) & 0x3FFF) << 32) | ((uint64_t)swz << 62);
}

template<int SD> __device__ __forceinline__ void wg_rs64(float* d, const uint32_t* a, uint64_t bd) {
  if constexpr (SD) {
    asm volatile("{\n.reg .pred p;\nsetp.eq.b32 p, 0, 0;\n"
    "wgmma.mma_async.sync.aligned.m64n64k16.f32.bf16.bf16 {%0,%1,%2,%3,%4,%5,%6,%7,%8,%9,%10,%11,%12,%13,%14,%15,%16,%17,%18,%19,%20,%21,%22,%23,%24,%25,%26,%27,%28,%29,%30,%31}, {%32,%33,%34,%35}, %36, p, 1, 1, 1;\n}"
    : "+f"(d[0]),"+f"(d[1]),"+f"(d[2]),"+f"(d[3]),"+f"(d[4]),"+f"(d[5]),"+f"(d[6]),"+f"(d[7]),"+f"(d[8]),"+f"(d[9]),"+f"(d[10]),"+f"(d[11]),"+f"(d[12]),"+f"(d[13]),"+f"(d[14]),"+f"(d[15]),"+f"(d[16]),"+f"(d[17]),"+f"(d[18]),"+f"(d[19]),"+f"(d[20]),"+f"(d[21]),"+f"(d[22]),"+f"(d[23]),"+f"(d[24]),"+f"(d[25]),"+f"(d[26]),"+f"(d[27]),"+f"(d[28]),"+f"(d[29]),"+f"(d[30]),"+f"(d[31])
    : "r"(a[0]),"r"(a[1]),"r"(a[2]),"r"(a[3]), "l"(bd));
  } else {
    asm volatile("{\n.reg .pred p;\nsetp.ne.b32 p, 0, 0;\n"
    "wgmma.mma_async.sync.aligned.m64n64k16.f32.bf16.bf16 {%0,%1,%2,%3,%4,%5,%6,%7,%8,%9,%10,%11,%12,%13,%14,%15,%16,%17,%18,%19,%20,%21,%22,%23,%24,%25,%26,%27,%28,%29,%30,%31}, {%32,%33,%34,%35}, %36, p, 1, 1, 1;\n}"
    : "+f"(d[0]),"+f"(d[1]),"+f"(d[2]),"+f"(d[3]),"+f"(d[4]),"+f"(d[5]),"+f"(d[6]),"+f"(d[7]),"+f"(d[8]),"+f"(d[9]),"+f"(d[10]),"+f"(d[11]),"+f"(d[12]),"+f"(d[13]),"+f"(d[14]),"+f"(d[15]),"+f"(d[16]),"+f"(d[17]),"+f"(d[18]),"+f"(d[19]),"+f"(d[20]),"+f"(d[21]),"+f"(d[22]),"+f"(d[23]),"+f"(d[24]),"+f"(d[25]),"+f"(d[26]),"+f"(d[27]),"+f"(d[28]),"+f"(d[29]),"+f"(d[30]),"+f"(d[31])
    : "r"(a[0]),"r"(a[1]),"r"(a[2]),"r"(a[3]), "l"(bd));
  }
}
template<int SD> __device__ __forceinline__ void wg_ss64(float* d, uint64_t ad, uint64_t bd) {
  if constexpr (SD) {
    asm volatile("{\n.reg .pred p;\nsetp.eq.b32 p, 0, 0;\n"
    "wgmma.mma_async.sync.aligned.m64n64k16.f32.bf16.bf16 {%0,%1,%2,%3,%4,%5,%6,%7,%8,%9,%10,%11,%12,%13,%14,%15,%16,%17,%18,%19,%20,%21,%22,%23,%24,%25,%26,%27,%28,%29,%30,%31}, %32, %33, p, 1, 1, 0, 1;\n}"
    : "+f"(d[0]),"+f"(d[1]),"+f"(d[2]),"+f"(d[3]),"+f"(d[4]),"+f"(d[5]),"+f"(d[6]),"+f"(d[7]),"+f"(d[8]),"+f"(d[9]),"+f"(d[10]),"+f"(d[11]),"+f"(d[12]),"+f"(d[13]),"+f"(d[14]),"+f"(d[15]),"+f"(d[16]),"+f"(d[17]),"+f"(d[18]),"+f"(d[19]),"+f"(d[20]),"+f"(d[21]),"+f"(d[22]),"+f"(d[23]),"+f"(d[24]),"+f"(d[25]),"+f"(d[26]),"+f"(d[27]),"+f"(d[28]),"+f"(d[29]),"+f"(d[30]),"+f"(d[31])
    : "l"(ad), "l"(bd));
  } else {
    asm volatile("{\n.reg .pred p;\nsetp.ne.b32 p, 0, 0;\n"
    "wgmma.mma_async.sync.aligned.m64n64k16.f32.bf16.bf16 {%0,%1,%2,%3,%4,%5,%6,%7,%8,%9,%10,%11,%12,%13,%14,%15,%16,%17,%18,%19,%20,%21,%22,%23,%24,%25,%26,%27,%28,%29,%30,%31}, %32, %33, p, 1, 1, 0, 1;\n}"
    : "+f"(d[0]),"+f"(d[1]),"+f"(d[2]),"+f"(d[3]),"+f"(d[4]),"+f"(d[5]),"+f"(d[6]),"+f"(d[7]),"+f"(d[8]),"+f"(d[9]),"+f"(d[10]),"+f"(d[11]),"+f"(d[12]),"+f"(d[13]),"+f"(d[14]),"+f"(d[15]),"+f"(d[16]),"+f"(d[17]),"+f"(d[18]),"+f"(d[19]),"+f"(d[20]),"+f"(d[21]),"+f"(d[22]),"+f"(d[23]),"+f"(d[24]),"+f"(d[25]),"+f"(d[26]),"+f"(d[27]),"+f"(d[28]),"+f"(d[29]),"+f"(d[30]),"+f"(d[31])
    : "l"(ad), "l"(bd));
  }
}
template<int SD> __device__ __forceinline__ void wg_rs72(float* d, const uint32_t* a, uint64_t bd) {
  if constexpr (SD) {
    asm volatile("{\n.reg .pred p;\nsetp.eq.b32 p, 0, 0;\n"
    "wgmma.mma_async.sync.aligned.m64n72k16.f32.bf16.bf16 {%0,%1,%2,%3,%4,%5,%6,%7,%8,%9,%10,%11,%12,%13,%14,%15,%16,%17,%18,%19,%20,%21,%22,%23,%24,%25,%26,%27,%28,%29,%30,%31,%32,%33,%34,%35}, {%36,%37,%38,%39}, %40, p, 1, 1, 1;\n}"
    : "+f"(d[0]),"+f"(d[1]),"+f"(d[2]),"+f"(d[3]),"+f"(d[4]),"+f"(d[5]),"+f"(d[6]),"+f"(d[7]),"+f"(d[8]),"+f"(d[9]),"+f"(d[10]),"+f"(d[11]),"+f"(d[12]),"+f"(d[13]),"+f"(d[14]),"+f"(d[15]),"+f"(d[16]),"+f"(d[17]),"+f"(d[18]),"+f"(d[19]),"+f"(d[20]),"+f"(d[21]),"+f"(d[22]),"+f"(d[23]),"+f"(d[24]),"+f"(d[25]),"+f"(d[26]),"+f"(d[27]),"+f"(d[28]),"+f"(d[29]),"+f"(d[30]),"+f"(d[31]),"+f"(d[32]),"+f"(d[33]),"+f"(d[34]),"+f"(d[35])
    : "r"(a[0]),"r"(a[1]),"r"(a[2]),"r"(a[3]), "l"(bd));
  } else {
    asm volatile("{\n.reg .pred p;\nsetp.ne.b32 p, 0, 0;\n"
    "wgmma.mma_async.sync.aligned.m64n72k16.f32.bf16.bf16 {%0,%1,%2,%3,%4,%5,%6,%7,%8,%9,%10,%11,%12,%13,%14,%15,%16,%17,%18,%19,%20,%21,%22,%23,%24,%25,%26,%27,%28,%29,%30,%31,%32,%33,%34,%35}, {%36,%37,%38,%39}, %40, p, 1, 1, 1;\n}"
    : "+f"(d[0]),"+f"(d[1]),"+f"(d[2]),"+f"(d[3]),"+f"(d[4]),"+f"(d[5]),"+f"(d[6]),"+f"(d[7]),"+f"(d[8]),"+f"(d[9]),"+f"(d[10]),"+f"(d[11]),"+f"(d[12]),"+f"(d[13]),"+f"(d[14]),"+f"(d[15]),"+f"(d[16]),"+f"(d[17]),"+f"(d[18]),"+f"(d[19]),"+f"(d[20]),"+f"(d[21]),"+f"(d[22]),"+f"(d[23]),"+f"(d[24]),"+f"(d[25]),"+f"(d[26]),"+f"(d[27]),"+f"(d[28]),"+f"(d[29]),"+f"(d[30]),"+f"(d[31]),"+f"(d[32]),"+f"(d[33]),"+f"(d[34]),"+f"(d[35])
    : "r"(a[0]),"r"(a[1]),"r"(a[2]),"r"(a[3]), "l"(bd));
  }
}
template<int SD> __device__ __forceinline__ void wg_ss72(float* d, uint64_t ad, uint64_t bd) {
  if constexpr (SD) {
    asm volatile("{\n.reg .pred p;\nsetp.eq.b32 p, 0, 0;\n"
    "wgmma.mma_async.sync.aligned.m64n72k16.f32.bf16.bf16 {%0,%1,%2,%3,%4,%5,%6,%7,%8,%9,%10,%11,%12,%13,%14,%15,%16,%17,%18,%19,%20,%21,%22,%23,%24,%25,%26,%27,%28,%29,%30,%31,%32,%33,%34,%35}, %36, %37, p, 1, 1, 0, 1;\n}"
    : "+f"(d[0]),"+f"(d[1]),"+f"(d[2]),"+f"(d[3]),"+f"(d[4]),"+f"(d[5]),"+f"(d[6]),"+f"(d[7]),"+f"(d[8]),"+f"(d[9]),"+f"(d[10]),"+f"(d[11]),"+f"(d[12]),"+f"(d[13]),"+f"(d[14]),"+f"(d[15]),"+f"(d[16]),"+f"(d[17]),"+f"(d[18]),"+f"(d[19]),"+f"(d[20]),"+f"(d[21]),"+f"(d[22]),"+f"(d[23]),"+f"(d[24]),"+f"(d[25]),"+f"(d[26]),"+f"(d[27]),"+f"(d[28]),"+f"(d[29]),"+f"(d[30]),"+f"(d[31]),"+f"(d[32]),"+f"(d[33]),"+f"(d[34]),"+f"(d[35])
    : "l"(ad), "l"(bd));
  } else {
    asm volatile("{\n.reg .pred p;\nsetp.ne.b32 p, 0, 0;\n"
    "wgmma.mma_async.sync.aligned.m64n72k16.f32.bf16.bf16 {%0,%1,%2,%3,%4,%5,%6,%7,%8,%9,%10,%11,%12,%13,%14,%15,%16,%17,%18,%19,%20,%21,%22,%23,%24,%25,%26,%27,%28,%29,%30,%31,%32,%33,%34,%35}, %36, %37, p, 1, 1, 0, 1;\n}"
    : "+f"(d[0]),"+f"(d[1]),"+f"(d[2]),"+f"(d[3]),"+f"(d[4]),"+f"(d[5]),"+f"(d[6]),"+f"(d[7]),"+f"(d[8]),"+f"(d[9]),"+f"(d[10]),"+f"(d[11]),"+f"(d[12]),"+f"(d[13]),"+f"(d[14]),"+f"(d[15]),"+f"(d[16]),"+f"(d[17]),"+f"(d[18]),"+f"(d[19]),"+f"(d[20]),"+f"(d[21]),"+f"(d[22]),"+f"(d[23]),"+f"(d[24]),"+f"(d[25]),"+f"(d[26]),"+f"(d[27]),"+f"(d[28]),"+f"(d[29]),"+f"(d[30]),"+f"(d[31]),"+f"(d[32]),"+f"(d[33]),"+f"(d[34]),"+f"(d[35])
    : "l"(ad), "l"(bd));
  }
}
template<int SD> __device__ __forceinline__ void wg_tt64(float* d, uint64_t ad, uint64_t bd) {
  if constexpr (SD) {
    asm volatile("{\n.reg .pred p;\nsetp.eq.b32 p, 0, 0;\n"
    "wgmma.mma_async.sync.aligned.m64n64k16.f32.bf16.bf16 {%0,%1,%2,%3,%4,%5,%6,%7,%8,%9,%10,%11,%12,%13,%14,%15,%16,%17,%18,%19,%20,%21,%22,%23,%24,%25,%26,%27,%28,%29,%30,%31}, %32, %33, p, 1, 1, 1, 1;\n}"
    : "+f"(d[0]),"+f"(d[1]),"+f"(d[2]),"+f"(d[3]),"+f"(d[4]),"+f"(d[5]),"+f"(d[6]),"+f"(d[7]),"+f"(d[8]),"+f"(d[9]),"+f"(d[10]),"+f"(d[11]),"+f"(d[12]),"+f"(d[13]),"+f"(d[14]),"+f"(d[15]),"+f"(d[16]),"+f"(d[17]),"+f"(d[18]),"+f"(d[19]),"+f"(d[20]),"+f"(d[21]),"+f"(d[22]),"+f"(d[23]),"+f"(d[24]),"+f"(d[25]),"+f"(d[26]),"+f"(d[27]),"+f"(d[28]),"+f"(d[29]),"+f"(d[30]),"+f"(d[31])
    : "l"(ad), "l"(bd));
  } else {
    asm volatile("{\n.reg .pred p;\nsetp.ne.b32 p, 0, 0;\n"
    "wgmma.mma_async.sync.aligned.m64n64k16.f32.bf16.bf16 {%0,%1,%2,%3,%4,%5,%6,%7,%8,%9,%10,%11,%12,%13,%14,%15,%16,%17,%18,%19,%20,%21,%22,%23,%24,%25,%26,%27,%28,%29,%30,%31}, %32, %33, p, 1, 1, 1, 1;\n}"
    : "+f"(d[0]),"+f"(d[1]),"+f"(d[2]),"+f"(d[3]),"+f"(d[4]),"+f"(d[5]),"+f"(d[6]),"+f"(d[7]),"+f"(d[8]),"+f"(d[9]),"+f"(d[10]),"+f"(d[11]),"+f"(d[12]),"+f"(d[13]),"+f"(d[14]),"+f"(d[15]),"+f"(d[16]),"+f"(d[17]),"+f"(d[18]),"+f"(d[19]),"+f"(d[20]),"+f"(d[21]),"+f"(d[22]),"+f"(d[23]),"+f"(d[24]),"+f"(d[25]),"+f"(d[26]),"+f"(d[27]),"+f"(d[28]),"+f"(d[29]),"+f"(d[30]),"+f"(d[31])
    : "l"(ad), "l"(bd));
  }
}

template<int V> struct IC { static constexpr int v = V; };
template<int I, int N, class F> __device__ __forceinline__ void sfor(F&& f) {
    if constexpr (I < N) { f(IC<I>{}); sfor<I + 1, N>(f); }
}

enum { K_QKV = 0, K_H = 1 };

struct Ctx {
    uint32_t tph;
    uint32_t tid_;
    bool pf = false;
    __device__ __forceinline__ uint32_t tid() const { uint32_t r; asm volatile("mov.u32 %0, %1;" : "=r"(r) : "r"(tid_)); return r; }
};
__device__ __forceinline__ void release_slot(const Ctx& c, int slot) { if ((c.tid() & 31) == 0) mbar_arrive(bar(B_EMPTY + slot)); }

__device__ __forceinline__ void turn_wait(const Ctx& c) { asm volatile("bar.sync %0, 256;" :: "r"(4 + (c.tid() >> 7)) : "memory"); }
__device__ __forceinline__ void turn_pass(const Ctx& c) { asm volatile("bar.arrive %0, 256;" :: "r"(5 - (c.tid() >> 7)) : "memory"); }

template<int KIND, class PART, class POST>
__device__ __forceinline__ void run_step(Ctx& c, float* acc, const uint32_t* a, PART&& part, POST&& post, bool last = false) {
    constexpr int NST = (KIND == K_QKV) ? 6 : 3;
    constexpr int KPS = 36 / NST;
    sfor<0, NST>([&](auto ST) {
        constexpr int st = decltype(ST)::v;
        constexpr int slot = st % 3;
        mbar_wait(bar(B_FULL + slot), c.tph);
        uint32_t wgo = 0;
        if constexpr (st == NST - 1) wgo = (c.tid() >> 7) * 512;
        if (KIND == K_H && c.pf) prof(44 + st * 5);
        turn_wait(c);
        if (KIND == K_H && c.pf) prof(45 + st * 5);
        wg_fence();
        sfor<0, KPS>([&](auto KK) {
            constexpr int kk = decltype(KK)::v;
            constexpr int ks = st * KPS + kk;
            constexpr int SD = ks ? 1 : 0;
            if constexpr (KIND == K_QKV) {
                constexpr uint64_t bd = mkdesc(RING + slot * SLOT + kk * 2048, 12288, 1024, 1);
                if constexpr (ks < 32) wg_rs72<SD>(acc, a + ks * 4, bd);
                else wg_ss72<SD>(acc, mkdesc(XB + (ks - 32) * 32, 16, 1024, 1) + wgo, bd);
            } else {
                constexpr uint64_t bd = mkdesc(RING + slot * SLOT + kk * 2048, 16, 1024, 1);
                if constexpr (ks < 32) wg_rs64<SD>(acc, a + ks * 4, bd);
                else wg_ss64<SD>(acc, mkdesc(XB + (ks - 32) * 32, 16, 1024, 1) + wgo, bd);
            }
        });
        wg_commit();
        if (st < NST - 1 || !last || c.tid() < 128) turn_pass(c);
        if (KIND == K_H && c.pf) prof(46 + st * 5);
        part(ST);
        if (KIND == K_H && c.pf) prof(47 + st * 5);
        wg_wait<0>();
        if (KIND == K_H && c.pf) prof(48 + st * 5);
        release_slot(c, slot);
        if constexpr (slot == 2) c.tph ^= 1;
        post(ST);
    });
    if constexpr (KIND == K_QKV) reg_fence<36>(acc); else reg_fence<32>(acc);
}

__device__ __forceinline__ float phi(float t) {
    float e = ex2(t * 1.4426950408889634f);
    return (t > 0.f ? t + 1.0f : e) + 1e-6f;
}
__device__ __forceinline__ float gelu_h(float hx) {
    float u = hx * fmaf(hx * hx, 0.2854192650f, 1.5957691216f);
    return fmaf(hx, tanh_ap(u), hx);
}

struct Params {
    const __nv_bfloat16* x;
    const __nv_bfloat16* wqkv;
    const __nv_bfloat16* wo;
    const __nv_bfloat16* w1;
    const __nv_bfloat16* b1;
    const __nv_bfloat16* w2;
    const __nv_bfloat16* b2;
    __nv_bfloat16* out;
};

__global__ void __launch_bounds__(384, 1)
fused_kernel(const __grid_constant__ CUtensorMap tm_x, const __grid_constant__ CUtensorMap tm_w1,
             const __grid_constant__ CUtensorMap tm_w2, const __grid_constant__ CUtensorMap tm_wo,
             const __grid_constant__ CUtensorMap tm_o, const __grid_constant__ CUtensorMap tm_qkv,
             const __grid_constant__ CUtensorMap tm_qkve, const __grid_constant__ CUtensorMap tm_ost, const Params p) {
    extern __shared__ __align__(1024) unsigned char smem_raw[];
    const int tid = threadIdx.x;
    const int bid = blockIdx.x;
    const bool is_main = bid < NMAIN;
    const int j = bid & 7;
    const int m = bid >> 3;

    if (tid == 0) {
        if ((uint32_t)__cvta_generic_to_shared(smem_raw) != SB) __trap();
        for (int i = 0; i < 3; i++) {
            mbar_init(bar(B_FULL + i), 1); mbar_init(bar(B_EMPTY + i), 8);
            mbar_init(bar(B_XFULL + i), 1);
        }
        mbar_init(bar(B_KVB), 2); mbar_init(bar(B_INIT), 1);
        mbar_init(bar(B_OFULL), 1); mbar_init(bar(B_O8FULL), 1); mbar_init(bar(B_OFREE), 8); mbar_init(bar(B_O8FREE), 8);
        asm volatile("fence.mbarrier_init.release.cluster;" ::: "memory");
    }
    if (tid == 256) { asm volatile("prefetch.tensormap [%0];" :: "l"(&tm_x) : "memory"); asm volatile("prefetch.tensormap [%0];" :: "l"(&tm_qkv) : "memory"); asm volatile("prefetch.tensormap [%0];" :: "l"(&tm_qkve) : "memory"); }
    if (tid >= 40 && tid < 48) sts32(EVC + (tid - 40) * 4, 0);
    if (tid == 48) sts32(EPO + 4, 0);
    __syncthreads();

    if (tid >= 256) {
        asm volatile("setmaxnreg.dec.sync.aligned.u32 24;");
        const int hw = (tid >> 5) - 8, lane = tid & 31;
        uint32_t epoch = 0;
        if (hw > 0) {
            epoch = g_epoch[bid];
            if (hw == 3) {
                if (lane == 0) sts32(EPO, epoch);
                if (is_main) {
                    #pragma unroll 1
                    for (int i = lane; i < 288; i += 32) {
                        uint32_t v = *reinterpret_cast<const uint32_t*>(p.b1 + j * 576 + 2 * i);
                        sts32(B1S + 8 * i, __float_as_uint(0.5f * bf_lo(v))); sts32(B1S + 8 * i + 4, __float_as_uint(0.5f * bf_hi(v)));
                    }
                }
                uint32_t v = *reinterpret_cast<const uint32_t*>(p.b2 + (is_main ? j : 8) * 64 + 2 * lane);
                sts32(B2S + 8 * lane, v << 16); sts32(B2S + 8 * lane + 4, v & 0xffff0000u);
                __syncwarp();
                if (lane == 0) mbar_arrive(bar(B_INIT));
            }
        }
        const uint32_t par = epoch & 1;
        if (hw == 0) {
            if (lane == 0) {
                uint32_t n = 0;
                if (is_main) {
                    #pragma unroll 1
                    for (int kb = 0; kb < 9; kb++) {
                        if (kb % 3 == 0) mbar_expect_tx(bar(B_XFULL + kb / 3), 49152);
                        tma_2d(HA + kb * 16384, &tm_x, bar(B_XFULL + kb / 3), kb * 64, m * 128);
                    }
                    #pragma unroll 1
                    for (int u = 0; u < 18; u++) {
                        const int st = u % 3, step = u / 6;
                        const int col = ((step == 2) ? 0 : (step + 1) * 576) + j * 72, row = (u % 6) * 96;
                        mbar_wait(bar(B_EMPTY + st), (n & 1) ^ 1);
                        mbar_expect_tx(bar(B_FULL + st), 96 * 144);
                        tma_2d(RING + st * SLOT, &tm_qkv, bar(B_FULL + st), col, row);
                        tma_2d(RING + st * SLOT + 12288, &tm_qkve, bar(B_FULL + st), col + 64, row);
                        if (st == 2) n++;
                    }
                }
                const int nsteps = is_main ? 19 : 1;
                #pragma unroll 1
                for (int s = 0; s < nsteps; s++, n++) {
                    const CUtensorMap* tm; int col, row;
                    if (!is_main) { tm = &tm_wo; col = 512; row = 0; }
                    else if (s < 9) { tm = &tm_w1; col = j * 576 + s * 64; row = 0; }
                    else if (s < 18) { tm = &tm_w2; col = (s == 9) ? 512 : (((j + s - 9) & 7) * 64); row = j * 576; }
                    else { tm = &tm_wo; col = j * 64; row = 0; }
                    #pragma unroll 1
                    for (int st = 0; st < 3; st++) {
                        mbar_wait(bar(B_EMPTY + st), (n & 1) ^ 1);
                        mbar_expect_tx(bar(B_FULL + st), SLOT);
                        tma_2d(RING + st * SLOT, tm, bar(B_FULL + st), col, row + st * 192);
                    }
                }
            }
        } else {
            if (is_main) {
                const int t = tid - 288;
                __nanosleep(PF0_NS);
                #pragma unroll 1
                for (int i = t; i < 36 * 6; i += 96) {
                    int r = i / 6, q = i - r * 6;
                    prefetch_l2(reinterpret_cast<const char*>(p.wqkv) + (36 * m + r) * 3456 + (q >> 1) * 1152 + j * 144 + (q & 1) * 128);
                }
                __nanosleep(PF1_NS);
                #pragma unroll 1
                for (int i = t; i < 36 * 9; i += 96) {
                    int r = i / 9, q = i - r * 9;
                    prefetch_l2(reinterpret_cast<const char*>(p.w1) + (36 * m + r) * 9216 + j * 1152 + q * 128);
                    __nanosleep(PF3_NS);
                }
                __nanosleep(PF2_NS);
                #pragma unroll 1
                for (int i = t; i < 36 * 9; i += 96)
                    prefetch_l2(reinterpret_cast<const char*>(p.w2) + (576 * j + 36 * m) * 1152 + i * 128);
                if (t < 41 && (bid * 41 + t) < 5184) prefetch_l2(reinterpret_cast<const char*>(p.wo) + (bid * 41 + t) * 128);
                if (hw != 2) {
                    if (lane == 0) wait_cnt(cnt_kv(j), (epoch + 1) * 16);
                    __syncwarp();
                    const float4* kv = reinterpret_cast<const float4*>(g_kv + (par * 8 + j) * 1440);
                    #pragma unroll 2
                    for (int i = lane + (hw == 1 ? 0 : 32); i < 360; i += 64) {
                        const float4 v = __ldcg(kv + i);
                        const int d = i / 5, e = (i - d * 5) * 4, h = d / 18;
                        const uint32_t base = KVB + (d >> 3) * 128 + (d & 7) * 16;
                        const int n0 = 8 + h * 18 + e;
                        sts32(base + (n0 >> 3) * 1280 + (n0 & 7) * 2, pack_bf16(v.x, v.y));
                        if (e < 16) sts32(base + ((n0 + 2) >> 3) * 1280 + ((n0 + 2) & 7) * 2, pack_bf16(v.z, v.w));
                        else asm volatile("st.shared.u16 [%0], %1;" :: "r"(base + h * 2), "h"((unsigned short)pack_bf16(v.z, 0.f)) : "memory");
                    }
                    fence_async_smem();
                    __syncwarp();
                    if (lane == 0) mbar_arrive(bar(B_KVB));
                }
            }
            if (hw == 1) {
                if (lane == 0) {
                    const int nit = is_main ? 1 : 4;
                    for (int it = 0; it < nit; it++) {
                        const int mt = is_main ? m : ((bid - NMAIN) * 4 + it);
                        const bool wf = is_main || it > 0;
                        const uint32_t fp = is_main ? 0 : ((it - 1) & 1);
                        wait_cnt(cnt_o(mt), (epoch + 1) * 8);
                        fence_async_all();
                        if (wf) mbar_wait(bar(B_OFREE), fp);
                        mbar_expect_tx(bar(B_OFULL), 131072);
                        #pragma unroll 1
                        for (int kb = 0; kb < 8; kb++) tma_2d(HA + kb * 16384, &tm_o, bar(B_OFULL), kb * 64, mt * 128);
                        if (wf) mbar_wait(bar(B_O8FREE), fp);
                        mbar_expect_tx(bar(B_O8FULL), 16384);
                        tma_2d(XB, &tm_o, bar(B_O8FULL), 512, mt * 128);
                    }
                    if (is_main) { wait_cnt(cnt_y(m, j), (epoch + 1) * 7); asm volatile("st.release.cta.shared.u32 [%0], %1;" :: "r"(EPO + 4), "r"(1) : "memory"); }
                }
            } else if (hw == 2) {
                if (!is_main) {
                    if (lane == 0) {
                        #pragma unroll 1
                        for (int it = 0; it < 4; it++) {
                            wait_cnt(cnt_y((bid - NMAIN) * 4 + it, 8), (epoch + 1) * 8);
                            asm volatile("st.release.cta.shared.u32 [%0], %1;" :: "r"(EPO + 4), "r"(it + 1) : "memory");
                        }
                    }
                } else {
                    #pragma unroll 1
                    for (int e = 0; e < 10; e++) {
                        int spin = 0;
                        while (true) {
                            uint32_t v;
                            asm volatile("ld.acquire.cta.shared.u32 %0, [%1];" : "=r"(v) : "r"(EVC + (lane & 7) * 4) : "memory");
                            if (__all_sync(0xffffffffu, v > (uint32_t)e)) break;
                            if (++spin > 20000000) __trap();
                            __nanosleep(20);
                        }
                        if (lane == 0) {
                            unsigned int* cp = (e == 0) ? cnt_kv(j) : (e == 1) ? cnt_o(m) : cnt_y(m, e == 2 ? 8 : ((j + e - 2) & 7));
                            if (e == 1) fence_async_all();
                            __threadfence();
                            asm volatile("red.relaxed.gpu.global.add.u32 [%0], 1;" :: "l"(cp) : "memory");
                        }
                        __syncwarp();
                    }
                }
            } else {
                {
                    const int t0 = is_main ? (m * 9 + j) : ((bid - NMAIN) * 4 * 9 + 8);
                    const int nt = is_main ? 1 : 4;
                    for (int t = 0; t < nt; t++) {
                        uint4* z = reinterpret_cast<uint4*>(g_yacc + (size_t)((par ^ 1) * 144 + t0 + t * 9) * YT_BYTES);
                        for (int i = lane; i < YT_BYTES / 16; i += 32) z[i] = make_uint4(0, 0, 0, 0);
                    }
                    if (is_main && m == 0) {
                        float* z = g_kv + ((par ^ 1) * 8 + j) * 1440;
                        for (int i = lane; i < 1440; i += 32) z[i] = 0.f;
                    }
                }
            }
        }
    } else {
        asm volatile("setmaxnreg.inc.sync.aligned.u32 240;");
        prof(0);
        Ctx c; c.tph = 0; c.tid_ = v_tid();
        float hc[32], pv[36];
        if (tid >> 7) turn_pass(c);
        auto event = [&](uint32_t ev) {
            __syncwarp();
            if (((c.tid() & 31) == 0)) asm volatile("st.release.cta.shared.u32 [%0], %1;" :: "r"(EVC + (c.tid() >> 3)), "r"(ev) : "memory");
        };
        auto warp_arrive = [&](uint32_t b) { __syncwarp(); if (((c.tid() & 31) == 0)) mbar_arrive(b); };

        auto lrow_off = [&]() { uint32_t t_ = c.tid(); return HA + ((t_ >> 5) * 16 + (t_ & 15)) * 128 + ((((t_ >> 4) & 1) ^ (t_ & 7)) << 4); };
        auto tail_off = [&]() { uint32_t t_ = c.tid(), g = (t_ >> 2) & 7; return XB + ((t_ >> 5) * 16 + g) * 128 + (g << 4) + (t_ & 3) * 4; };
        if (is_main) {
            uint32_t a[128];
            float rs0, rs1;
            {
                uint32_t tl[16];
                const uint32_t lrow = lrow_off();
                float cs[4][4], sq[8][4];
                #pragma unroll
                for (int i = 0; i < 4; i++) {
                    #pragma unroll
                    for (int k = 0; k < 4; k++) { cs[i][k] = 0.f; sq[i][k] = 0.f; sq[i + 4][k] = 0.f; }
                }
                uint32_t s00 = 0, s11 = 0;
                auto frag = [&](auto KS) -> uint32_t* { constexpr int ks = decltype(KS)::v; return (ks < 32) ? (a + (ks & 31) * 4) : (tl + (ks & 3) * 4); };
                auto sqacc = [&](auto KS) {
                    constexpr int ks = decltype(KS)::v;
                    const uint32_t* f = frag(KS);
                    uint32_t v[4];
                    #pragma unroll
                    for (int r = 0; r < 4; r++) v[r] = sub_bf16x2(f[r], (r & 1) ? s11 : s00);
                    mma_bf16(sq[(ks & 3) * 2], v, v[0], v[2]);
                    mma_bf16(sq[(ks & 3) * 2 + 1], v, v[1], v[3]);
                };
                sfor<0, 3>([&](auto G) {
                    constexpr int g = decltype(G)::v;
                    mbar_wait(bar(B_XFULL + g), 0);
                    prof(37 + g);
                    sfor<12 * g, 12 * g + 12>([&](auto KS) {
                        constexpr int ks = decltype(KS)::v;
                        ldsm4((lrow ^ ((ks % 4) << 5)) + (ks / 4) * 16384, frag(KS));
                    });
                    sfor<12 * g, 12 * g + 12>([&](auto KS) { mma_ones(cs[decltype(KS)::v & 3], frag(KS)); });
                    if constexpr (g == 0) {
                        const float t0 = (cs[0][0] + cs[1][0] + cs[2][0] + cs[3][0]) * (1.0f / 192.0f), t1 = (cs[0][2] + cs[1][2] + cs[2][2] + cs[3][2]) * (1.0f / 192.0f);
                        s00 = pack_bf16(t0, t0); s11 = pack_bf16(t1, t1);
                    }
                    sfor<12 * g, 12 * g + 12>(sqacc);
                });
                prof(2);
                const float mean0 = (cs[0][0] + cs[1][0] + cs[2][0] + cs[3][0]) * (1.0f / 576.0f), mean1 = (cs[0][2] + cs[1][2] + cs[2][2] + cs[3][2]) * (1.0f / 576.0f);
                const uint32_t m00 = pack_bf16(mean0, mean0), m11 = pack_bf16(mean1, mean1);
                const uint32_t tb = tail_off();
                #pragma unroll
                for (int i = 0; i < 16; i++) sts32((tb ^ ((i >> 1) << 4)) + (i & 1) * 1024, sub_bf16x2(tl[i], (i & 1) ? m11 : m00));
                fence_async_smem();
                #pragma unroll
                for (int i = 0; i < 128; i++) a[i] = sub_bf16x2(a[i], (i & 1) ? m11 : m00);
                {
                    const uint32_t l_ = c.tid() & 31, g_ = l_ >> 2, src = (l_ & 28) | (g_ >> 1);
                    rs0 = __shfl_sync(0xffffffffu, (g_ & 1) ? (sq[0][1] + sq[2][1] + sq[4][1] + sq[6][1]) : (sq[0][0] + sq[2][0] + sq[4][0] + sq[6][0]), src);
                    rs1 = __shfl_sync(0xffffffffu, (g_ & 1) ? (sq[1][3] + sq[3][3] + sq[5][3] + sq[7][3]) : (sq[1][2] + sq[3][2] + sq[5][2] + sq[7][2]), src);
                    const float d0 = mean0 - bf_lo(s00), d1 = mean1 - bf_lo(s11);
                    rs0 = rsqrtf(fmaxf(fmaf(rs0, 1.0f / 576.0f, -d0 * d0), 0.f) + 1e-5f);
                    rs1 = rsqrtf(fmaxf(fmaf(rs1, 1.0f / 576.0f, -d1 * d1), 0.f) + 1e-5f);
                }
                named_bar(1, 256);
            }
            prof(3);
            auto cm_off = [&]() { uint32_t t_ = c.tid(); return (t_ >> 5) * 256 + (t_ & 31) * 4; };
            {
                float qc[36];
                #pragma unroll
                for (int i = 0; i < 36; i++) { qc[i] = 0.f; pv[i] = 0.f; }
                #pragma unroll 1
                for (int s = 0; s < 3; s++) {
                    c.pf = (s == 0);
                    run_step<K_QKV>(c, qc, a, [&](auto ST) {
                        constexpr int st = decltype(ST)::v;
                        if (s > 0) {
                            const uint32_t cm = cm_off();
                            sfor<0, 9>([&](auto B) {
                                constexpr int b = decltype(B)::v;
                                if constexpr ((b * 6) / 9 == st) {
                                    const float v0 = pv[4 * b] * rs0, v1 = pv[4 * b + 1] * rs0, v2 = pv[4 * b + 2] * rs1, v3 = pv[4 * b + 3] * rs1;
                                    if (s == 1) {
                                        sts32(PKT + b * 2048 + cm, pack_bf16(phi(v0), phi(v1)));
                                        sts32(PKT + b * 2048 + cm + 128, pack_bf16(phi(v2), phi(v3)));
                                    } else {
                                        const uint32_t w0 = pack_bf16(v0, v1), w1 = pack_bf16(v2, v3);
                                        if constexpr (b <= 4) { sts32(VT + b * 2048 + cm, w0); sts32(VT + b * 2048 + cm + 128, w1); }
                                        if constexpr (b >= 4) { sts32(VT + (b + 2) * 2048 + cm, w0); sts32(VT + (b + 2) * 2048 + cm + 128, w1); }
                                        if constexpr (b == 0) {
                                            const uint32_t one = (cm & 12) ? 0u : 0x00003F80u;
                                            sts32(VT + 5 * 2048 + cm, one); sts32(VT + 5 * 2048 + cm + 128, one);
                                        }
                                        if constexpr (b == 8) {
                                            const uint32_t z = KVB + c.tid() * 16;
                                            sts128(z, 0, 0, 0, 0); sts128(z + 4096, 0, 0, 0, 0); sts128(z + 8192, 0, 0, 0, 0);
                                            if (z < KVB + 512) sts128(z + 12288, 0, 0, 0, 0);
                                            fence_async_smem();
                                        }
                                    }
                                }
                            });
                        }
                    }, [](auto) {});
                    reg_copy<36>(pv, qc);
                    prof(4 + s);
                }
            }
            {
                #pragma unroll
                for (int i = 0; i < 32; i++) hc[i] = 0.f;
                named_bar(1, 256);
                const uint32_t wgo = ((c.tid() >> 7) * 512);
                wg_fence();
                sfor<0, 8>([&](auto KS) {
                    constexpr int ks = decltype(KS)::v;
                    wg_tt64<(ks ? 1 : 0)>(hc, mkdesc(PKT + ks * 256, 128, 2048, 0) + wgo,
                                          mkdesc(VT + ks * 256, 128, 2048, 0) + wgo + (wgo >> 2));
                });
                wg_commit();
                const uint32_t pq = PQT + cm_off() + ((c.tid() >> 7) * 512) * 16;
                sfor<0, 9>([&](auto B) {
                    constexpr int b = decltype(B)::v;
                    sts32(pq + b * 1024, pack_bf16(phi(pv[4 * b] * rs0), phi(pv[4 * b + 1] * rs0)));
                    sts32(pq + b * 1024 + 128, pack_bf16(phi(pv[4 * b + 2] * rs1), phi(pv[4 * b + 3] * rs1)));
                });
                fence_async_smem();
                wg_wait<0>();
                reg_fence<32>(hc);
                reg_copy<24>(pv, hc);
            }
            prof(7);
            rs0 *= 0.5f; rs1 *= 0.5f;
            mbar_wait(bar(B_INIT), 0);
            auto gelun = [&](auto B0, auto B1, uint32_t bofs, uint32_t* w) {
                constexpr int b0 = decltype(B0)::v, nb = decltype(B1)::v - b0;
                float2 bv[nb];
                #pragma unroll
                for (int i = 0; i < nb; i++) bv[i] = lds64f(bofs + (b0 + i) * 32);
                #pragma unroll
                for (int i = 0; i < nb; i++) {
                    const int b = b0 + i;
                    w[2 * i]     = pack_bf16(gelu_h(fmaf(pv[4 * b], rs0, bv[i].x)), gelu_h(fmaf(pv[4 * b + 1], rs0, bv[i].y)));
                    w[2 * i + 1] = pack_bf16(gelu_h(fmaf(pv[4 * b + 2], rs1, bv[i].x)), gelu_h(fmaf(pv[4 * b + 3], rs1, bv[i].y)));
                }
            };
            auto spill_off = [&]() { uint32_t t_ = c.tid(); return HA + (t_ >> 7) * 8192 + (t_ & 127) * 8; };
            auto reload = [&](auto S0, auto S1) {
                const uint32_t spill = spill_off();
                sfor<decltype(S0)::v * 8, decltype(S1)::v * 8>([&](auto Q) {
                    constexpr int q = decltype(Q)::v;
                    lds64(spill + (q / 8) * 16384 + (q % 8) * 1024, a + q * 2);
                });
            };
            #pragma unroll 1
            for (int idx = 0; idx < 18; idx++) {
                run_step<K_H>(c, hc, a, [&](auto ST) {
                    constexpr int st = decltype(ST)::v;
                    if (idx >= 10) {
                        if constexpr (st < 2) {
                            const uint32_t b_ = v_bid();
                            const uint32_t chunk = (idx == 10) ? 8 : ((b_ + idx - 10) & 7);
                            unsigned char* yp = g_yacc + ((v_epoch() & 1) * 144 + (b_ >> 3) * 9 + chunk) * YT_BYTES + c.tid() * 16;
                            sfor<2 * st, 2 * st + 2>([&](auto Q) {
                                constexpr int q = decltype(Q)::v;
                                asm volatile("red.global.add.noftz.v4.bf16x2 [%0], {%1,%2,%3,%4};" :: "l"(yp + q * 4096),
                                             "r"(pack_bf16(pv[8 * q], pv[8 * q + 1])), "r"(pack_bf16(pv[8 * q + 2], pv[8 * q + 3])),
                                             "r"(pack_bf16(pv[8 * q + 4], pv[8 * q + 5])), "r"(pack_bf16(pv[8 * q + 6], pv[8 * q + 7])) : "memory");
                            });
                            if constexpr (st == 1) event(idx - 7);
                        }
                    } else if (idx >= 1) {
                        const uint32_t bofs = B1S + (idx - 1) * 256 + (c.tid() & 3) * 8;
                        if (idx < 9) {
                            if constexpr (st == 0) {
                                if (idx == OSTEP_AT + 1) {
                                    if ((c.tid() & 31) == 0) asm volatile("cp.async.bulk.wait_group 0;" ::: "memory");
                                    event(2);
                                }
                            }
                            const uint32_t spill = spill_off() + (idx - 1) * 16384;
                            constexpr int b0 = st * 3, b1 = (st == 2 ? 8 : st * 3 + 3);
                            uint32_t w[6];
                            gelun(IC<b0>{}, IC<b1>{}, bofs, w);
                            #pragma unroll
                            for (int b = b0; b < b1; b++) sts64(spill + b * 1024, w[2 * (b - b0)], w[2 * (b - b0) + 1]);
                        } else {
                            if constexpr (st < 2) {
                                const uint32_t tb = tail_off();
                                uint32_t w[8];
                                gelun(IC<st * 4>{}, IC<st * 4 + 4>{}, bofs, w);
                                #pragma unroll
                                for (int i = 0; i < 4; i++) { sts32(tb ^ ((st * 4 + i) << 4), w[2 * i]); sts32((tb ^ ((st * 4 + i) << 4)) + 1024, w[2 * i + 1]); }
                            }
                            if constexpr (st == 1) { fence_async_smem(); named_bar(2 + (c.tid() >> 7), 128); }
                        }
                    } else {
                        if constexpr (st < 2) {
                            constexpr int hf = st;
                            const int t_ = c.tid(), wg = t_ >> 7, t = t_ & 3;
                            float* dst = g_kv + ((v_epoch() & 1) * 8 + (v_bid() & 7)) * 1440;
                            const int d = wg * 32 + ((t_ >> 5) & 3) * 16 + ((t_ >> 2) & 7) + hf * 8;
                            const bool dv = wg ? (d >= 36 && d < 72) : (d < 36);
                            const int e00 = wg * 24 + 2 * t - (d / 18) * 18;
                            float* dp = dst + d * 20 + e00;
                            #pragma unroll
                            for (int i = 0; i < 6; i++) {
                                const int e = e00 + i * 8;
                                const bool blk = wg ? (i >= 1) : (i <= 4);
                                if (dv && blk && e >= 0 && e < 18)
                                    asm volatile("red.global.add.v2.f32 [%0], {%1,%2};" :: "l"(dp + i * 8), "f"(pv[4 * i + 2 * hf]), "f"(pv[4 * i + 2 * hf + 1]) : "memory");
                            }
                            if (dv && t == 0) atomicAdd(dst + d * 20 + 18, wg ? pv[2 * hf] : pv[20 + 2 * hf]);
                            if constexpr (st == 1) event(1);
                        }
                    }
                }, [&](auto ST) {
                    constexpr int st = decltype(ST)::v;
                    if (idx == 8) {
                        reload(IC<3 * st>{}, IC<(st == 2 ? 8 : 3 * st + 3)>{});
                        if constexpr (st == 2) warp_arrive(bar(B_OFREE));
                    }
                });
                reg_copy<32>(pv, hc);
                prof(8 + idx);
                if (idx == OSTEP_AT) {
                    mbar_wait(bar(B_KVB), 0);
                    prof(34);
                    const uint32_t pqo = (c.tid() >> 7) * 576;
                    const int t_ = c.tid(), b_ = v_bid(), t = t_ & 3, l4 = t_ & 28;
                    const uint32_t op = OST + ((t_ >> 5) * 16 + ((t_ >> 2) & 7)) * 144 + t * 4;
                    float r3[2];
                    sfor<0, 2>([&](auto PS) {
                        constexpr int ps = decltype(PS)::v;
                        wg_fence();
                        sfor<0, 5>([&](auto KS) {
                            constexpr int ks = decltype(KS)::v;
                            wg_ss64<(ks ? 1 : 0)>(hc, mkdesc(PQT + ks * 2048, ks == 4 ? 0 : 1024, 128, 0) + pqo, mkdesc(KVB + ps * 8 * 1280 + ks * 256, 128, 1280, 0));
                        });
                        wg_commit();
                        wg_wait<0>();
                        reg_fence<32>(hc);
                        #pragma unroll
                        for (int hf = 0; hf < 2; hf++) {
                            if constexpr (ps == 0) {
                                float r[4];
                                r[0] = rcp(__shfl_sync(0xffffffffu, hc[2 * hf], l4) + 1e-6f);
                                r[1] = rcp(__shfl_sync(0xffffffffu, hc[1 + 2 * hf], l4) + 1e-6f);
                                r[2] = rcp(__shfl_sync(0xffffffffu, hc[2 * hf], l4 + 1) + 1e-6f);
                                r[3] = rcp(__shfl_sync(0xffffffffu, hc[1 + 2 * hf], l4 + 1) + 1e-6f);
                                r3[hf] = r[3];
                                #pragma unroll
                                for (int i = 0; i < 7; i++) {
                                    float rr = (i < 2) ? r[0] : (i == 2) ? (t < 1 ? r[0] : r[1]) : (i == 3) ? r[1] : (i == 4) ? (t < 2 ? r[1] : r[2])
                                             : (i == 5) ? r[2] : (t < 3 ? r[2] : r[3]);
                                    sts32(op + hf * 8 * 144 + i * 16, pack_bf16(hc[4 * i + 4 + 2 * hf] * rr, hc[4 * i + 5 + 2 * hf] * rr));
                                }
                            } else {
                                #pragma unroll
                                for (int i = 0; i < 2; i++)
                                    sts32(op + hf * 8 * 144 + 112 + i * 16, pack_bf16(hc[4 * i + 2 * hf] * r3[hf], hc[4 * i + 1 + 2 * hf] * r3[hf]));
                            }
                        }
                    });
                    fence_async_smem();
                    __syncwarp();
                    if ((t_ & 31) == 0) {
                        asm volatile("cp.async.bulk.tensor.2d.global.shared::cta.bulk_group [%0, {%2, %3}], [%1];"
                                     :: "l"(&tm_ost), "r"(OST + (t_ >> 5) * 2304), "r"((b_ & 7) * 72), "r"((b_ >> 3) * 128 + (t_ >> 5) * 16) : "memory");
                        asm volatile("cp.async.bulk.commit_group;" ::: "memory");
                    }
                }
            }
        }
        if (is_main) warp_arrive(bar(B_O8FREE));
        else {
            mbar_wait(bar(B_INIT), 0);
            #pragma unroll
            for (int i = 0; i < 32; i++) { asm volatile("mov.b32 %0, 0;" : "=f"(hc[i])); asm volatile("mov.b32 %0, 0;" : "=f"(pv[i])); }
        }
        auto add_b2 = [&]() {
            #pragma unroll
            for (int b = 0; b < 8; b++) {
                float2 bv = lds64f(B2S + b * 32 + (c.tid() & 3) * 8);
                pv[4 * b] += bv.x; pv[4 * b + 1] += bv.y; pv[4 * b + 2] += bv.x; pv[4 * b + 3] += bv.y;
            }
        };
        auto load_xy = [&](int ftile, int nrdy, uint32_t* xr, uint32_t* yv) {
            const int mt = ftile / 9, ch = ftile - mt * 9;
            const uint32_t t_ = c.tid();
            const __nv_bfloat16* xp = p.x + (size_t)(mt * 128 + (t_ >> 5) * 16 + ((t_ >> 2) & 7)) * DM + ch * 64 + 2 * (t_ & 3);
            #pragma unroll
            for (int i = 0; i < 8; i++) {
                asm volatile("ld.global.nc.u32 %0, [%1];" : "=r"(xr[2 * i]) : "l"(xp + i * 8));
                asm volatile("ld.global.nc.u32 %0, [%1];" : "=r"(xr[2 * i + 1]) : "l"(xp + 8 * DM + i * 8));
            }
            prof(26);
            smem_wait_gt(EPO + 4, nrdy);
            prof(27);
            const unsigned char* yp = g_yacc + ((v_epoch() & 1) * 144 + ftile) * YT_BYTES + t_ * 16;
            #pragma unroll
            for (int q = 0; q < YT_BYTES / 4096; q++)
                asm volatile("ld.global.cg.v4.u32 {%0,%1,%2,%3}, [%4];" : "=r"(yv[4 * q]), "=r"(yv[4 * q + 1]), "=r"(yv[4 * q + 2]), "=r"(yv[4 * q + 3]) : "l"(yp + q * 4096) : "memory");
        };
        auto gate = [&](const uint32_t* yv) {
            #pragma unroll
            for (int i = 0; i < 16; i++) { pv[2 * i] += bf_lo(yv[i]); pv[2 * i + 1] += bf_hi(yv[i]); }
            #pragma unroll
            for (int i = 0; i < 32; i++) { const float h = 0.5f * pv[i]; pv[i] = fmaf(h, tanh_ap(h), h); }
        };
        auto store_out = [&](int ftile, const uint32_t* xr) {
            const int mt = ftile / 9, ch = ftile - mt * 9;
            const uint32_t t_ = c.tid();
            __nv_bfloat16* op = p.out + (size_t)(mt * 128 + (t_ >> 5) * 16 + ((t_ >> 2) & 7)) * DM + ch * 64 + 2 * (t_ & 3);
            #pragma unroll
            for (int b = 0; b < 8; b++) {
                *reinterpret_cast<uint32_t*>(op + b * 8) =
                    pack_bf16(fmaf(hc[4 * b], pv[4 * b], bf_lo(xr[2 * b])), fmaf(hc[4 * b + 1], pv[4 * b + 1], bf_hi(xr[2 * b])));
                *reinterpret_cast<uint32_t*>(op + 8 * DM + b * 8) =
                    pack_bf16(fmaf(hc[4 * b + 2], pv[4 * b + 2], bf_lo(xr[2 * b + 1])), fmaf(hc[4 * b + 3], pv[4 * b + 3], bf_hi(xr[2 * b + 1])));
            }
        };
        const int njob = is_main ? 1 : 4;
        #pragma unroll 1
        for (int job = 0; job < njob; job++) {
            const uint32_t jpar = job & 1;
            const uint32_t b_ = v_bid();
            const bool mainf = b_ < NMAIN;
            const int ftile = (b_ >> 3) * 9 + (b_ & 7);
            uint32_t oa[128];
            {
                mbar_wait(bar(B_OFULL), jpar);
                const uint32_t lrow = lrow_off();
                sfor<0, 32>([&](auto KS) {
                    constexpr int ks = decltype(KS)::v;
                    ldsm4((lrow ^ ((ks % 4) << 5)) + (ks / 4) * 16384, oa + ks * 4);
                });
                warp_arrive(bar(B_OFREE));
                if (job) c.tph ^= 1;
            }
            c.pf = false;
            run_step<K_H>(c, hc, oa, [&](auto ST) {
                constexpr int st = decltype(ST)::v;
                if (mainf) {
                    if constexpr (st == 0) add_b2();
                    else if constexpr (st == 1) load_xy(ftile, 0, oa, oa + 16);
                    else { prof(28); gate(oa + 16); prof(29); }
                }
                if constexpr (st == 1) mbar_wait(bar(B_O8FULL), jpar);
            }, [](auto) {}, job == njob - 1);
            prof(30);
            if (mainf) {
                store_out(ftile, oa);
            } else {
                warp_arrive(bar(B_O8FREE));
                uint4* sp = reinterpret_cast<uint4*>(g_s8) + ((b_ - NMAIN) * 4 + job) * 1024 + c.tid();
                #pragma unroll
                for (int q = 0; q < 4; q++)
                    sp[q * 256] = make_uint4(pack_bf16(hc[8 * q], hc[8 * q + 1]), pack_bf16(hc[8 * q + 2], hc[8 * q + 3]),
                                             pack_bf16(hc[8 * q + 4], hc[8 * q + 5]), pack_bf16(hc[8 * q + 6], hc[8 * q + 7]));
                prof(8 + job);
            }
        }
        if (!is_main) {
            #pragma unroll 1
            for (int job = 0; job < 4; job++) {
                const int tile = (v_bid() - NMAIN) * 4 + job;
                uint32_t xr[16], yv[YT_BYTES / 1024];
                const uint4* sp = reinterpret_cast<const uint4*>(g_s8) + tile * 1024 + c.tid();
                #pragma unroll
                for (int q = 0; q < 4; q++) {
                    const uint4 u = __ldcg(sp + q * 256);
                    hc[8 * q] = bf_lo(u.x); hc[8 * q + 1] = bf_hi(u.x); hc[8 * q + 2] = bf_lo(u.y); hc[8 * q + 3] = bf_hi(u.y);
                    hc[8 * q + 4] = bf_lo(u.z); hc[8 * q + 5] = bf_hi(u.z); hc[8 * q + 6] = bf_lo(u.w); hc[8 * q + 7] = bf_hi(u.w);
                }
                #pragma unroll
                for (int i = 0; i < 32; i++) pv[i] = 0.f;
                add_b2();
                load_xy(tile * 9 + 8, job, xr, yv);
                gate(yv);
                store_out(tile * 9 + 8, xr);
                prof(12 + job);
            }
        }
        prof(40);
        if (c.tid() == 0) g_epoch[v_bid()] = v_epoch() + 1;
    }
}

typedef CUresult (*EncodeFn)(CUtensorMap*, CUtensorMapDataType, cuuint32_t, void*, const cuuint64_t*, const cuuint64_t*,
                             const cuuint32_t*, const cuuint32_t*, CUtensorMapInterleave, CUtensorMapSwizzle,
                             CUtensorMapL2promotion, CUtensorMapFloatOOBfill);

void make_map(EncodeFn enc, CUtensorMap* tm, const void* base, int rows, int cols, int box_rows, int box_cols = 64, bool swz = true) {
    cuuint64_t gdim[2] = {(cuuint64_t)cols, (cuuint64_t)rows};
    cuuint64_t gstr[1] = {(cuuint64_t)cols * 2};
    cuuint32_t box[2] = {(cuuint32_t)box_cols, (cuuint32_t)box_rows};
    cuuint32_t estr[2] = {1, 1};
    enc(tm, CU_TENSOR_MAP_DATA_TYPE_BFLOAT16, 2, const_cast<void*>(base), gdim, gstr, box, estr, CU_TENSOR_MAP_INTERLEAVE_NONE,
        swz ? CU_TENSOR_MAP_SWIZZLE_128B : CU_TENSOR_MAP_SWIZZLE_NONE, CU_TENSOR_MAP_L2_PROMOTION_L2_128B, CU_TENSOR_MAP_FLOAT_OOB_FILL_NONE);
}

}

extern "C" void kernel_launch(void* const* d_in, const int* in_sizes, int n_in, void* d_out, int out_size) {
    static EncodeFn enc = nullptr;
    static void* o_ptr = nullptr;
    if (!enc) {
        void* fn = nullptr;
        cudaDriverEntryPointQueryResult qr;
        cudaGetDriverEntryPoint("cuTensorMapEncodeTiled", &fn, cudaEnableDefault, &qr);
        enc = (EncodeFn)fn;
        cudaGetSymbolAddress(&o_ptr, g_o);
        cudaFuncSetAttribute(fused_kernel, cudaFuncAttributeMaxDynamicSharedMemorySize, SMEM_BYTES);
    }
    Params p;
    p.x = (const __nv_bfloat16*)d_in[0];
    p.wqkv = (const __nv_bfloat16*)d_in[1];
    p.wo = (const __nv_bfloat16*)d_in[2];
    p.w1 = (const __nv_bfloat16*)d_in[4];
    p.b1 = (const __nv_bfloat16*)d_in[5];
    p.w2 = (const __nv_bfloat16*)d_in[6];
    p.b2 = (const __nv_bfloat16*)d_in[7];
    p.out = (__nv_bfloat16*)d_out;
    CUtensorMap tm_x, tm_w1, tm_w2, tm_wo, tm_o, tm_qkv, tm_qkve, tm_ost;
    make_map(enc, &tm_ost, o_ptr, SEQ, DM, 16, 72, false);
    make_map(enc, &tm_qkv, p.wqkv, DM, 3 * DM, 96);
    make_map(enc, &tm_qkve, p.wqkv, DM, 3 * DM, 96, 8);
    make_map(enc, &tm_x, p.x, SEQ, DM, 128);
    make_map(enc, &tm_w1, p.w1, DM, FF, 192);
    make_map(enc, &tm_w2, p.w2, FF, DM, 192);
    make_map(enc, &tm_wo, p.wo, DM, DM, 192);
    make_map(enc, &tm_o, o_ptr, SEQ, DM, 128);
    fused_kernel<<<NMAIN + NAUX, 384, SMEM_BYTES>>>(tm_x, tm_w1, tm_w2, tm_wo, tm_o, tm_qkv, tm_qkve, tm_ost, p);
}
```

```cpp
#include <cuda_runtime.h>
#include <cuda.h>
#include <cuda_bf16.h>
#include <stdint.h>

#define OSTEP_AT 4
#define KNOB_A 1
#define KNOB_B 0
#define PF1_NS 1500
#define PF2_NS 2000
#define PFIDX 3
#define PF3_NS 800
#define EARLY_REL 0
#define PF0_NS 1200
#define YF32 0

namespace {
constexpr int WAIT_ITERS = 3000000;

constexpr int SEQ = 2048, DM = 576, FF = 4608;
constexpr int NMAIN = 128, NAUX = 4;

constexpr uint32_t SB    = 0x400;
constexpr uint32_t HA    = SB;
constexpr uint32_t XB    = SB + 131072;
constexpr uint32_t RING  = SB + 147456;
constexpr uint32_t SLOT  = 24576;
constexpr uint32_t MISC  = SB + 221184;
constexpr uint32_t BARS  = MISC;
constexpr uint32_t B1S   = MISC + 512;
constexpr uint32_t B2S   = MISC + 2816;
constexpr uint32_t EPO   = MISC + 3072;
constexpr uint32_t EVC   = MISC + 3104;
constexpr uint32_t SMEM_BYTES = 221184 + 3200 + 512;
constexpr uint32_t PKT   = HA + 32768;
constexpr uint32_t VT    = HA + 51200;
constexpr uint32_t OST   = HA + 79872;
constexpr uint32_t PQT   = HA + 98304;
constexpr uint32_t KVB   = HA + 116736;

enum { B_FULL = 0, B_EMPTY = 3, B_XFULL = 6, B_OFULL = 9, B_O8FULL = 10, B_OFREE = 11, B_O8FREE = 12, B_KVB = 13, B_INIT = 14, B_COUNT = 15 };
__device__ __forceinline__ constexpr uint32_t bar(int i) { return BARS + 8u * i; }

constexpr int YT_BYTES = YF32 ? 32768 : 16384;
__device__ __align__(1024) __nv_bfloat16 g_o[SEQ * DM];
__device__ __align__(1024) unsigned char g_yacc[2 * 16 * 9 * YT_BYTES];
__device__ __align__(128) float g_kv[2 * 8 * 72 * 20];
__device__ __align__(128) unsigned int g_s8[16 * 4096];
__device__ __align__(128) unsigned int g_cnt[(8 + 16 + 16 * 9) * 8];
__device__ unsigned int g_epoch[NMAIN + NAUX];
__device__ __forceinline__ unsigned int* cnt_kv(int j) { return g_cnt + j * 8; }
__device__ __forceinline__ unsigned int* cnt_o(int m) { return g_cnt + (8 + m) * 8; }
__device__ __forceinline__ unsigned int* cnt_y(int m, int c) { return g_cnt + (24 + m * 9 + c) * 8; }

__device__ __forceinline__ void mbar_init(uint32_t b, uint32_t cnt) { asm volatile("mbarrier.init.shared::cta.b64 [%0], %1;" :: "r"(b), "r"(cnt)); }
__device__ __forceinline__ void mbar_expect_tx(uint32_t b, uint32_t bytes) { asm volatile("mbarrier.arrive.expect_tx.shared::cta.b64 _, [%0], %1;" :: "r"(b), "r"(bytes) : "memory"); }
__device__ __forceinline__ void mbar_arrive(uint32_t b) { asm volatile("mbarrier.arrive.shared::cta.b64 _, [%0];" :: "r"(b) : "memory"); }
__device__ __forceinline__ void prof(int) {}
__device__ __forceinline__ void mbar_wait(uint32_t b, uint32_t parity) {
    asm volatile("{\n.reg .pred p;\n.reg .u32 c;\nmov.u32 c, 0;\n"
                 "WAIT_LOOP:\nmbarrier.try_wait.parity.shared::cta.b64 p, [%0], %1;\n@p bra WAIT_DONE;\n"
                 "add.u32 c, c, 1;\nsetp.lt.u32 p, c, 4000000;\n@p bra WAIT_LOOP;\ntrap;\nWAIT_DONE:\n}"
                 :: "r"(b), "r"(parity) : "memory");
}
__device__ __forceinline__ void smem_wait_gt(uint32_t addr, uint32_t val) {
    asm volatile("{\n.reg .pred p;\n.reg .u32 c, v;\nmov.u32 c, 0;\n"
                 "SW_LOOP:\nld.acquire.cta.shared.u32 v, [%0];\nsetp.gt.u32 p, v, %1;\n@p bra SW_DONE;\n"
                 "add.u32 c, c, 1;\nsetp.lt.u32 p, c, 100000000;\n@p bra SW_LOOP;\ntrap;\nSW_DONE:\n}"
                 :: "r"(addr), "r"(val) : "memory");
}
__device__ __forceinline__ void tma_2d(uint32_t dst, const CUtensorMap* tm, uint32_t b, int c0, int c1) {
    asm volatile("cp.async.bulk.tensor.2d.shared::cluster.global.mbarrier::complete_tx::bytes [%0], [%1, {%3, %4}], [%2];"
                 :: "r"(dst), "l"(tm), "r"(b), "r"(c0), "r"(c1) : "memory");
}
__device__ __forceinline__ void fence_async_smem() { asm volatile("fence.proxy.async.shared::cta;" ::: "memory"); }
__device__ __forceinline__ void fence_async_all() { asm volatile("fence.proxy.async;" ::: "memory"); }
__device__ __forceinline__ void named_bar(int id, int n) { asm volatile("bar.sync %0, %1;" :: "r"(id), "r"(n) : "memory"); }
__device__ __forceinline__ void wg_fence() { asm volatile("wgmma.fence.sync.aligned;" ::: "memory"); }
__device__ __forceinline__ void wg_commit() { asm volatile("wgmma.commit_group.sync.aligned;" ::: "memory"); }
template<int N> __device__ __forceinline__ void wg_wait() { asm volatile("wgmma.wait_group.sync.aligned %0;" :: "n"(N) : "memory"); }
template<int N> __device__ __forceinline__ void reg_fence(float* d) {
    #pragma unroll
    for (int i = 0; i < N; i++) asm volatile("" : "+f"(d[i]) :: "memory");
}
template<int N> __device__ __forceinline__ void reg_copy(float* d, const float* s) {
    #pragma unroll
    for (int i = 0; i < N; i++) asm volatile("mov.b32 %0, %1;" : "=f"(d[i]) : "f"(s[i]));
}
__device__ __forceinline__ uint32_t pack_bf16(float lo, float hi) { uint32_t r; asm("cvt.rn.bf16x2.f32 %0, %1, %2;" : "=r"(r) : "f"(hi), "f"(lo)); return r; }
__device__ __forceinline__ float bf_lo(uint32_t v) { return __uint_as_float(v << 16); }
__device__ __forceinline__ float bf_hi(uint32_t v) { return __uint_as_float(v & 0xffff0000u); }
__device__ __forceinline__ uint32_t sub_bf16x2(uint32_t a, uint32_t b) { uint32_t r; asm("sub.rn.bf16x2 %0, %1, %2;" : "=r"(r) : "r"(a), "r"(b)); return r; }
__device__ __forceinline__ float ex2(float x) { float r; asm("ex2.approx.ftz.f32 %0, %1;" : "=f"(r) : "f"(x)); return r; }
__device__ __forceinline__ float rcp(float x) { float r; asm("rcp.approx.ftz.f32 %0, %1;" : "=f"(r) : "f"(x)); return r; }
__device__ __forceinline__ float tanh_ap(float x) { float r; asm("tanh.approx.f32 %0, %1;" : "=f"(r) : "f"(x)); return r; }
__device__ __forceinline__ void sts32(uint32_t a, uint32_t v) { asm volatile("st.shared.b32 [%0], %1;" :: "r"(a), "r"(v)); }
__device__ __forceinline__ void sts128(uint32_t a, uint32_t x, uint32_t y, uint32_t z, uint32_t w) { asm volatile("st.shared.v4.b32 [%0], {%1,%2,%3,%4};" :: "r"(a), "r"(x), "r"(y), "r"(z), "r"(w)); }
__device__ __forceinline__ void sts64(uint32_t a, uint32_t x, uint32_t y) { asm volatile("st.shared.v2.b32 [%0], {%1,%2};" :: "r"(a), "r"(x), "r"(y)); }
__device__ __forceinline__ void lds64(uint32_t a, uint32_t* v) { asm volatile("ld.shared.v2.b32 {%0,%1}, [%2];" : "=r"(v[0]), "=r"(v[1]) : "r"(a)); }
__device__ __forceinline__ void lds128(uint32_t a, uint32_t* v) { asm volatile("ld.shared.v4.b32 {%0,%1,%2,%3}, [%4];" : "=r"(v[0]), "=r"(v[1]), "=r"(v[2]), "=r"(v[3]) : "r"(a) : "memory"); }
__device__ __forceinline__ float2 lds64f(uint32_t a) { float2 v; asm("ld.shared.v2.f32 {%0,%1}, [%2];" : "=f"(v.x), "=f"(v.y) : "r"(a)); return v; }
__device__ __forceinline__ void ldsm4(uint32_t a, uint32_t* v) {
    asm volatile("ldmatrix.sync.aligned.m8n8.x4.shared.b16 {%0,%1,%2,%3}, [%4];" : "=r"(v[0]), "=r"(v[1]), "=r"(v[2]), "=r"(v[3]) : "r"(a));
}
__device__ __forceinline__ void mma_ones(float* c, const uint32_t* a) {
    const uint32_t one2 = 0x3F803F80u;
    asm volatile("mma.sync.aligned.m16n8k16.row.col.f32.bf16.bf16.f32 {%0,%1,%2,%3}, {%4,%5,%6,%7}, {%8,%8}, {%0,%1,%2,%3};"
                 : "+f"(c[0]), "+f"(c[1]), "+f"(c[2]), "+f"(c[3]) : "r"(a[0]), "r"(a[1]), "r"(a[2]), "r"(a[3]), "r"(one2));
}
__device__ __forceinline__ void mma_bf16(float* c, const uint32_t* a, uint32_t b0, uint32_t b1) {
    asm volatile("mma.sync.aligned.m16n8k16.row.col.f32.bf16.bf16.f32 {%0,%1,%2,%3}, {%4,%5,%6,%7}, {%8,%9}, {%0,%1,%2,%3};"
                 : "+f"(c[0]), "+f"(c[1]), "+f"(c[2]), "+f"(c[3]) : "r"(a[0]), "r"(a[1]), "r"(a[2]), "r"(a[3]), "r"(b0), "r"(b1));
}
__device__ __forceinline__ unsigned int ld_acquire(const unsigned int* p) { unsigned int v; asm volatile("ld.acquire.gpu.global.u32 %0, [%1];" : "=r"(v) : "l"(p) : "memory"); return v; }
__device__ __forceinline__ void wait_cnt(const unsigned int* p, unsigned int target) {
    for (int i = 0; i < WAIT_ITERS; i++) {
        if ((int)(ld_acquire(p) - target) >= 0) return;
        __nanosleep(40);
    }
    __trap();
}
__device__ __forceinline__ uint32_t v_tid() { uint32_t r; asm volatile("mov.u32 %0, %%tid.x;" : "=r"(r)); return r; }
__device__ __forceinline__ uint32_t v_bid() { uint32_t r; asm volatile("mov.u32 %0, %%ctaid.x;" : "=r"(r)); return r; }
__device__ __forceinline__ uint32_t v_epoch() { uint32_t r; asm volatile("ld.shared.u32 %0, [%1];" : "=r"(r) : "r"(EPO)); return r; }
__device__ __forceinline__ void prefetch_l2(const void* p) { asm volatile("prefetch.global.L2 [%0];" :: "l"(p)); }

__host__ __device__ constexpr uint64_t mkdesc(uint32_t addr, uint32_t lbo, uint32_t sbo, uint32_t swz) {
    return (uint64_t)((addr & 0x3FFFF) >> 4) | ((uint64_t)((lbo >> 4) & 0x3FFF) << 16) | ((uint64_t)((sbo >> 4) & 0x3FFF) << 32) | ((uint64_t)swz << 62);
}

template<int SD> __device__ __forceinline__ void wg_rs64(float* d, const uint32_t* a, uint64_t bd) {
  if constexpr (SD) {
    asm volatile("{\n.reg .pred p;\nsetp.eq.b32 p, 0, 0;\n"
    "wgmma.mma_async.sync.aligned.m64n64k16.f32.bf16.bf16 {%0,%1,%2,%3,%4,%5,%6,%7,%8,%9,%10,%11,%12,%13,%14,%15,%16,%17,%18,%19,%20,%21,%22,%23,%24,%25,%26,%27,%28,%29,%30,%31}, {%32,%33,%34,%35}, %36, p, 1, 1, 1;\n}"
    : "+f"(d[0]),"+f"(d[1]),"+f"(d[2]),"+f"(d[3]),"+f"(d[4]),"+f"(d[5]),"+f"(d[6]),"+f"(d[7]),"+f"(d[8]),"+f"(d[9]),"+f"(d[10]),"+f"(d[11]),"+f"(d[12]),"+f"(d[13]),"+f"(d[14]),"+f"(d[15]),"+f"(d[16]),"+f"(d[17]),"+f"(d[18]),"+f"(d[19]),"+f"(d[20]),"+f"(d[21]),"+f"(d[22]),"+f"(d[23]),"+f"(d[24]),"+f"(d[25]),"+f"(d[26]),"+f"(d[27]),"+f"(d[28]),"+f"(d[29]),"+f"(d[30]),"+f"(d[31])
    : "r"(a[0]),"r"(a[1]),"r"(a[2]),"r"(a[3]), "l"(bd));
  } else {
    asm volatile("{\n.reg .pred p;\nsetp.ne.b32 p, 0, 0;\n"
    "wgmma.mma_async.sync.aligned.m64n64k16.f32.bf16.bf16 {%0,%1,%2,%3,%4,%5,%6,%7,%8,%9,%10,%11,%12,%13,%14,%15,%16,%17,%18,%19,%20,%21,%22,%23,%24,%25,%26,%27,%28,%29,%30,%31}, {%32,%33,%34,%35}, %36, p, 1, 1, 1;\n}"
    : "+f"(d[0]),"+f"(d[1]),"+f"(d[2]),"+f"(d[3]),"+f"(d[4]),"+f"(d[5]),"+f"(d[6]),"+f"(d[7]),"+f"(d[8]),"+f"(d[9]),"+f"(d[10]),"+f"(d[11]),"+f"(d[12]),"+f"(d[13]),"+f"(d[14]),"+f"(d[15]),"+f"(d[16]),"+f"(d[17]),"+f"(d[18]),"+f"(d[19]),"+f"(d[20]),"+f"(d[21]),"+f"(d[22]),"+f"(d[23]),"+f"(d[24]),"+f"(d[25]),"+f"(d[26]),"+f"(d[27]),"+f"(d[28]),"+f"(d[29]),"+f"(d[30]),"+f"(d[31])
    : "r"(a[0]),"r"(a[1]),"r"(a[2]),"r"(a[3]), "l"(bd));
  }
}
template<int SD> __device__ __forceinline__ void wg_ss64(float* d, uint64_t ad, uint64_t bd) {
  if constexpr (SD) {
    asm volatile("{\n.reg .pred p;\nsetp.eq.b32 p, 0, 0;\n"
    "wgmma.mma_async.sync.aligned.m64n64k16.f32.bf16.bf16 {%0,%1,%2,%3,%4,%5,%6,%7,%8,%9,%10,%11,%12,%13,%14,%15,%16,%17,%18,%19,%20,%21,%22,%23,%24,%25,%26,%27,%28,%29,%30,%31}, %32, %33, p, 1, 1, 0, 1;\n}"
    : "+f"(d[0]),"+f"(d[1]),"+f"(d[2]),"+f"(d[3]),"+f"(d[4]),"+f"(d[5]),"+f"(d[6]),"+f"(d[7]),"+f"(d[8]),"+f"(d[9]),"+f"(d[10]),"+f"(d[11]),"+f"(d[12]),"+f"(d[13]),"+f"(d[14]),"+f"(d[15]),"+f"(d[16]),"+f"(d[17]),"+f"(d[18]),"+f"(d[19]),"+f"(d[20]),"+f"(d[21]),"+f"(d[22]),"+f"(d[23]),"+f"(d[24]),"+f"(d[25]),"+f"(d[26]),"+f"(d[27]),"+f"(d[28]),"+f"(d[29]),"+f"(d[30]),"+f"(d[31])
    : "l"(ad), "l"(bd));
  } else {
    asm volatile("{\n.reg .pred p;\nsetp.ne.b32 p, 0, 0;\n"
    "wgmma.mma_async.sync.aligned.m64n64k16.f32.bf16.bf16 {%0,%1,%2,%3,%4,%5,%6,%7,%8,%9,%10,%11,%12,%13,%14,%15,%16,%17,%18,%19,%20,%21,%22,%23,%24,%25,%26,%27,%28,%29,%30,%31}, %32, %33, p, 1, 1, 0, 1;\n}"
    : "+f"(d[0]),"+f"(d[1]),"+f"(d[2]),"+f"(d[3]),"+f"(d[4]),"+f"(d[5]),"+f"(d[6]),"+f"(d[7]),"+f"(d[8]),"+f"(d[9]),"+f"(d[10]),"+f"(d[11]),"+f"(d[12]),"+f"(d[13]),"+f"(d[14]),"+f"(d[15]),"+f"(d[16]),"+f"(d[17]),"+f"(d[18]),"+f"(d[19]),"+f"(d[20]),"+f"(d[21]),"+f"(d[22]),"+f"(d[23]),"+f"(d[24]),"+f"(d[25]),"+f"(d[26]),"+f"(d[27]),"+f"(d[28]),"+f"(d[29]),"+f"(d[30]),"+f"(d[31])
    : "l"(ad), "l"(bd));
  }
}
template<int SD> __device__ __forceinline__ void wg_rs72(float* d, const uint32_t* a, uint64_t bd) {
  if constexpr (SD) {
    asm volatile("{\n.reg .pred p;\nsetp.eq.b32 p, 0, 0;\n"
    "wgmma.mma_async.sync.aligned.m64n72k16.f32.bf16.bf16 {%0,%1,%2,%3,%4,%5,%6,%7,%8,%9,%10,%11,%12,%13,%14,%15,%16,%17,%18,%19,%20,%21,%22,%23,%24,%25,%26,%27,%28,%29,%30,%31,%32,%33,%34,%35}, {%36,%37,%38,%39}, %40, p, 1, 1, 1;\n}"
    : "+f"(d[0]),"+f"(d[1]),"+f"(d[2]),"+f"(d[3]),"+f"(d[4]),"+f"(d[5]),"+f"(d[6]),"+f"(d[7]),"+f"(d[8]),"+f"(d[9]),"+f"(d[10]),"+f"(d[11]),"+f"(d[12]),"+f"(d[13]),"+f"(d[14]),"+f"(d[15]),"+f"(d[16]),"+f"(d[17]),"+f"(d[18]),"+f"(d[19]),"+f"(d[20]),"+f"(d[21]),"+f"(d[22]),"+f"(d[23]),"+f"(d[24]),"+f"(d[25]),"+f"(d[26]),"+f"(d[27]),"+f"(d[28]),"+f"(d[29]),"+f"(d[30]),"+f"(d[31]),"+f"(d[32]),"+f"(d[33]),"+f"(d[34]),"+f"(d[35])
    : "r"(a[0]),"r"(a[1]),"r"(a[2]),"r"(a[3]), "l"(bd));
  } else {
    asm volatile("{\n.reg .pred p;\nsetp.ne.b32 p, 0, 0;\n"
    "wgmma.mma_async.sync.aligned.m64n72k16.f32.bf16.bf16 {%0,%1,%2,%3,%4,%5,%6,%7,%8,%9,%10,%11,%12,%13,%14,%15,%16,%17,%18,%19,%20,%21,%22,%23,%24,%25,%26,%27,%28,%29,%30,%31,%32,%33,%34,%35}, {%36,%37,%38,%39}, %40, p, 1, 1, 1;\n}"
    : "+f"(d[0]),"+f"(d[1]),"+f"(d[2]),"+f"(d[3]),"+f"(d[4]),"+f"(d[5]),"+f"(d[6]),"+f"(d[7]),"+f"(d[8]),"+f"(d[9]),"+f"(d[10]),"+f"(d[11]),"+f"(d[12]),"+f"(d[13]),"+f"(d[14]),"+f"(d[15]),"+f"(d[16]),"+f"(d[17]),"+f"(d[18]),"+f"(d[19]),"+f"(d[20]),"+f"(d[21]),"+f"(d[22]),"+f"(d[23]),"+f"(d[24]),"+f"(d[25]),"+f"(d[26]),"+f"(d[27]),"+f"(d[28]),"+f"(d[29]),"+f"(d[30]),"+f"(d[31]),"+f"(d[32]),"+f"(d[33]),"+f"(d[34]),"+f"(d[35])
    : "r"(a[0]),"r"(a[1]),"r"(a[2]),"r"(a[3]), "l"(bd));
  }
}
template<int SD> __device__ __forceinline__ void wg_ss72(float* d, uint64_t ad, uint64_t bd) {
  if constexpr (SD) {
    asm volatile("{\n.reg .pred p;\nsetp.eq.b32 p, 0, 0;\n"
    "wgmma.mma_async.sync.aligned.m64n72k16.f32.bf16.bf16 {%0,%1,%2,%3,%4,%5,%6,%7,%8,%9,%10,%11,%12,%13,%14,%15,%16,%17,%18,%19,%20,%21,%22,%23,%24,%25,%26,%27,%28,%29,%30,%31,%32,%33,%34,%35}, %36, %37, p, 1, 1, 0, 1;\n}"
    : "+f"(d[0]),"+f"(d[1]),"+f"(d[2]),"+f"(d[3]),"+f"(d[4]),"+f"(d[5]),"+f"(d[6]),"+f"(d[7]),"+f"(d[8]),"+f"(d[9]),"+f"(d[10]),"+f"(d[11]),"+f"(d[12]),"+f"(d[13]),"+f"(d[14]),"+f"(d[15]),"+f"(d[16]),"+f"(d[17]),"+f"(d[18]),"+f"(d[19]),"+f"(d[20]),"+f"(d[21]),"+f"(d[22]),"+f"(d[23]),"+f"(d[24]),"+f"(d[25]),"+f"(d[26]),"+f"(d[27]),"+f"(d[28]),"+f"(d[29]),"+f"(d[30]),"+f"(d[31]),"+f"(d[32]),"+f"(d[33]),"+f"(d[34]),"+f"(d[35])
    : "l"(ad), "l"(bd));
  } else {
    asm volatile("{\n.reg .pred p;\nsetp.ne.b32 p, 0, 0;\n"
    "wgmma.mma_async.sync.aligned.m64n72k16.f32.bf16.bf16 {%0,%1,%2,%3,%4,%5,%6,%7,%8,%9,%10,%11,%12,%13,%14,%15,%16,%17,%18,%19,%20,%21,%22,%23,%24,%25,%26,%27,%28,%29,%30,%31,%32,%33,%34,%35}, %36, %37, p, 1, 1, 0, 1;\n}"
    : "+f"(d[0]),"+f"(d[1]),"+f"(d[2]),"+f"(d[3]),"+f"(d[4]),"+f"(d[5]),"+f"(d[6]),"+f"(d[7]),"+f"(d[8]),"+f"(d[9]),"+f"(d[10]),"+f"(d[11]),"+f"(d[12]),"+f"(d[13]),"+f"(d[14]),"+f"(d[15]),"+f"(d[16]),"+f"(d[17]),"+f"(d[18]),"+f"(d[19]),"+f"(d[20]),"+f"(d[21]),"+f"(d[22]),"+f"(d[23]),"+f"(d[24]),"+f"(d[25]),"+f"(d[26]),"+f"(d[27]),"+f"(d[28]),"+f"(d[29]),"+f"(d[30]),"+f"(d[31]),"+f"(d[32]),"+f"(d[33]),"+f"(d[34]),"+f"(d[35])
    : "l"(ad), "l"(bd));
  }
}
template<int SD> __device__ __forceinline__ void wg_tt64(float* d, uint64_t ad, uint64_t bd) {
  if constexpr (SD) {
    asm volatile("{\n.reg .pred p;\nsetp.eq.b32 p, 0, 0;\n"
    "wgmma.mma_async.sync.aligned.m64n64k16.f32.bf16.bf16 {%0,%1,%2,%3,%4,%5,%6,%7,%8,%9,%10,%11,%12,%13,%14,%15,%16,%17,%18,%19,%20,%21,%22,%23,%24,%25,%26,%27,%28,%29,%30,%31}, %32, %33, p, 1, 1, 1, 1;\n}"
    : "+f"(d[0]),"+f"(d[1]),"+f"(d[2]),"+f"(d[3]),"+f"(d[4]),"+f"(d[5]),"+f"(d[6]),"+f"(d[7]),"+f"(d[8]),"+f"(d[9]),"+f"(d[10]),"+f"(d[11]),"+f"(d[12]),"+f"(d[13]),"+f"(d[14]),"+f"(d[15]),"+f"(d[16]),"+f"(d[17]),"+f"(d[18]),"+f"(d[19]),"+f"(d[20]),"+f"(d[21]),"+f"(d[22]),"+f"(d[23]),"+f"(d[24]),"+f"(d[25]),"+f"(d[26]),"+f"(d[27]),"+f"(d[28]),"+f"(d[29]),"+f"(d[30]),"+f"(d[31])
    : "l"(ad), "l"(bd));
  } else {
    asm volatile("{\n.reg .pred p;\nsetp.ne.b32 p, 0, 0;\n"
    "wgmma.mma_async.sync.aligned.m64n64k16.f32.bf16.bf16 {%0,%1,%2,%3,%4,%5,%6,%7,%8,%9,%10,%11,%12,%13,%14,%15,%16,%17,%18,%19,%20,%21,%22,%23,%24,%25,%26,%27,%28,%29,%30,%31}, %32, %33, p, 1, 1, 1, 1;\n}"
    : "+f"(d[0]),"+f"(d[1]),"+f"(d[2]),"+f"(d[3]),"+f"(d[4]),"+f"(d[5]),"+f"(d[6]),"+f"(d[7]),"+f"(d[8]),"+f"(d[9]),"+f"(d[10]),"+f"(d[11]),"+f"(d[12]),"+f"(d[13]),"+f"(d[14]),"+f"(d[15]),"+f"(d[16]),"+f"(d[17]),"+f"(d[18]),"+f"(d[19]),"+f"(d[20]),"+f"(d[21]),"+f"(d[22]),"+f"(d[23]),"+f"(d[24]),"+f"(d[25]),"+f"(d[26]),"+f"(d[27]),"+f"(d[28]),"+f"(d[29]),"+f"(d[30]),"+f"(d[31])
    : "l"(ad), "l"(bd));
  }
}

template<int V> struct IC { static constexpr int v = V; };
template<int I, int N, class F> __device__ __forceinline__ void sfor(F&& f) {
    if constexpr (I < N) { f(IC<I>{}); sfor<I + 1, N>(f); }
}

enum { K_QKV = 0, K_H = 1 };

struct Ctx {
    uint32_t tph;
    uint32_t tid_;
    bool pf = false;
    __device__ __forceinline__ uint32_t tid() const { uint32_t r; asm volatile("mov.u32 %0, %1;" : "=r"(r) : "r"(tid_)); return r; }
};
__device__ __forceinline__ void release_slot(const Ctx& c, int slot) { if ((c.tid() & 31) == 0) mbar_arrive(bar(B_EMPTY + slot)); }

__device__ __forceinline__ void turn_wait(const Ctx& c) { asm volatile("bar.sync %0, 256;" :: "r"(4 + (c.tid() >> 7)) : "memory"); }
__device__ __forceinline__ void turn_pass(const Ctx& c) { asm volatile("bar.arrive %0, 256;" :: "r"(5 - (c.tid() >> 7)) : "memory"); }

template<int KIND, class PART, class POST>
__device__ __forceinline__ void run_step(Ctx& c, float* acc, const uint32_t* a, PART&& part, POST&& post, bool last = false) {
    constexpr int NST = (KIND == K_QKV) ? 6 : 3;
    constexpr int KPS = 36 / NST;
    sfor<0, NST>([&](auto ST) {
        constexpr int st = decltype(ST)::v;
        constexpr int slot = st % 3;
        mbar_wait(bar(B_FULL + slot), c.tph);
        uint32_t wgo = 0;
        if constexpr (st == NST - 1) wgo = (c.tid() >> 7) * 512;
        if (KIND == K_H && c.pf) prof(44 + st * 5);
        turn_wait(c);
        if (KIND == K_H && c.pf) prof(45 + st * 5);
        wg_fence();
        sfor<0, KPS>([&](auto KK) {
            constexpr int kk = decltype(KK)::v;
            constexpr int ks = st * KPS + kk;
            constexpr int SD = ks ? 1 : 0;
            if constexpr (KIND == K_QKV) {
                constexpr uint64_t bd = mkdesc(RING + slot * SLOT + kk * 2048, 12288, 1024, 1);
                if constexpr (ks < 32) wg_rs72<SD>(acc, a + ks * 4, bd);
                else wg_ss72<SD>(acc, mkdesc(XB + (ks - 32) * 32, 16, 1024, 1) + wgo, bd);
            } else {
                constexpr uint64_t bd = mkdesc(RING + slot * SLOT + kk * 2048, 16, 1024, 1);
                if constexpr (ks < 32) wg_rs64<SD>(acc, a + ks * 4, bd);
                else wg_ss64<SD>(acc, mkdesc(XB + (ks - 32) * 32, 16, 1024, 1) + wgo, bd);
            }
        });
        wg_commit();
        if (st < NST - 1 || !last || c.tid() < 128) turn_pass(c);
        if (KIND == K_H && c.pf) prof(46 + st * 5);
        part(ST);
        if (KIND == K_H && c.pf) prof(47 + st * 5);
        wg_wait<0>();
        if (KIND == K_H && c.pf) prof(48 + st * 5);
        release_slot(c, slot);
        if constexpr (slot == 2) c.tph ^= 1;
        post(ST);
    });
    if constexpr (KIND == K_QKV) reg_fence<36>(acc); else reg_fence<32>(acc);
}

__device__ __forceinline__ float phi(float t) {
    float e = ex2(t * 1.4426950408889634f);
    return (t > 0.f ? t + 1.0f : e) + 1e-6f;
}
__device__ __forceinline__ float gelu_h(float hx) {
    float u = hx * fmaf(hx * hx, 0.2854192650f, 1.5957691216f);
    return fmaf(hx, tanh_ap(u), hx);
}

struct Params {
    const __nv_bfloat16* x;
    const __nv_bfloat16* wqkv;
    const __nv_bfloat16* wo;
    const __nv_bfloat16* w1;
    const __nv_bfloat16* b1;
    const __nv_bfloat16* w2;
    const __nv_bfloat16* b2;
    __nv_bfloat16* out;
};

__global__ void __launch_bounds__(384, 1)
fused_kernel(const __grid_constant__ CUtensorMap tm_x, const __grid_constant__ CUtensorMap tm_w1,
             const __grid_constant__ CUtensorMap tm_w2, const __grid_constant__ CUtensorMap tm_wo,
             const __grid_constant__ CUtensorMap tm_o, const __grid_constant__ CUtensorMap tm_qkv,
             const __grid_constant__ CUtensorMap tm_qkve, const __grid_constant__ CUtensorMap tm_ost, const Params p) {
    extern __shared__ __align__(1024) unsigned char smem_raw[];
    const int tid = threadIdx.x;
    const int bid = blockIdx.x;
    const bool is_main = bid < NMAIN;
    const int j = bid & 7;
    const int m = bid >> 3;

    if (tid == 0) {
        if ((uint32_t)__cvta_generic_to_shared(smem_raw) != SB) __trap();
        for (int i = 0; i < 3; i++) {
            mbar_init(bar(B_FULL + i), 1); mbar_init(bar(B_EMPTY + i), 8);
            mbar_init(bar(B_XFULL + i), 1);
        }
        mbar_init(bar(B_KVB), 2); mbar_init(bar(B_INIT), 1);
        mbar_init(bar(B_OFULL), 1); mbar_init(bar(B_O8FULL), 1); mbar_init(bar(B_OFREE), 8); mbar_init(bar(B_O8FREE), 8);
        asm volatile("fence.mbarrier_init.release.cluster;" ::: "memory");
    }
    if (tid == 256) { asm volatile("prefetch.tensormap [%0];" :: "l"(&tm_x) : "memory"); asm volatile("prefetch.tensormap [%0];" :: "l"(&tm_qkv) : "memory"); asm volatile("prefetch.tensormap [%0];" :: "l"(&tm_qkve) : "memory"); }
    if (tid >= 40 && tid < 48) sts32(EVC + (tid - 40) * 4, 0);
    if (tid == 48) sts32(EPO + 4, 0);
    __syncthreads();

    if (tid >= 256) {
        asm volatile("setmaxnreg.dec.sync.aligned.u32 24;");
        const int hw = (tid >> 5) - 8, lane = tid & 31;
        uint32_t epoch = 0;
        if (hw > 0) {
            epoch = g_epoch[bid];
            if (hw == 3) {
                if (lane == 0) sts32(EPO, epoch);
                if (is_main) {
                    #pragma unroll 1
                    for (int i = lane; i < 288; i += 32) {
                        uint32_t v = *reinterpret_cast<const uint32_t*>(p.b1 + j * 576 + 2 * i);
                        sts32(B1S + 8 * i, __float_as_uint(0.5f * bf_lo(v))); sts32(B1S + 8 * i + 4, __float_as_uint(0.5f * bf_hi(v)));
                    }
                }
                uint32_t v = *reinterpret_cast<const uint32_t*>(p.b2 + (is_main ? j : 8) * 64 + 2 * lane);
                sts32(B2S + 8 * lane, v << 16); sts32(B2S + 8 * lane + 4, v & 0xffff0000u);
                __syncwarp();
                if (lane == 0) mbar_arrive(bar(B_INIT));
            }
        }
        const uint32_t par = epoch & 1;
        if (hw == 0) {
            if (lane == 0) {
                uint32_t n = 0;
                if (is_main) {
                    #pragma unroll 1
                    for (int kb = 0; kb < 9; kb++) {
                        if (kb % 3 == 0) mbar_expect_tx(bar(B_XFULL + kb / 3), 49152);
                        tma_2d(HA + kb * 16384, &tm_x, bar(B_XFULL + kb / 3), kb * 64, m * 128);
                    }
                    #pragma unroll 1
                    for (int u = 0; u < 18; u++) {
                        const int st = u % 3, step = u / 6;
                        const int col = ((step == 2) ? 0 : (step + 1) * 576) + j * 72, row = (u % 6) * 96;
                        mbar_wait(bar(B_EMPTY + st), (n & 1) ^ 1);
                        mbar_expect_tx(bar(B_FULL + st), 96 * 144);
                        tma_2d(RING + st * SLOT, &tm_qkv, bar(B_FULL + st), col, row);
                        tma_2d(RING + st * SLOT + 12288, &tm_qkve, bar(B_FULL + st), col + 64, row);
                        if (st == 2) n++;
                    }
                }
                const int nsteps = is_main ? 19 : 1;
                #pragma unroll 1
                for (int s = 0; s < nsteps; s++, n++) {
                    const CUtensorMap* tm; int col, row;
                    if (!is_main) { tm = &tm_wo; col = 512; row = 0; }
                    else if (s < 9) { tm = &tm_w1; col = j * 576 + s * 64; row = 0; }
                    else if (s < 18) { tm = &tm_w2; col = (s == 9) ? 512 : (((j + s - 9) & 7) * 64); row = j * 576; }
                    else { tm = &tm_wo; col = j * 64; row = 0; }
                    #pragma unroll 1
                    for (int st = 0; st < 3; st++) {
                        mbar_wait(bar(B_EMPTY + st), (n & 1) ^ 1);
                        mbar_expect_tx(bar(B_FULL + st), SLOT);
                        tma_2d(RING + st * SLOT, tm, bar(B_FULL + st), col, row + st * 192);
                    }
                }
            }
        } else {
            if (is_main) {
                const int t = tid - 288;
                __nanosleep(PF0_NS);
                #pragma unroll 1
                for (int i = t; i < 36 * 6; i += 96) {
                    int r = i / 6, q = i - r * 6;
                    prefetch_l2(reinterpret_cast<const char*>(p.wqkv) + (36 * m + r) * 3456 + (q >> 1) * 1152 + j * 144 + (q & 1) * 128);
                }
                __nanosleep(PF1_NS);
                #pragma unroll 1
                for (int i = t; i < 36 * 9; i += 96) {
                    int r = i / 9, q = i - r * 9;
                    prefetch_l2(reinterpret_cast<const char*>(p.w1) + (36 * m + r) * 9216 + j * 1152 + q * 128);
                    __nanosleep(PF3_NS);
                }
                __nanosleep(PF2_NS);
                #pragma unroll 1
                for (int i = t; i < 36 * 9; i += 96)
                    prefetch_l2(reinterpret_cast<const char*>(p.w2) + (576 * j + 36 * m) * 1152 + i * 128);
                if (t < 41 && (bid * 41 + t) < 5184) prefetch_l2(reinterpret_cast<const char*>(p.wo) + (bid * 41 + t) * 128);
                if (hw != 2) {
                    if (lane == 0) wait_cnt(cnt_kv(j), (epoch + 1) * 16);
                    __syncwarp();
                    const float4* kv = reinterpret_cast<const float4*>(g_kv + (par * 8 + j) * 1440);
                    #pragma unroll 2
                    for (int i = lane + (hw == 1 ? 0 : 32); i < 360; i += 64) {
                        const float4 v = __ldcg(kv + i);
                        const int d = i / 5, e = (i - d * 5) * 4, h = d / 18;
                        const uint32_t base = KVB + (d >> 3) * 128 + (d & 7) * 16;
                        const int n0 = 8 + h * 18 + e;
                        sts32(base + (n0 >> 3) * 1280 + (n0 & 7) * 2, pack_bf16(v.x, v.y));
                        if (e < 16) sts32(base + ((n0 + 2) >> 3) * 1280 + ((n0 + 2) & 7) * 2, pack_bf16(v.z, v.w));
                        else asm volatile("st.shared.u16 [%0], %1;" :: "r"(base + h * 2), "h"((unsigned short)pack_bf16(v.z, 0.f)) : "memory");
                    }
                    fence_async_smem();
                    __syncwarp();
                    if (lane == 0) mbar_arrive(bar(B_KVB));
                }
            }
            if (hw == 1) {
                if (lane == 0) {
                    const int nit = is_main ? 1 : 4;
                    for (int it = 0; it < nit; it++) {
                        const int mt = is_main ? m : ((bid - NMAIN) * 4 + it);
                        const bool wf = is_main || it > 0;
                        const uint32_t fp = is_main ? 0 : ((it - 1) & 1);
                        wait_cnt(cnt_o(mt), (epoch + 1) * 8);
                        fence_async_all();
                        if (wf) mbar_wait(bar(B_OFREE), fp);
                        mbar_expect_tx(bar(B_OFULL), 131072);
                        #pragma unroll 1
                        for (int kb = 0; kb < 8; kb++) tma_2d(HA + kb * 16384, &tm_o, bar(B_OFULL), kb * 64, mt * 128);
                        if (wf) mbar_wait(bar(B_O8FREE), fp);
                        mbar_expect_tx(bar(B_O8FULL), 16384);
                        tma_2d(XB, &tm_o, bar(B_O8FULL), 512, mt * 128);
                    }
                    if (is_main) { wait_cnt(cnt_y(m, j), (epoch + 1) * 7); asm volatile("st.release.cta.shared.u32 [%0], %1;" :: "r"(EPO + 4), "r"(1) : "memory"); }
                }
            } else if (hw == 2) {
                if (!is_main) {
                    if (lane == 0) {
                        #pragma unroll 1
                        for (int it = 0; it < 4; it++) {
                            wait_cnt(cnt_y((bid - NMAIN) * 4 + it, 8), (epoch + 1) * 8);
                            asm volatile("st.release.cta.shared.u32 [%0], %1;" :: "r"(EPO + 4), "r"(it + 1) : "memory");
                        }
                    }
                } else {
                    #pragma unroll 1
                    for (int e = 0; e < 10; e++) {
                        int spin = 0;
                        while (true) {
                            uint32_t v;
                            asm volatile("ld.acquire.cta.shared.u32 %0, [%1];" : "=r"(v) : "r"(EVC + (lane & 7) * 4) : "memory");
                            if (__all_sync(0xffffffffu, v > (uint32_t)e)) break;
                            if (++spin > 20000000) __trap();
                            __nanosleep(20);
                        }
                        if (lane == 0) {
                            unsigned int* cp = (e == 0) ? cnt_kv(j) : (e == 1) ? cnt_o(m) : cnt_y(m, e == 2 ? 8 : ((j + e - 2) & 7));
                            if (e == 1) fence_async_all();
                            __threadfence();
                            asm volatile("red.relaxed.gpu.global.add.u32 [%0], 1;" :: "l"(cp) : "memory");
                        }
                        __syncwarp();
                    }
                }
            } else {
                {
                    const int t0 = is_main ? (m * 9 + j) : ((bid - NMAIN) * 4 * 9 + 8);
                    const int nt = is_main ? 1 : 4;
                    for (int t = 0; t < nt; t++) {
                        uint4* z = reinterpret_cast<uint4*>(g_yacc + (size_t)((par ^ 1) * 144 + t0 + t * 9) * YT_BYTES);
                        for (int i = lane; i < YT_BYTES / 16; i += 32) z[i] = make_uint4(0, 0, 0, 0);
                    }
                    if (is_main && m == 0) {
                        float* z = g_kv + ((par ^ 1) * 8 + j) * 1440;
                        for (int i = lane; i < 1440; i += 32) z[i] = 0.f;
                    }
                }
            }
        }
    } else {
        asm volatile("setmaxnreg.inc.sync.aligned.u32 240;");
        prof(0);
        Ctx c; c.tph = 0; c.tid_ = v_tid();
        float hc[32], pv[36];
        if (tid >> 7) turn_pass(c);
        auto event = [&](uint32_t ev) {
            __syncwarp();
            if (((c.tid() & 31) == 0)) asm volatile("st.release.cta.shared.u32 [%0], %1;" :: "r"(EVC + (c.tid() >> 3)), "r"(ev) : "memory");
        };
        auto warp_arrive = [&](uint32_t b) { __syncwarp(); if (((c.tid() & 31) == 0)) mbar_arrive(b); };

        auto lrow_off = [&]() { uint32_t t_ = c.tid(); return HA + ((t_ >> 5) * 16 + (t_ & 15)) * 128 + ((((t_ >> 4) & 1) ^ (t_ & 7)) << 4); };
        auto tail_off = [&]() { uint32_t t_ = c.tid(), g = (t_ >> 2) & 7; return XB + ((t_ >> 5) * 16 + g) * 128 + (g << 4) + (t_ & 3) * 4; };
        if (is_main) {
            uint32_t a[128];
            float rs0, rs1;
            {
                uint32_t tl[16];
                const uint32_t lrow = lrow_off();
                float cs[4][4], sq[8];
                #pragma unroll
                for (int i = 0; i < 4; i++) {
                    #pragma unroll
                    for (int k = 0; k < 4; k++) { cs[i][k] = 0.f; sq[k] = 0.f; sq[k + 4] = 0.f; }
                }
                uint32_t s00 = 0, s11 = 0;
                auto frag = [&](auto KS) -> uint32_t* { constexpr int ks = decltype(KS)::v; return (ks < 32) ? (a + (ks & 31) * 4) : (tl + (ks & 3) * 4); };
                auto sqacc = [&](auto KS) {
                    const uint32_t* f = frag(KS);
                    #pragma unroll
                    for (int r = 0; r < 4; r++) {
                        const uint32_t w = sub_bf16x2(f[r], (r & 1) ? s11 : s00);
                        const float lo = bf_lo(w), hi = bf_hi(w);
                        sq[r] = fmaf(lo, lo, sq[r]); sq[r + 4] = fmaf(hi, hi, sq[r + 4]);
                    }
                };
                sfor<0, 3>([&](auto G) {
                    constexpr int g = decltype(G)::v;
                    mbar_wait(bar(B_XFULL + g), 0);
                    prof(37 + g);
                    sfor<12 * g, 12 * g + 12>([&](auto KS) {
                        constexpr int ks = decltype(KS)::v;
                        ldsm4((lrow ^ ((ks % 4) << 5)) + (ks / 4) * 16384, frag(KS));
                    });
                    sfor<12 * g, 12 * g + 12>([&](auto KS) { mma_ones(cs[decltype(KS)::v & 3], frag(KS)); });
                    if constexpr (g == 0) {
                        const float t0 = (cs[0][0] + cs[1][0] + cs[2][0] + cs[3][0]) * (1.0f / 192.0f), t1 = (cs[0][2] + cs[1][2] + cs[2][2] + cs[3][2]) * (1.0f / 192.0f);
                        s00 = pack_bf16(t0, t0); s11 = pack_bf16(t1, t1);
                    }
                    sfor<12 * g, 12 * g + 12>(sqacc);
                });
                prof(2);
                const float mean0 = (cs[0][0] + cs[1][0] + cs[2][0] + cs[3][0]) * (1.0f / 576.0f), mean1 = (cs[0][2] + cs[1][2] + cs[2][2] + cs[3][2]) * (1.0f / 576.0f);
                const uint32_t m00 = pack_bf16(mean0, mean0), m11 = pack_bf16(mean1, mean1);
                const uint32_t tb = tail_off();
                #pragma unroll
                for (int i = 0; i < 16; i++) sts32((tb ^ ((i >> 1) << 4)) + (i & 1) * 1024, sub_bf16x2(tl[i], (i & 1) ? m11 : m00));
                fence_async_smem();
                #pragma unroll
                for (int i = 0; i < 128; i++) a[i] = sub_bf16x2(a[i], (i & 1) ? m11 : m00);
                {
                    rs0 = (sq[0] + sq[2]) + (sq[4] + sq[6]); rs1 = (sq[1] + sq[3]) + (sq[5] + sq[7]);
                    rs0 += __shfl_xor_sync(0xffffffffu, rs0, 1); rs1 += __shfl_xor_sync(0xffffffffu, rs1, 1);
                    rs0 += __shfl_xor_sync(0xffffffffu, rs0, 2); rs1 += __shfl_xor_sync(0xffffffffu, rs1, 2);
                    const float d0 = mean0 - bf_lo(s00), d1 = mean1 - bf_lo(s11);
                    rs0 = rsqrtf(fmaxf(fmaf(rs0, 1.0f / 576.0f, -d0 * d0), 0.f) + 1e-5f);
                    rs1 = rsqrtf(fmaxf(fmaf(rs1, 1.0f / 576.0f, -d1 * d1), 0.f) + 1e-5f);
                }
                named_bar(1, 256);
            }
            prof(3);
            auto cm_off = [&]() { uint32_t t_ = c.tid(); return (t_ >> 5) * 256 + (t_ & 31) * 4; };
            {
                float qc[36];
                #pragma unroll
                for (int i = 0; i < 36; i++) { qc[i] = 0.f; pv[i] = 0.f; }
                #pragma unroll 1
                for (int s = 0; s < 3; s++) {
                    c.pf = (s == 0);
                    run_step<K_QKV>(c, qc, a, [&](auto ST) {
                        constexpr int st = decltype(ST)::v;
                        if (s > 0) {
                            const uint32_t cm = cm_off();
                            sfor<0, 9>([&](auto B) {
                                constexpr int b = decltype(B)::v;
                                if constexpr ((b * 6) / 9 == st) {
                                    const float v0 = pv[4 * b] * rs0, v1 = pv[4 * b + 1] * rs0, v2 = pv[4 * b + 2] * rs1, v3 = pv[4 * b + 3] * rs1;
                                    if (s == 1) {
                                        sts32(PKT + b * 2048 + cm, pack_bf16(phi(v0), phi(v1)));
                                        sts32(PKT + b * 2048 + cm + 128, pack_bf16(phi(v2), phi(v3)));
                                    } else {
                                        const uint32_t w0 = pack_bf16(v0, v1), w1 = pack_bf16(v2, v3);
                                        if constexpr (b <= 4) { sts32(VT + b * 2048 + cm, w0); sts32(VT + b * 2048 + cm + 128, w1); }
                                        if constexpr (b >= 4) { sts32(VT + (b + 2) * 2048 + cm, w0); sts32(VT + (b + 2) * 2048 + cm + 128, w1); }
                                        if constexpr (b == 0) {
                                            const uint32_t one = (cm & 12) ? 0u : 0x00003F80u;
                                            sts32(VT + 5 * 2048 + cm, one); sts32(VT + 5 * 2048 + cm + 128, one);
                                        }
                                        if constexpr (b == 8) {
                                            const uint32_t z = KVB + c.tid() * 16;
                                            sts128(z, 0, 0, 0, 0); sts128(z + 4096, 0, 0, 0, 0); sts128(z + 8192, 0, 0, 0, 0);
                                            if (z < KVB + 512) sts128(z + 12288, 0, 0, 0, 0);
                                            fence_async_smem();
                                        }
                                    }
                                }
                            });
                        }
                    }, [](auto) {});
                    reg_copy<36>(pv, qc);
                    prof(4 + s);
                }
            }
            {
                #pragma unroll
                for (int i = 0; i < 32; i++) hc[i] = 0.f;
                named_bar(1, 256);
                const uint32_t wgo = ((c.tid() >> 7) * 512);
                wg_fence();
                sfor<0, 8>([&](auto KS) {
                    constexpr int ks = decltype(KS)::v;
                    wg_tt64<(ks ? 1 : 0)>(hc, mkdesc(PKT + ks * 256, 128, 2048, 0) + wgo,
                                          mkdesc(VT + ks * 256, 128, 2048, 0) + wgo + (wgo >> 2));
                });
                wg_commit();
                const uint32_t pq = PQT + cm_off() + ((c.tid() >> 7) * 512) * 16;
                sfor<0, 9>([&](auto B) {
                    constexpr int b = decltype(B)::v;
                    sts32(pq + b * 1024, pack_bf16(phi(pv[4 * b] * rs0), phi(pv[4 * b + 1] * rs0)));
                    sts32(pq + b * 1024 + 128, pack_bf16(phi(pv[4 * b + 2] * rs1), phi(pv[4 * b + 3] * rs1)));
                });
                fence_async_smem();
                wg_wait<0>();
                reg_fence<32>(hc);
                reg_copy<24>(pv, hc);
            }
            prof(7);
            rs0 *= 0.5f; rs1 *= 0.5f;
            mbar_wait(bar(B_INIT), 0);
            auto gelun = [&](auto B0, auto B1, uint32_t bofs, uint32_t* w) {
                constexpr int b0 = decltype(B0)::v, nb = decltype(B1)::v - b0;
                float2 bv[nb];
                #pragma unroll
                for (int i = 0; i < nb; i++) bv[i] = lds64f(bofs + (b0 + i) * 32);
                #pragma unroll
                for (int i = 0; i < nb; i++) {
                    const int b = b0 + i;
                    w[2 * i]     = pack_bf16(gelu_h(fmaf(pv[4 * b], rs0, bv[i].x)), gelu_h(fmaf(pv[4 * b + 1], rs0, bv[i].y)));
                    w[2 * i + 1] = pack_bf16(gelu_h(fmaf(pv[4 * b + 2], rs1, bv[i].x)), gelu_h(fmaf(pv[4 * b + 3], rs1, bv[i].y)));
                }
            };
            auto spill_off = [&]() { uint32_t t_ = c.tid(); return HA + (t_ >> 7) * 8192 + (t_ & 127) * 8; };
            auto reload = [&](auto S0, auto S1) {
                const uint32_t spill = spill_off();
                sfor<decltype(S0)::v * 8, decltype(S1)::v * 8>([&](auto Q) {
                    constexpr int q = decltype(Q)::v;
                    lds64(spill + (q / 8) * 16384 + (q % 8) * 1024, a + q * 2);
                });
            };
            #pragma unroll 1
            for (int idx = 0; idx < 18; idx++) {
                run_step<K_H>(c, hc, a, [&](auto ST) {
                    constexpr int st = decltype(ST)::v;
                    if (idx >= 10) {
                        if constexpr (st < 2) {
                            const uint32_t b_ = v_bid();
                            const uint32_t chunk = (idx == 10) ? 8 : ((b_ + idx - 10) & 7);
                            unsigned char* yp = g_yacc + ((v_epoch() & 1) * 144 + (b_ >> 3) * 9 + chunk) * YT_BYTES + c.tid() * 16;
                            sfor<2 * st, 2 * st + 2>([&](auto Q) {
                                constexpr int q = decltype(Q)::v;
                                asm volatile("red.global.add.noftz.v4.bf16x2 [%0], {%1,%2,%3,%4};" :: "l"(yp + q * 4096),
                                             "r"(pack_bf16(pv[8 * q], pv[8 * q + 1])), "r"(pack_bf16(pv[8 * q + 2], pv[8 * q + 3])),
                                             "r"(pack_bf16(pv[8 * q + 4], pv[8 * q + 5])), "r"(pack_bf16(pv[8 * q + 6], pv[8 * q + 7])) : "memory");
                            });
                            if constexpr (st == 1) event(idx - 7);
                        }
                    } else if (idx >= 1) {
                        const uint32_t bofs = B1S + (idx - 1) * 256 + (c.tid() & 3) * 8;
                        if (idx < 9) {
                            if constexpr (st == 0) {
                                if (idx == OSTEP_AT + 1) {
                                    if ((c.tid() & 31) == 0) asm volatile("cp.async.bulk.wait_group 0;" ::: "memory");
                                    event(2);
                                }
                            }
                            const uint32_t spill = spill_off() + (idx - 1) * 16384;
                            constexpr int b0 = st * 3, b1 = (st == 2 ? 8 : st * 3 + 3);
                            uint32_t w[6];
                            gelun(IC<b0>{}, IC<b1>{}, bofs, w);
                            #pragma unroll
                            for (int b = b0; b < b1; b++) sts64(spill + b * 1024, w[2 * (b - b0)], w[2 * (b - b0) + 1]);
                        } else {
                            if constexpr (st < 2) {
                                const uint32_t tb = tail_off();
                                uint32_t w[8];
                                gelun(IC<st * 4>{}, IC<st * 4 + 4>{}, bofs, w);
                                #pragma unroll
                                for (int i = 0; i < 4; i++) { sts32(tb ^ ((st * 4 + i) << 4), w[2 * i]); sts32((tb ^ ((st * 4 + i) << 4)) + 1024, w[2 * i + 1]); }
                            }
                            if constexpr (st == 1) { fence_async_smem(); named_bar(2 + (c.tid() >> 7), 128); }
                        }
                    } else {
                        if constexpr (st < 2) {
                            constexpr int hf = st;
                            const int t_ = c.tid(), wg = t_ >> 7, t = t_ & 3;
                            float* dst = g_kv + ((v_epoch() & 1) * 8 + (v_bid() & 7)) * 1440;
                            const int d = wg * 32 + ((t_ >> 5) & 3) * 16 + ((t_ >> 2) & 7) + hf * 8;
                            const bool dv = wg ? (d >= 36 && d < 72) : (d < 36);
                            const int e00 = wg * 24 + 2 * t - (d / 18) * 18;
                            float* dp = dst + d * 20 + e00;
                            #pragma unroll
                            for (int i = 0; i < 6; i++) {
                                const int e = e00 + i * 8;
                                const bool blk = wg ? (i >= 1) : (i <= 4);
                                if (dv && blk && e >= 0 && e < 18)
                                    asm volatile("red.global.add.v2.f32 [%0], {%1,%2};" :: "l"(dp + i * 8), "f"(pv[4 * i + 2 * hf]), "f"(pv[4 * i + 2 * hf + 1]) : "memory");
                            }
                            if (dv && t == 0) atomicAdd(dst + d * 20 + 18, wg ? pv[2 * hf] : pv[20 + 2 * hf]);
                            if constexpr (st == 1) event(1);
                        }
                    }
                }, [&](auto ST) {
                    constexpr int st = decltype(ST)::v;
                    if (idx == 8) {
                        reload(IC<3 * st>{}, IC<(st == 2 ? 8 : 3 * st + 3)>{});
                        if constexpr (st == 2) warp_arrive(bar(B_OFREE));
                    }
                });
                reg_copy<32>(pv, hc);
                prof(8 + idx);
                if (idx == OSTEP_AT) {
                    mbar_wait(bar(B_KVB), 0);
                    prof(34);
                    const uint32_t pqo = (c.tid() >> 7) * 576;
                    const int t_ = c.tid(), b_ = v_bid(), t = t_ & 3, l4 = t_ & 28;
                    const uint32_t op = OST + ((t_ >> 5) * 16 + ((t_ >> 2) & 7)) * 144 + t * 4;
                    float r3[2];
                    sfor<0, 2>([&](auto PS) {
                        constexpr int ps = decltype(PS)::v;
                        wg_fence();
                        sfor<0, 5>([&](auto KS) {
                            constexpr int ks = decltype(KS)::v;
                            wg_ss64<(ks ? 1 : 0)>(hc, mkdesc(PQT + ks * 2048, ks == 4 ? 0 : 1024, 128, 0) + pqo, mkdesc(KVB + ps * 8 * 1280 + ks * 256, 128, 1280, 0));
                        });
                        wg_commit();
                        wg_wait<0>();
                        reg_fence<32>(hc);
                        #pragma unroll
                        for (int hf = 0; hf < 2; hf++) {
                            if constexpr (ps == 0) {
                                float r[4];
                                r[0] = rcp(__shfl_sync(0xffffffffu, hc[2 * hf], l4) + 1e-6f);
                                r[1] = rcp(__shfl_sync(0xffffffffu, hc[1 + 2 * hf], l4) + 1e-6f);
                                r[2] = rcp(__shfl_sync(0xffffffffu, hc[2 * hf], l4 + 1) + 1e-6f);
                                r[3] = rcp(__shfl_sync(0xffffffffu, hc[1 + 2 * hf], l4 + 1) + 1e-6f);
                                r3[hf] = r[3];
                                #pragma unroll
                                for (int i = 0; i < 7; i++) {
                                    float rr = (i < 2) ? r[0] : (i == 2) ? (t < 1 ? r[0] : r[1]) : (i == 3) ? r[1] : (i == 4) ? (t < 2 ? r[1] : r[2])
                                             : (i == 5) ? r[2] : (t < 3 ? r[2] : r[3]);
                                    sts32(op + hf * 8 * 144 + i * 16, pack_bf16(hc[4 * i + 4 + 2 * hf] * rr, hc[4 * i + 5 + 2 * hf] * rr));
                                }
                            } else {
                                #pragma unroll
                                for (int i = 0; i < 2; i++)
                                    sts32(op + hf * 8 * 144 + 112 + i * 16, pack_bf16(hc[4 * i + 2 * hf] * r3[hf], hc[4 * i + 1 + 2 * hf] * r3[hf]));
                            }
                        }
                    });
                    fence_async_smem();
                    __syncwarp();
                    if ((t_ & 31) == 0) {
                        asm volatile("cp.async.bulk.tensor.2d.global.shared::cta.bulk_group [%0, {%2, %3}], [%1];"
                                     :: "l"(&tm_ost), "r"(OST + (t_ >> 5) * 2304), "r"((b_ & 7) * 72), "r"((b_ >> 3) * 128 + (t_ >> 5) * 16) : "memory");
                        asm volatile("cp.async.bulk.commit_group;" ::: "memory");
                    }
                }
            }
        }
        if (is_main) warp_arrive(bar(B_O8FREE));
        else {
            mbar_wait(bar(B_INIT), 0);
            #pragma unroll
            for (int i = 0; i < 32; i++) { asm volatile("mov.b32 %0, 0;" : "=f"(hc[i])); asm volatile("mov.b32 %0, 0;" : "=f"(pv[i])); }
        }
        auto add_b2 = [&]() {
            #pragma unroll
            for (int b = 0; b < 8; b++) {
                float2 bv = lds64f(B2S + b * 32 + (c.tid() & 3) * 8);
                pv[4 * b] += bv.x; pv[4 * b + 1] += bv.y; pv[4 * b + 2] += bv.x; pv[4 * b + 3] += bv.y;
            }
        };
        auto load_xy = [&](int ftile, int nrdy, uint32_t* xr, uint32_t* yv) {
            const int mt = ftile / 9, ch = ftile - mt * 9;
            const uint32_t t_ = c.tid();
            const __nv_bfloat16* xp = p.x + (size_t)(mt * 128 + (t_ >> 5) * 16 + ((t_ >> 2) & 7)) * DM + ch * 64 + 2 * (t_ & 3);
            #pragma unroll
            for (int i = 0; i < 8; i++) {
                asm volatile("ld.global.nc.u32 %0, [%1];" : "=r"(xr[2 * i]) : "l"(xp + i * 8));
                asm volatile("ld.global.nc.u32 %0, [%1];" : "=r"(xr[2 * i + 1]) : "l"(xp + 8 * DM + i * 8));
            }
            prof(26);
            smem_wait_gt(EPO + 4, nrdy);
            prof(27);
            const unsigned char* yp = g_yacc + ((v_epoch() & 1) * 144 + ftile) * YT_BYTES + t_ * 16;
            #pragma unroll
            for (int q = 0; q < YT_BYTES / 4096; q++)
                asm volatile("ld.global.cg.v4.u32 {%0,%1,%2,%3}, [%4];" : "=r"(yv[4 * q]), "=r"(yv[4 * q + 1]), "=r"(yv[4 * q + 2]), "=r"(yv[4 * q + 3]) : "l"(yp + q * 4096) : "memory");
        };
        auto gate = [&](const uint32_t* yv) {
            #pragma unroll
            for (int i = 0; i < 16; i++) { pv[2 * i] += bf_lo(yv[i]); pv[2 * i + 1] += bf_hi(yv[i]); }
            #pragma unroll
            for (int i = 0; i < 32; i++) { const float h = 0.5f * pv[i]; pv[i] = fmaf(h, tanh_ap(h), h); }
        };
        auto store_out = [&](int ftile, const uint32_t* xr) {
            const int mt = ftile / 9, ch = ftile - mt * 9;
            const uint32_t t_ = c.tid();
            __nv_bfloat16* op = p.out + (size_t)(mt * 128 + (t_ >> 5) * 16 + ((t_ >> 2) & 7)) * DM + ch * 64 + 2 * (t_ & 3);
            #pragma unroll
            for (int b = 0; b < 8; b++) {
                *reinterpret_cast<uint32_t*>(op + b * 8) =
                    pack_bf16(fmaf(hc[4 * b], pv[4 * b], bf_lo(xr[2 * b])), fmaf(hc[4 * b + 1], pv[4 * b + 1], bf_hi(xr[2 * b])));
                *reinterpret_cast<uint32_t*>(op + 8 * DM + b * 8) =
                    pack_bf16(fmaf(hc[4 * b + 2], pv[4 * b + 2], bf_lo(xr[2 * b + 1])), fmaf(hc[4 * b + 3], pv[4 * b + 3], bf_hi(xr[2 * b + 1])));
            }
        };
        const int njob = is_main ? 1 : 4;
        #pragma unroll 1
        for (int job = 0; job < njob; job++) {
            const uint32_t jpar = job & 1;
            const uint32_t b_ = v_bid();
            const bool mainf = b_ < NMAIN;
            const int ftile = (b_ >> 3) * 9 + (b_ & 7);
            uint32_t oa[128];
            {
                mbar_wait(bar(B_OFULL), jpar);
                const uint32_t lrow = lrow_off();
                sfor<0, 32>([&](auto KS) {
                    constexpr int ks = decltype(KS)::v;
                    ldsm4((lrow ^ ((ks % 4) << 5)) + (ks / 4) * 16384, oa + ks * 4);
                });
                warp_arrive(bar(B_OFREE));
                if (job) c.tph ^= 1;
            }
            c.pf = false;
            run_step<K_H>(c, hc, oa, [&](auto ST) {
                constexpr int st = decltype(ST)::v;
                if (mainf) {
                    if constexpr (st == 0) add_b2();
                    else if constexpr (st == 1) load_xy(ftile, 0, oa, oa + 16);
                    else { prof(28); gate(oa + 16); prof(29); }
                }
                if constexpr (st == 1) mbar_wait(bar(B_O8FULL), jpar);
            }, [](auto) {}, job == njob - 1);
            prof(30);
            if (mainf) {
                store_out(ftile, oa);
            } else {
                warp_arrive(bar(B_O8FREE));
                uint4* sp = reinterpret_cast<uint4*>(g_s8) + ((b_ - NMAIN) * 4 + job) * 1024 + c.tid();
                #pragma unroll
                for (int q = 0; q < 4; q++)
                    sp[q * 256] = make_uint4(pack_bf16(hc[8 * q], hc[8 * q + 1]), pack_bf16(hc[8 * q + 2], hc[8 * q + 3]),
                                             pack_bf16(hc[8 * q + 4], hc[8 * q + 5]), pack_bf16(hc[8 * q + 6], hc[8 * q + 7]));
                prof(8 + job);
            }
        }
        if (!is_main) {
            #pragma unroll 1
            for (int job = 0; job < 4; job++) {
                const int tile = (v_bid() - NMAIN) * 4 + job;
                uint32_t xr[16], yv[YT_BYTES / 1024];
                const uint4* sp = reinterpret_cast<const uint4*>(g_s8) + tile * 1024 + c.tid();
                #pragma unroll
                for (int q = 0; q < 4; q++) {
                    const uint4 u = __ldcg(sp + q * 256);
                    hc[8 * q] = bf_lo(u.x); hc[8 * q + 1] = bf_hi(u.x); hc[8 * q + 2] = bf_lo(u.y); hc[8 * q + 3] = bf_hi(u.y);
                    hc[8 * q + 4] = bf_lo(u.z); hc[8 * q + 5] = bf_hi(u.z); hc[8 * q + 6] = bf_lo(u.w); hc[8 * q + 7] = bf_hi(u.w);
                }
                #pragma unroll
                for (int i = 0; i < 32; i++) pv[i] = 0.f;
                add_b2();
                load_xy(tile * 9 + 8, job, xr, yv);
                gate(yv);
                store_out(tile * 9 + 8, xr);
                prof(12 + job);
            }
        }
        prof(40);
        if (c.tid() == 0) g_epoch[v_bid()] = v_epoch() + 1;
    }
}

typedef CUresult (*EncodeFn)(CUtensorMap*, CUtensorMapDataType, cuuint32_t, void*, const cuuint64_t*, const cuuint64_t*,
                             const cuuint32_t*, const cuuint32_t*, CUtensorMapInterleave, CUtensorMapSwizzle,
                             CUtensorMapL2promotion, CUtensorMapFloatOOBfill);

void make_map(EncodeFn enc, CUtensorMap* tm, const void* base, int rows, int cols, int box_rows, int box_cols = 64, bool swz = true) {
    cuuint64_t gdim[2] = {(cuuint64_t)cols, (cuuint64_t)rows};
    cuuint64_t gstr[1] = {(cuuint64_t)cols * 2};
    cuuint32_t box[2] = {(cuuint32_t)box_cols, (cuuint32_t)box_rows};
    cuuint32_t estr[2] = {1, 1};
    enc(tm, CU_TENSOR_MAP_DATA_TYPE_BFLOAT16, 2, const_cast<void*>(base), gdim, gstr, box, estr, CU_TENSOR_MAP_INTERLEAVE_NONE,
        swz ? CU_TENSOR_MAP_SWIZZLE_128B : CU_TENSOR_MAP_SWIZZLE_NONE, CU_TENSOR_MAP_L2_PROMOTION_L2_128B, CU_TENSOR_MAP_FLOAT_OOB_FILL_NONE);
}

}

extern "C" void kernel_launch(void* const* d_in, const int* in_sizes, int n_in, void* d_out, int out_size) {
    static EncodeFn enc = nullptr;
    static void* o_ptr = nullptr;
    if (!enc) {
        void* fn = nullptr;
        cudaDriverEntryPointQueryResult qr;
        cudaGetDriverEntryPoint("cuTensorMapEncodeTiled", &fn, cudaEnableDefault, &qr);
        enc = (EncodeFn)fn;
        cudaGetSymbolAddress(&o_ptr, g_o);
        cudaFuncSetAttribute(fused_kernel, cudaFuncAttributeMaxDynamicSharedMemorySize, SMEM_BYTES);
    }
    Params p;
    p.x = (const __nv_bfloat16*)d_in[0];
    p.wqkv = (const __nv_bfloat16*)d_in[1];
    p.wo = (const __nv_bfloat16*)d_in[2];
    p.w1 = (const __nv_bfloat16*)d_in[4];
    p.b1 = (const __nv_bfloat16*)d_in[5];
    p.w2 = (const __nv_bfloat16*)d_in[6];
    p.b2 = (const __nv_bfloat16*)d_in[7];
    p.out = (__nv_bfloat16*)d_out;
    CUtensorMap tm_x, tm_w1, tm_w2, tm_wo, tm_o, tm_qkv, tm_qkve, tm_ost;
    make_map(enc, &tm_ost, o_ptr, SEQ, DM, 16, 72, false);
    make_map(enc, &tm_qkv, p.wqkv, DM, 3 * DM, 96);
    make_map(enc, &tm_qkve, p.wqkv, DM, 3 * DM, 96, 8);
    make_map(enc, &tm_x, p.x, SEQ, DM, 128);
    make_map(enc, &tm_w1, p.w1, DM, FF, 192);
    make_map(enc, &tm_w2, p.w2, FF, DM, 192);
    make_map(enc, &tm_wo, p.wo, DM, DM, 192);
    make_map(enc, &tm_o, o_ptr, SEQ, DM, 128);
    fused_kernel<<<NMAIN + NAUX, 384, SMEM_BYTES>>>(tm_x, tm_w1, tm_w2, tm_wo, tm_o, tm_qkv, tm_qkve, tm_ost, p);
}
```

```cpp
#include <cuda_runtime.h>
#include <cuda.h>
#include <cuda_bf16.h>
#include <stdint.h>

#define OSTEP_AT 4
#define KNOB_A 1
#define KNOB_B 0
#define PF1_NS 1500
#define PF2_NS 2000
#define PFIDX 3
#define PF3_NS 800
#define EARLY_REL 0
#define PF0_NS 1200
#define SIG_NS 64
#define POLL_NS 100
#define YF32 0

namespace {
constexpr int WAIT_ITERS = 3000000;

constexpr int SEQ = 2048, DM = 576, FF = 4608;
constexpr int NMAIN = 128, NAUX = 4;

constexpr uint32_t SB    = 0x400;
constexpr uint32_t HA    = SB;
constexpr uint32_t XB    = SB + 131072;
constexpr uint32_t RING  = SB + 147456;
constexpr uint32_t SLOT  = 24576;
constexpr uint32_t MISC  = SB + 221184;
constexpr uint32_t BARS  = MISC;
constexpr uint32_t B1S   = MISC + 512;
constexpr uint32_t B2S   = MISC + 2816;
constexpr uint32_t EPO   = MISC + 3072;
constexpr uint32_t EVC   = MISC + 3104;
constexpr uint32_t SMEM_BYTES = 221184 + 3200 + 512;
constexpr uint32_t PKT   = HA + 32768;
constexpr uint32_t VT    = HA + 51200;
constexpr uint32_t OST   = HA + 79872;
constexpr uint32_t PQT   = HA + 98304;
constexpr uint32_t KVB   = HA + 116736;

enum { B_FULL = 0, B_EMPTY = 3, B_XFULL = 6, B_OFULL = 9, B_O8FULL = 10, B_OFREE = 11, B_O8FREE = 12, B_KVB = 13, B_INIT = 14, B_COUNT = 15 };
__device__ __forceinline__ constexpr uint32_t bar(int i) { return BARS + 8u * i; }

constexpr int YT_BYTES = YF32 ? 32768 : 16384;
__device__ __align__(1024) __nv_bfloat16 g_o[SEQ * DM];
__device__ __align__(1024) unsigned char g_yacc[2 * 16 * 9 * YT_BYTES];
__device__ __align__(128) float g_kv[2 * 8 * 72 * 20];
__device__ __align__(128) unsigned int g_s8[16 * 4096];
__device__ __align__(128) unsigned int g_cnt[(8 + 16 + 16 * 9) * 8];
__device__ unsigned int g_epoch[NMAIN + NAUX];
__device__ __forceinline__ unsigned int* cnt_kv(int j) { return g_cnt + j * 8; }
__device__ __forceinline__ unsigned int* cnt_o(int m) { return g_cnt + (8 + m) * 8; }
__device__ __forceinline__ unsigned int* cnt_y(int m, int c) { return g_cnt + (24 + m * 9 + c) * 8; }

__device__ __forceinline__ void mbar_init(uint32_t b, uint32_t cnt) { asm volatile("mbarrier.init.shared::cta.b64 [%0], %1;" :: "r"(b), "r"(cnt)); }
__device__ __forceinline__ void mbar_expect_tx(uint32_t b, uint32_t bytes) { asm volatile("mbarrier.arrive.expect_tx.shared::cta.b64 _, [%0], %1;" :: "r"(b), "r"(bytes) : "memory"); }
__device__ __forceinline__ void mbar_arrive(uint32_t b) { asm volatile("mbarrier.arrive.shared::cta.b64 _, [%0];" :: "r"(b) : "memory"); }
__device__ __forceinline__ void prof(int) {}
__device__ __forceinline__ void mbar_wait(uint32_t b, uint32_t parity) {
    asm volatile("{\n.reg .pred p;\n.reg .u32 c;\nmov.u32 c, 0;\n"
                 "WAIT_LOOP:\nmbarrier.try_wait.parity.shared::cta.b64 p, [%0], %1;\n@p bra WAIT_DONE;\n"
                 "add.u32 c, c, 1;\nsetp.lt.u32 p, c, 1000000;\n@p bra WAIT_LOOP;\ntrap;\nWAIT_DONE:\n}"
                 :: "r"(b), "r"(parity) : "memory");
}
__device__ __forceinline__ void smem_wait_gt(uint32_t addr, uint32_t val) {
    asm volatile("{\n.reg .pred p;\n.reg .u32 c, v;\nmov.u32 c, 0;\n"
                 "SW_LOOP:\nld.acquire.cta.shared.u32 v, [%0];\nsetp.gt.u32 p, v, %1;\n@p bra SW_DONE;\n"
                 "nanosleep.u32 64;\nadd.u32 c, c, 1;\nsetp.lt.u32 p, c, 20000000;\n@p bra SW_LOOP;\ntrap;\nSW_DONE:\n}"
                 :: "r"(addr), "r"(val) : "memory");
}
__device__ __forceinline__ void tma_2d(uint32_t dst, const CUtensorMap* tm, uint32_t b, int c0, int c1) {
    asm volatile("cp.async.bulk.tensor.2d.shared::cluster.global.mbarrier::complete_tx::bytes [%0], [%1, {%3, %4}], [%2];"
                 :: "r"(dst), "l"(tm), "r"(b), "r"(c0), "r"(c1) : "memory");
}
__device__ __forceinline__ void fence_async_smem() { asm volatile("fence.proxy.async.shared::cta;" ::: "memory"); }
__device__ __forceinline__ void fence_async_all() { asm volatile("fence.proxy.async;" ::: "memory"); }
__device__ __forceinline__ void named_bar(int id, int n) { asm volatile("bar.sync %0, %1;" :: "r"(id), "r"(n) : "memory"); }
__device__ __forceinline__ void wg_fence() { asm volatile("wgmma.fence.sync.aligned;" ::: "memory"); }
__device__ __forceinline__ void wg_commit() { asm volatile("wgmma.commit_group.sync.aligned;" ::: "memory"); }
template<int N> __device__ __forceinline__ void wg_wait() { asm volatile("wgmma.wait_group.sync.aligned %0;" :: "n"(N) : "memory"); }
template<int N> __device__ __forceinline__ void reg_fence(float* d) {
    #pragma unroll
    for (int i = 0; i < N; i++) asm volatile("" : "+f"(d[i]) :: "memory");
}
template<int N> __device__ __forceinline__ void reg_copy(float* d, const float* s) {
    #pragma unroll
    for (int i = 0; i < N; i++) asm volatile("mov.b32 %0, %1;" : "=f"(d[i]) : "f"(s[i]));
}
__device__ __forceinline__ uint32_t pack_bf16(float lo, float hi) { uint32_t r; asm("cvt.rn.bf16x2.f32 %0, %1, %2;" : "=r"(r) : "f"(hi), "f"(lo)); return r; }
__device__ __forceinline__ float bf_lo(uint32_t v) { return __uint_as_float(v << 16); }
__device__ __forceinline__ float bf_hi(uint32_t v) { return __uint_as_float(v & 0xffff0000u); }
__device__ __forceinline__ uint32_t sub_bf16x2(uint32_t a, uint32_t b) { uint32_t r; asm("sub.rn.bf16x2 %0, %1, %2;" : "=r"(r) : "r"(a), "r"(b)); return r; }
__device__ __forceinline__ float ex2(float x) { float r; asm("ex2.approx.ftz.f32 %0, %1;" : "=f"(r) : "f"(x)); return r; }
__device__ __forceinline__ float rcp(float x) { float r; asm("rcp.approx.ftz.f32 %0, %1;" : "=f"(r) : "f"(x)); return r; }
__device__ __forceinline__ float tanh_ap(float x) { float r; asm("tanh.approx.f32 %0, %1;" : "=f"(r) : "f"(x)); return r; }
__device__ __forceinline__ void sts32(uint32_t a, uint32_t v) { asm volatile("st.shared.b32 [%0], %1;" :: "r"(a), "r"(v)); }
__device__ __forceinline__ void sts128(uint32_t a, uint32_t x, uint32_t y, uint32_t z, uint32_t w) { asm volatile("st.shared.v4.b32 [%0], {%1,%2,%3,%4};" :: "r"(a), "r"(x), "r"(y), "r"(z), "r"(w)); }
__device__ __forceinline__ void sts64(uint32_t a, uint32_t x, uint32_t y) { asm volatile("st.shared.v2.b32 [%0], {%1,%2};" :: "r"(a), "r"(x), "r"(y)); }
__device__ __forceinline__ void lds64(uint32_t a, uint32_t* v) { asm volatile("ld.shared.v2.b32 {%0,%1}, [%2];" : "=r"(v[0]), "=r"(v[1]) : "r"(a)); }
__device__ __forceinline__ void lds128(uint32_t a, uint32_t* v) { asm volatile("ld.shared.v4.b32 {%0,%1,%2,%3}, [%4];" : "=r"(v[0]), "=r"(v[1]), "=r"(v[2]), "=r"(v[3]) : "r"(a) : "memory"); }
__device__ __forceinline__ float2 lds64f(uint32_t a) { float2 v; asm("ld.shared.v2.f32 {%0,%1}, [%2];" : "=f"(v.x), "=f"(v.y) : "r"(a)); return v; }
__device__ __forceinline__ void ldsm4(uint32_t a, uint32_t* v) {
    asm volatile("ldmatrix.sync.aligned.m8n8.x4.shared.b16 {%0,%1,%2,%3}, [%4];" : "=r"(v[0]), "=r"(v[1]), "=r"(v[2]), "=r"(v[3]) : "r"(a));
}
__device__ __forceinline__ void mma_ones(float* c, const uint32_t* a) {
    const uint32_t one2 = 0x3F803F80u;
    asm volatile("mma.sync.aligned.m16n8k16.row.col.f32.bf16.bf16.f32 {%0,%1,%2,%3}, {%4,%5,%6,%7}, {%8,%8}, {%0,%1,%2,%3};"
                 : "+f"(c[0]), "+f"(c[1]), "+f"(c[2]), "+f"(c[3]) : "r"(a[0]), "r"(a[1]), "r"(a[2]), "r"(a[3]), "r"(one2));
}
__device__ __forceinline__ void mma_bf16(float* c, const uint32_t* a, uint32_t b0, uint32_t b1) {
    asm volatile("mma.sync.aligned.m16n8k16.row.col.f32.bf16.bf16.f32 {%0,%1,%2,%3}, {%4,%5,%6,%7}, {%8,%9}, {%0,%1,%2,%3};"
                 : "+f"(c[0]), "+f"(c[1]), "+f"(c[2]), "+f"(c[3]) : "r"(a[0]), "r"(a[1]), "r"(a[2]), "r"(a[3]), "r"(b0), "r"(b1));
}
__device__ __forceinline__ unsigned int ld_acquire(const unsigned int* p) { unsigned int v; asm volatile("ld.acquire.gpu.global.u32 %0, [%1];" : "=r"(v) : "l"(p) : "memory"); return v; }
__device__ __forceinline__ void wait_cnt(const unsigned int* p, unsigned int target) {
    for (int i = 0; i < WAIT_ITERS; i++) {
        if ((int)(ld_acquire(p) - target) >= 0) return;
        __nanosleep(POLL_NS);
    }
    __trap();
}
__device__ __forceinline__ uint32_t v_tid() { uint32_t r; asm volatile("mov.u32 %0, %%tid.x;" : "=r"(r)); return r; }
__device__ __forceinline__ uint32_t v_bid() { uint32_t r; asm volatile("mov.u32 %0, %%ctaid.x;" : "=r"(r)); return r; }
__device__ __forceinline__ uint32_t v_epoch() { uint32_t r; asm volatile("ld.shared.u32 %0, [%1];" : "=r"(r) : "r"(EPO)); return r; }
__device__ __forceinline__ void prefetch_l2(const void* p) { asm volatile("prefetch.global.L2 [%0];" :: "l"(p)); }

__host__ __device__ constexpr uint64_t mkdesc(uint32_t addr, uint32_t lbo, uint32_t sbo, uint32_t swz) {
    return (uint64_t)((addr & 0x3FFFF) >> 4) | ((uint64_t)((lbo >> 4) & 0x3FFF) << 16) | ((uint64_t)((sbo >> 4) & 0x3FFF) << 32) | ((uint64_t)swz << 62);
}

template<int SD> __device__ __forceinline__ void wg_rs64(float* d, const uint32_t* a, uint64_t bd) {
  if constexpr (SD) {
    asm volatile("{\n.reg .pred p;\nsetp.eq.b32 p, 0, 0;\n"
    "wgmma.mma_async.sync.aligned.m64n64k16.f32.bf16.bf16 {%0,%1,%2,%3,%4,%5,%6,%7,%8,%9,%10,%11,%12,%13,%14,%15,%16,%17,%18,%19,%20,%21,%22,%23,%24,%25,%26,%27,%28,%29,%30,%31}, {%32,%33,%34,%35}, %36, p, 1, 1, 1;\n}"
    : "+f"(d[0]),"+f"(d[1]),"+f"(d[2]),"+f"(d[3]),"+f"(d[4]),"+f"(d[5]),"+f"(d[6]),"+f"(d[7]),"+f"(d[8]),"+f"(d[9]),"+f"(d[10]),"+f"(d[11]),"+f"(d[12]),"+f"(d[13]),"+f"(d[14]),"+f"(d[15]),"+f"(d[16]),"+f"(d[17]),"+f"(d[18]),"+f"(d[19]),"+f"(d[20]),"+f"(d[21]),"+f"(d[22]),"+f"(d[23]),"+f"(d[24]),"+f"(d[25]),"+f"(d[26]),"+f"(d[27]),"+f"(d[28]),"+f"(d[29]),"+f"(d[30]),"+f"(d[31])
    : "r"(a[0]),"r"(a[1]),"r"(a[2]),"r"(a[3]), "l"(bd));
  } else {
    asm volatile("{\n.reg .pred p;\nsetp.ne.b32 p, 0, 0;\n"
    "wgmma.mma_async.sync.aligned.m64n64k16.f32.bf16.bf16 {%0,%1,%2,%3,%4,%5,%6,%7,%8,%9,%10,%11,%12,%13,%14,%15,%16,%17,%18,%19,%20,%21,%22,%23,%24,%25,%26,%27,%28,%29,%30,%31}, {%32,%33,%34,%35}, %36, p, 1, 1, 1;\n}"
    : "+f"(d[0]),"+f"(d[1]),"+f"(d[2]),"+f"(d[3]),"+f"(d[4]),"+f"(d[5]),"+f"(d[6]),"+f"(d[7]),"+f"(d[8]),"+f"(d[9]),"+f"(d[10]),"+f"(d[11]),"+f"(d[12]),"+f"(d[13]),"+f"(d[14]),"+f"(d[15]),"+f"(d[16]),"+f"(d[17]),"+f"(d[18]),"+f"(d[19]),"+f"(d[20]),"+f"(d[21]),"+f"(d[22]),"+f"(d[23]),"+f"(d[24]),"+f"(d[25]),"+f"(d[26]),"+f"(d[27]),"+f"(d[28]),"+f"(d[29]),"+f"(d[30]),"+f"(d[31])
    : "r"(a[0]),"r"(a[1]),"r"(a[2]),"r"(a[3]), "l"(bd));
  }
}
template<int SD> __device__ __forceinline__ void wg_ss64(float* d, uint64_t ad, uint64_t bd) {
  if constexpr (SD) {
    asm volatile("{\n.reg .pred p;\nsetp.eq.b32 p, 0, 0;\n"
    "wgmma.mma_async.sync.aligned.m64n64k16.f32.bf16.bf16 {%0,%1,%2,%3,%4,%5,%6,%7,%8,%9,%10,%11,%12,%13,%14,%15,%16,%17,%18,%19,%20,%21,%22,%23,%24,%25,%26,%27,%28,%29,%30,%31}, %32, %33, p, 1, 1, 0, 1;\n}"
    : "+f"(d[0]),"+f"(d[1]),"+f"(d[2]),"+f"(d[3]),"+f"(d[4]),"+f"(d[5]),"+f"(d[6]),"+f"(d[7]),"+f"(d[8]),"+f"(d[9]),"+f"(d[10]),"+f"(d[11]),"+f"(d[12]),"+f"(d[13]),"+f"(d[14]),"+f"(d[15]),"+f"(d[16]),"+f"(d[17]),"+f"(d[18]),"+f"(d[19]),"+f"(d[20]),"+f"(d[21]),"+f"(d[22]),"+f"(d[23]),"+f"(d[24]),"+f"(d[25]),"+f"(d[26]),"+f"(d[27]),"+f"(d[28]),"+f"(d[29]),"+f"(d[30]),"+f"(d[31])
    : "l"(ad), "l"(bd));
  } else {
    asm volatile("{\n.reg .pred p;\nsetp.ne.b32 p, 0, 0;\n"
    "wgmma.mma_async.sync.aligned.m64n64k16.f32.bf16.bf16 {%0,%1,%2,%3,%4,%5,%6,%7,%8,%9,%10,%11,%12,%13,%14,%15,%16,%17,%18,%19,%20,%21,%22,%23,%24,%25,%26,%27,%28,%29,%30,%31}, %32, %33, p, 1, 1, 0, 1;\n}"
    : "+f"(d[0]),"+f"(d[1]),"+f"(d[2]),"+f"(d[3]),"+f"(d[4]),"+f"(d[5]),"+f"(d[6]),"+f"(d[7]),"+f"(d[8]),"+f"(d[9]),"+f"(d[10]),"+f"(d[11]),"+f"(d[12]),"+f"(d[13]),"+f"(d[14]),"+f"(d[15]),"+f"(d[16]),"+f"(d[17]),"+f"(d[18]),"+f"(d[19]),"+f"(d[20]),"+f"(d[21]),"+f"(d[22]),"+f"(d[23]),"+f"(d[24]),"+f"(d[25]),"+f"(d[26]),"+f"(d[27]),"+f"(d[28]),"+f"(d[29]),"+f"(d[30]),"+f"(d[31])
    : "l"(ad), "l"(bd));
  }
}
template<int SD> __device__ __forceinline__ void wg_rs72(float* d, const uint32_t* a, uint64_t bd) {
  if constexpr (SD) {
    asm volatile("{\n.reg .pred p;\nsetp.eq.b32 p, 0, 0;\n"
    "wgmma.mma_async.sync.aligned.m64n72k16.f32.bf16.bf16 {%0,%1,%2,%3,%4,%5,%6,%7,%8,%9,%10,%11,%12,%13,%14,%15,%16,%17,%18,%19,%20,%21,%22,%23,%24,%25,%26,%27,%28,%29,%30,%31,%32,%33,%34,%35}, {%36,%37,%38,%39}, %40, p, 1, 1, 1;\n}"
    : "+f"(d[0]),"+f"(d[1]),"+f"(d[2]),"+f"(d[3]),"+f"(d[4]),"+f"(d[5]),"+f"(d[6]),"+f"(d[7]),"+f"(d[8]),"+f"(d[9]),"+f"(d[10]),"+f"(d[11]),"+f"(d[12]),"+f"(d[13]),"+f"(d[14]),"+f"(d[15]),"+f"(d[16]),"+f"(d[17]),"+f"(d[18]),"+f"(d[19]),"+f"(d[20]),"+f"(d[21]),"+f"(d[22]),"+f"(d[23]),"+f"(d[24]),"+f"(d[25]),"+f"(d[26]),"+f"(d[27]),"+f"(d[28]),"+f"(d[29]),"+f"(d[30]),"+f"(d[31]),"+f"(d[32]),"+f"(d[33]),"+f"(d[34]),"+f"(d[35])
    : "r"(a[0]),"r"(a[1]),"r"(a[2]),"r"(a[3]), "l"(bd));
  } else {
    asm volatile("{\n.reg .pred p;\nsetp.ne.b32 p, 0, 0;\n"
    "wgmma.mma_async.sync.aligned.m64n72k16.f32.bf16.bf16 {%0,%1,%2,%3,%4,%5,%6,%7,%8,%9,%10,%11,%12,%13,%14,%15,%16,%17,%18,%19,%20,%21,%22,%23,%24,%25,%26,%27,%28,%29,%30,%31,%32,%33,%34,%35}, {%36,%37,%38,%39}, %40, p, 1, 1, 1;\n}"
    : "+f"(d[0]),"+f"(d[1]),"+f"(d[2]),"+f"(d[3]),"+f"(d[4]),"+f"(d[5]),"+f"(d[6]),"+f"(d[7]),"+f"(d[8]),"+f"(d[9]),"+f"(d[10]),"+f"(d[11]),"+f"(d[12]),"+f"(d[13]),"+f"(d[14]),"+f"(d[15]),"+f"(d[16]),"+f"(d[17]),"+f"(d[18]),"+f"(d[19]),"+f"(d[20]),"+f"(d[21]),"+f"(d[22]),"+f"(d[23]),"+f"(d[24]),"+f"(d[25]),"+f"(d[26]),"+f"(d[27]),"+f"(d[28]),"+f"(d[29]),"+f"(d[30]),"+f"(d[31]),"+f"(d[32]),"+f"(d[33]),"+f"(d[34]),"+f"(d[35])
    : "r"(a[0]),"r"(a[1]),"r"(a[2]),"r"(a[3]), "l"(bd));
  }
}
template<int SD> __device__ __forceinline__ void wg_ss72(float* d, uint64_t ad, uint64_t bd) {
  if constexpr (SD) {
    asm volatile("{\n.reg .pred p;\nsetp.eq.b32 p, 0, 0;\n"
    "wgmma.mma_async.sync.aligned.m64n72k16.f32.bf16.bf16 {%0,%1,%2,%3,%4,%5,%6,%7,%8,%9,%10,%11,%12,%13,%14,%15,%16,%17,%18,%19,%20,%21,%22,%23,%24,%25,%26,%27,%28,%29,%30,%31,%32,%33,%34,%35}, %36, %37, p, 1, 1, 0, 1;\n}"
    : "+f"(d[0]),"+f"(d[1]),"+f"(d[2]),"+f"(d[3]),"+f"(d[4]),"+f"(d[5]),"+f"(d[6]),"+f"(d[7]),"+f"(d[8]),"+f"(d[9]),"+f"(d[10]),"+f"(d[11]),"+f"(d[12]),"+f"(d[13]),"+f"(d[14]),"+f"(d[15]),"+f"(d[16]),"+f"(d[17]),"+f"(d[18]),"+f"(d[19]),"+f"(d[20]),"+f"(d[21]),"+f"(d[22]),"+f"(d[23]),"+f"(d[24]),"+f"(d[25]),"+f"(d[26]),"+f"(d[27]),"+f"(d[28]),"+f"(d[29]),"+f"(d[30]),"+f"(d[31]),"+f"(d[32]),"+f"(d[33]),"+f"(d[34]),"+f"(d[35])
    : "l"(ad), "l"(bd));
  } else {
    asm volatile("{\n.reg .pred p;\nsetp.ne.b32 p, 0, 0;\n"
    "wgmma.mma_async.sync.aligned.m64n72k16.f32.bf16.bf16 {%0,%1,%2,%3,%4,%5,%6,%7,%8,%9,%10,%11,%12,%13,%14,%15,%16,%17,%18,%19,%20,%21,%22,%23,%24,%25,%26,%27,%28,%29,%30,%31,%32,%33,%34,%35}, %36, %37, p, 1, 1, 0, 1;\n}"
    : "+f"(d[0]),"+f"(d[1]),"+f"(d[2]),"+f"(d[3]),"+f"(d[4]),"+f"(d[5]),"+f"(d[6]),"+f"(d[7]),"+f"(d[8]),"+f"(d[9]),"+f"(d[10]),"+f"(d[11]),"+f"(d[12]),"+f"(d[13]),"+f"(d[14]),"+f"(d[15]),"+f"(d[16]),"+f"(d[17]),"+f"(d[18]),"+f"(d[19]),"+f"(d[20]),"+f"(d[21]),"+f"(d[22]),"+f"(d[23]),"+f"(d[24]),"+f"(d[25]),"+f"(d[26]),"+f"(d[27]),"+f"(d[28]),"+f"(d[29]),"+f"(d[30]),"+f"(d[31]),"+f"(d[32]),"+f"(d[33]),"+f"(d[34]),"+f"(d[35])
    : "l"(ad), "l"(bd));
  }
}
template<int SD> __device__ __forceinline__ void wg_tt64(float* d, uint64_t ad, uint64_t bd) {
  if constexpr (SD) {
    asm volatile("{\n.reg .pred p;\nsetp.eq.b32 p, 0, 0;\n"
    "wgmma.mma_async.sync.aligned.m64n64k16.f32.bf16.bf16 {%0,%1,%2,%3,%4,%5,%6,%7,%8,%9,%10,%11,%12,%13,%14,%15,%16,%17,%18,%19,%20,%21,%22,%23,%24,%25,%26,%27,%28,%29,%30,%31}, %32, %33, p, 1, 1, 1, 1;\n}"
    : "+f"(d[0]),"+f"(d[1]),"+f"(d[2]),"+f"(d[3]),"+f"(d[4]),"+f"(d[5]),"+f"(d[6]),"+f"(d[7]),"+f"(d[8]),"+f"(d[9]),"+f"(d[10]),"+f"(d[11]),"+f"(d[12]),"+f"(d[13]),"+f"(d[14]),"+f"(d[15]),"+f"(d[16]),"+f"(d[17]),"+f"(d[18]),"+f"(d[19]),"+f"(d[20]),"+f"(d[21]),"+f"(d[22]),"+f"(d[23]),"+f"(d[24]),"+f"(d[25]),"+f"(d[26]),"+f"(d[27]),"+f"(d[28]),"+f"(d[29]),"+f"(d[30]),"+f"(d[31])
    : "l"(ad), "l"(bd));
  } else {
    asm volatile("{\n.reg .pred p;\nsetp.ne.b32 p, 0, 0;\n"
    "wgmma.mma_async.sync.aligned.m64n64k16.f32.bf16.bf16 {%0,%1,%2,%3,%4,%5,%6,%7,%8,%9,%10,%11,%12,%13,%14,%15,%16,%17,%18,%19,%20,%21,%22,%23,%24,%25,%26,%27,%28,%29,%30,%31}, %32, %33, p, 1, 1, 1, 1;\n}"
    : "+f"(d[0]),"+f"(d[1]),"+f"(d[2]),"+f"(d[3]),"+f"(d[4]),"+f"(d[5]),"+f"(d[6]),"+f"(d[7]),"+f"(d[8]),"+f"(d[9]),"+f"(d[10]),"+f"(d[11]),"+f"(d[12]),"+f"(d[13]),"+f"(d[14]),"+f"(d[15]),"+f"(d[16]),"+f"(d[17]),"+f"(d[18]),"+f"(d[19]),"+f"(d[20]),"+f"(d[21]),"+f"(d[22]),"+f"(d[23]),"+f"(d[24]),"+f"(d[25]),"+f"(d[26]),"+f"(d[27]),"+f"(d[28]),"+f"(d[29]),"+f"(d[30]),"+f"(d[31])
    : "l"(ad), "l"(bd));
  }
}

template<int V> struct IC { static constexpr int v = V; };
template<int I, int N, class F> __device__ __forceinline__ void sfor(F&& f) {
    if constexpr (I < N) { f(IC<I>{}); sfor<I + 1, N>(f); }
}

enum { K_QKV = 0, K_H = 1 };

struct Ctx {
    uint32_t tph;
    uint32_t tid_;
    bool pf = false;
    __device__ __forceinline__ uint32_t tid() const { uint32_t r; asm volatile("mov.u32 %0, %1;" : "=r"(r) : "r"(tid_)); return r; }
};
__device__ __forceinline__ void release_slot(const Ctx& c, int slot) { if ((c.tid() & 31) == 0) mbar_arrive(bar(B_EMPTY + slot)); }

__device__ __forceinline__ void turn_wait(const Ctx& c) { asm volatile("bar.sync %0, 256;" :: "r"(4 + (c.tid() >> 7)) : "memory"); }
__device__ __forceinline__ void turn_pass(const Ctx& c) { asm volatile("bar.arrive %0, 256;" :: "r"(5 - (c.tid() >> 7)) : "memory"); }

template<int KIND, class PART, class POST>
__device__ __forceinline__ void run_step(Ctx& c, float* acc, const uint32_t* a, PART&& part, POST&& post, bool last = false) {
    constexpr int NST = (KIND == K_QKV) ? 6 : 3;
    constexpr int KPS = 36 / NST;
    sfor<0, NST>([&](auto ST) {
        constexpr int st = decltype(ST)::v;
        constexpr int slot = st % 3;
        mbar_wait(bar(B_FULL + slot), c.tph);
        uint32_t wgo = 0;
        if constexpr (st == NST - 1) wgo = (c.tid() >> 7) * 512;
        if (KIND == K_H && c.pf) prof(44 + st * 5);
        turn_wait(c);
        if (KIND == K_H && c.pf) prof(45 + st * 5);
        wg_fence();
        sfor<0, KPS>([&](auto KK) {
            constexpr int kk = decltype(KK)::v;
            constexpr int ks = st * KPS + kk;
            constexpr int SD = ks ? 1 : 0;
            if constexpr (KIND == K_QKV) {
                constexpr uint64_t bd = mkdesc(RING + slot * SLOT + kk * 2048, 12288, 1024, 1);
                if constexpr (ks < 32) wg_rs72<SD>(acc, a + ks * 4, bd);
                else wg_ss72<SD>(acc, mkdesc(XB + (ks - 32) * 32, 16, 1024, 1) + wgo, bd);
            } else {
                constexpr uint64_t bd = mkdesc(RING + slot * SLOT + kk * 2048, 16, 1024, 1);
                if constexpr (ks < 32) wg_rs64<SD>(acc, a + ks * 4, bd);
                else wg_ss64<SD>(acc, mkdesc(XB + (ks - 32) * 32, 16, 1024, 1) + wgo, bd);
            }
        });
        wg_commit();
        if (st < NST - 1 || !last || c.tid() < 128) turn_pass(c);
        if (KIND == K_H && c.pf) prof(46 + st * 5);
        part(ST);
        if (KIND == K_H && c.pf) prof(47 + st * 5);
        wg_wait<0>();
        if (KIND == K_H && c.pf) prof(48 + st * 5);
        release_slot(c, slot);
        if constexpr (slot == 2) c.tph ^= 1;
        post(ST);
    });
    if constexpr (KIND == K_QKV) reg_fence<36>(acc); else reg_fence<32>(acc);
}

__device__ __forceinline__ float phi(float t) {
    float e = ex2(t * 1.4426950408889634f);
    return (t > 0.f ? t + 1.0f : e) + 1e-6f;
}
__device__ __forceinline__ float gelu_h(float hx) {
    float u = hx * fmaf(hx * hx, 0.2854192650f, 1.5957691216f);
    return fmaf(hx, tanh_ap(u), hx);
}

struct Params {
    const __nv_bfloat16* x;
    const __nv_bfloat16* wqkv;
    const __nv_bfloat16* wo;
    const __nv_bfloat16* w1;
    const __nv_bfloat16* b1;
    const __nv_bfloat16* w2;
    const __nv_bfloat16* b2;
    __nv_bfloat16* out;
};

__global__ void __launch_bounds__(384, 1)
fused_kernel(const __grid_constant__ CUtensorMap tm_x, const __grid_constant__ CUtensorMap tm_w1,
             const __grid_constant__ CUtensorMap tm_w2, const __grid_constant__ CUtensorMap tm_wo,
             const __grid_constant__ CUtensorMap tm_o, const __grid_constant__ CUtensorMap tm_qkv,
             const __grid_constant__ CUtensorMap tm_qkve, const __grid_constant__ CUtensorMap tm_ost, const Params p) {
    extern __shared__ __align__(1024) unsigned char smem_raw[];
    const int tid = threadIdx.x;
    const int bid = blockIdx.x;
    const bool is_main = bid < NMAIN;
    const int j = bid & 7;
    const int m = bid >> 3;

    if (tid == 0) {
        if ((uint32_t)__cvta_generic_to_shared(smem_raw) != SB) __trap();
        for (int i = 0; i < 3; i++) {
            mbar_init(bar(B_FULL + i), 1); mbar_init(bar(B_EMPTY + i), 8);
            mbar_init(bar(B_XFULL + i), 1);
        }
        mbar_init(bar(B_KVB), 2); mbar_init(bar(B_INIT), 1);
        mbar_init(bar(B_OFULL), 1); mbar_init(bar(B_O8FULL), 1); mbar_init(bar(B_OFREE), 8); mbar_init(bar(B_O8FREE), 8);
        asm volatile("fence.mbarrier_init.release.cluster;" ::: "memory");
    }
    if (tid == 256) { asm volatile("prefetch.tensormap [%0];" :: "l"(&tm_x) : "memory"); asm volatile("prefetch.tensormap [%0];" :: "l"(&tm_qkv) : "memory"); asm volatile("prefetch.tensormap [%0];" :: "l"(&tm_qkve) : "memory"); }
    if (tid >= 40 && tid < 48) sts32(EVC + (tid - 40) * 4, 0);
    if (tid == 48) sts32(EPO + 4, 0);
    __syncthreads();

    if (tid >= 256) {
        asm volatile("setmaxnreg.dec.sync.aligned.u32 24;");
        const int hw = (tid >> 5) - 8, lane = tid & 31;
        uint32_t epoch = 0;
        if (hw > 0) {
            epoch = g_epoch[bid];
            if (hw == 3) {
                if (lane == 0) sts32(EPO, epoch);
                if (is_main) {
                    #pragma unroll 1
                    for (int i = lane; i < 288; i += 32) {
                        uint32_t v = *reinterpret_cast<const uint32_t*>(p.b1 + j * 576 + 2 * i);
                        sts32(B1S + 8 * i, __float_as_uint(0.5f * bf_lo(v))); sts32(B1S + 8 * i + 4, __float_as_uint(0.5f * bf_hi(v)));
                    }
                }
                uint32_t v = *reinterpret_cast<const uint32_t*>(p.b2 + (is_main ? j : 8) * 64 + 2 * lane);
                sts32(B2S + 8 * lane, v << 16); sts32(B2S + 8 * lane + 4, v & 0xffff0000u);
                __syncwarp();
                if (lane == 0) mbar_arrive(bar(B_INIT));
            }
        }
        const uint32_t par = epoch & 1;
        if (hw == 0) {
            if (lane == 0) {
                uint32_t n = 0;
                if (is_main) {
                    #pragma unroll 1
                    for (int kb = 0; kb < 9; kb++) {
                        if (kb % 3 == 0) mbar_expect_tx(bar(B_XFULL + kb / 3), 49152);
                        tma_2d(HA + kb * 16384, &tm_x, bar(B_XFULL + kb / 3), kb * 64, m * 128);
                    }
                    #pragma unroll 1
                    for (int u = 0; u < 18; u++) {
                        const int st = u % 3, step = u / 6;
                        const int col = ((step == 2) ? 0 : (step + 1) * 576) + j * 72, row = (u % 6) * 96;
                        mbar_wait(bar(B_EMPTY + st), (n & 1) ^ 1);
                        mbar_expect_tx(bar(B_FULL + st), 96 * 144);
                        tma_2d(RING + st * SLOT, &tm_qkv, bar(B_FULL + st), col, row);
                        tma_2d(RING + st * SLOT + 12288, &tm_qkve, bar(B_FULL + st), col + 64, row);
                        if (st == 2) n++;
                    }
                }
                const int nsteps = is_main ? 19 : 1;
                #pragma unroll 1
                for (int s = 0; s < nsteps; s++, n++) {
                    const CUtensorMap* tm; int col, row;
                    if (!is_main) { tm = &tm_wo; col = 512; row = 0; }
                    else if (s < 9) { tm = &tm_w1; col = j * 576 + s * 64; row = 0; }
                    else if (s < 18) { tm = &tm_w2; col = (s == 9) ? 512 : (((j + s - 9) & 7) * 64); row = j * 576; }
                    else { tm = &tm_wo; col = j * 64; row = 0; }
                    #pragma unroll 1
                    for (int st = 0; st < 3; st++) {
                        mbar_wait(bar(B_EMPTY + st), (n & 1) ^ 1);
                        mbar_expect_tx(bar(B_FULL + st), SLOT);
                        tma_2d(RING + st * SLOT, tm, bar(B_FULL + st), col, row + st * 192);
                    }
                }
            }
        } else {
            if (is_main) {
                const int t = tid - 288;
                __nanosleep(PF0_NS);
                #pragma unroll 1
                for (int i = t; i < 36 * 6; i += 96) {
                    int r = i / 6, q = i - r * 6;
                    prefetch_l2(reinterpret_cast<const char*>(p.wqkv) + (36 * m + r) * 3456 + (q >> 1) * 1152 + j * 144 + (q & 1) * 128);
                }
                __nanosleep(PF1_NS);
                #pragma unroll 1
                for (int i = t; i < 36 * 9; i += 96) {
                    int r = i / 9, q = i - r * 9;
                    prefetch_l2(reinterpret_cast<const char*>(p.w1) + (36 * m + r) * 9216 + j * 1152 + q * 128);
                    __nanosleep(PF3_NS);
                }
                __nanosleep(PF2_NS);
                #pragma unroll 1
                for (int i = t; i < 36 * 9; i += 96)
                    prefetch_l2(reinterpret_cast<const char*>(p.w2) + (576 * j + 36 * m) * 1152 + i * 128);
                if (t < 41 && (bid * 41 + t) < 5184) prefetch_l2(reinterpret_cast<const char*>(p.wo) + (bid * 41 + t) * 128);
                if (hw != 2) {
                    if (lane == 0) wait_cnt(cnt_kv(j), (epoch + 1) * 16);
                    __syncwarp();
                    const float4* kv = reinterpret_cast<const float4*>(g_kv + (par * 8 + j) * 1440);
                    #pragma unroll 2
                    for (int i = lane + (hw == 1 ? 0 : 32); i < 360; i += 64) {
                        const float4 v = __ldcg(kv + i);
                        const int d = i / 5, e = (i - d * 5) * 4, h = d / 18;
                        const uint32_t base = KVB + (d >> 3) * 128 + (d & 7) * 16;
                        const int n0 = 8 + h * 18 + e;
                        sts32(base + (n0 >> 3) * 1280 + (n0 & 7) * 2, pack_bf16(v.x, v.y));
                        if (e < 16) sts32(base + ((n0 + 2) >> 3) * 1280 + ((n0 + 2) & 7) * 2, pack_bf16(v.z, v.w));
                        else asm volatile("st.shared.u16 [%0], %1;" :: "r"(base + h * 2), "h"((unsigned short)pack_bf16(v.z, 0.f)) : "memory");
                    }
                    fence_async_smem();
                    __syncwarp();
                    if (lane == 0) mbar_arrive(bar(B_KVB));
                }
            }
            if (hw == 1) {
                if (lane == 0) {
                    const int nit = is_main ? 1 : 4;
                    for (int it = 0; it < nit; it++) {
                        const int mt = is_main ? m : ((bid - NMAIN) * 4 + it);
                        const bool wf = is_main || it > 0;
                        const uint32_t fp = is_main ? 0 : ((it - 1) & 1);
                        wait_cnt(cnt_o(mt), (epoch + 1) * 8);
                        fence_async_all();
                        if (wf) mbar_wait(bar(B_OFREE), fp);
                        mbar_expect_tx(bar(B_OFULL), 131072);
                        #pragma unroll 1
                        for (int kb = 0; kb < 8; kb++) tma_2d(HA + kb * 16384, &tm_o, bar(B_OFULL), kb * 64, mt * 128);
                        if (wf) mbar_wait(bar(B_O8FREE), fp);
                        mbar_expect_tx(bar(B_O8FULL), 16384);
                        tma_2d(XB, &tm_o, bar(B_O8FULL), 512, mt * 128);
                    }
                    if (is_main) { wait_cnt(cnt_y(m, j), (epoch + 1) * 7); asm volatile("st.release.cta.shared.u32 [%0], %1;" :: "r"(EPO + 4), "r"(1) : "memory"); }
                }
            } else if (hw == 2) {
                if (!is_main) {
                    if (lane == 0) {
                        #pragma unroll 1
                        for (int it = 0; it < 4; it++) {
                            wait_cnt(cnt_y((bid - NMAIN) * 4 + it, 8), (epoch + 1) * 8);
                            asm volatile("st.release.cta.shared.u32 [%0], %1;" :: "r"(EPO + 4), "r"(it + 1) : "memory");
                        }
                    }
                } else {
                    #pragma unroll 1
                    for (int e = 0; e < 10; e++) {
                        int spin = 0;
                        while (true) {
                            uint32_t v;
                            asm volatile("ld.acquire.cta.shared.u32 %0, [%1];" : "=r"(v) : "r"(EVC + (lane & 7) * 4) : "memory");
                            if (__all_sync(0xffffffffu, v > (uint32_t)e)) break;
                            if (++spin > 20000000) __trap();
                            __nanosleep(SIG_NS);
                        }
                        if (lane == 0) {
                            unsigned int* cp = (e == 0) ? cnt_kv(j) : (e == 1) ? cnt_o(m) : cnt_y(m, e == 2 ? 8 : ((j + e - 2) & 7));
                            if (e == 1) fence_async_all();
                            __threadfence();
                            asm volatile("red.relaxed.gpu.global.add.u32 [%0], 1;" :: "l"(cp) : "memory");
                        }
                        __syncwarp();
                    }
                }
            } else {
                {
                    const int t0 = is_main ? (m * 9 + j) : ((bid - NMAIN) * 4 * 9 + 8);
                    const int nt = is_main ? 1 : 4;
                    for (int t = 0; t < nt; t++) {
                        uint4* z = reinterpret_cast<uint4*>(g_yacc + (size_t)((par ^ 1) * 144 + t0 + t * 9) * YT_BYTES);
                        for (int i = lane; i < YT_BYTES / 16; i += 32) z[i] = make_uint4(0, 0, 0, 0);
                    }
                    if (is_main && m == 0) {
                        float* z = g_kv + ((par ^ 1) * 8 + j) * 1440;
                        for (int i = lane; i < 1440; i += 32) z[i] = 0.f;
                    }
                }
            }
        }
    } else {
        asm volatile("setmaxnreg.inc.sync.aligned.u32 240;");
        prof(0);
        Ctx c; c.tph = 0; c.tid_ = v_tid();
        float hc[32], pv[36];
        if (tid >> 7) turn_pass(c);
        auto event = [&](uint32_t ev) {
            __syncwarp();
            if (((c.tid() & 31) == 0)) asm volatile("st.release.cta.shared.u32 [%0], %1;" :: "r"(EVC + (c.tid() >> 3)), "r"(ev) : "memory");
        };
        auto warp_arrive = [&](uint32_t b) { __syncwarp(); if (((c.tid() & 31) == 0)) mbar_arrive(b); };

        auto lrow_off = [&]() { uint32_t t_ = c.tid(); return HA + ((t_ >> 5) * 16 + (t_ & 15)) * 128 + ((((t_ >> 4) & 1) ^ (t_ & 7)) << 4); };
        auto tail_off = [&]() { uint32_t t_ = c.tid(), g = (t_ >> 2) & 7; return XB + ((t_ >> 5) * 16 + g) * 128 + (g << 4) + (t_ & 3) * 4; };
        if (is_main) {
            uint32_t a[128];
            float rs0, rs1;
            {
                uint32_t tl[16];
                const uint32_t lrow = lrow_off();
                float cs[4][4], sq[8];
                #pragma unroll
                for (int i = 0; i < 4; i++) {
                    #pragma unroll
                    for (int k = 0; k < 4; k++) { cs[i][k] = 0.f; sq[k] = 0.f; sq[k + 4] = 0.f; }
                }
                uint32_t s00 = 0, s11 = 0;
                auto frag = [&](auto KS) -> uint32_t* { constexpr int ks = decltype(KS)::v; return (ks < 32) ? (a + (ks & 31) * 4) : (tl + (ks & 3) * 4); };
                auto sqacc = [&](auto KS) {
                    const uint32_t* f = frag(KS);
                    #pragma unroll
                    for (int r = 0; r < 4; r++) {
                        const uint32_t w = sub_bf16x2(f[r], (r & 1) ? s11 : s00);
                        const float lo = bf_lo(w), hi = bf_hi(w);
                        sq[r] = fmaf(lo, lo, sq[r]); sq[r + 4] = fmaf(hi, hi, sq[r + 4]);
                    }
                };
                sfor<0, 3>([&](auto G) {
                    constexpr int g = decltype(G)::v;
                    mbar_wait(bar(B_XFULL + g), 0);
                    prof(37 + g);
                    sfor<12 * g, 12 * g + 12>([&](auto KS) {
                        constexpr int ks = decltype(KS)::v;
                        ldsm4((lrow ^ ((ks % 4) << 5)) + (ks / 4) * 16384, frag(KS));
                    });
                    sfor<12 * g, 12 * g + 12>([&](auto KS) { mma_ones(cs[decltype(KS)::v & 3], frag(KS)); });
                    if constexpr (g == 0) {
                        const float t0 = (cs[0][0] + cs[1][0] + cs[2][0] + cs[3][0]) * (1.0f / 192.0f), t1 = (cs[0][2] + cs[1][2] + cs[2][2] + cs[3][2]) * (1.0f / 192.0f);
                        s00 = pack_bf16(t0, t0); s11 = pack_bf16(t1, t1);
                    }
                    sfor<12 * g, 12 * g + 12>(sqacc);
                });
                prof(2);
                const float mean0 = (cs[0][0] + cs[1][0] + cs[2][0] + cs[3][0]) * (1.0f / 576.0f), mean1 = (cs[0][2] + cs[1][2] + cs[2][2] + cs[3][2]) * (1.0f / 576.0f);
                const uint32_t m00 = pack_bf16(mean0, mean0), m11 = pack_bf16(mean1, mean1);
                const uint32_t tb = tail_off();
                #pragma unroll
                for (int i = 0; i < 16; i++) sts32((tb ^ ((i >> 1) << 4)) + (i & 1) * 1024, sub_bf16x2(tl[i], (i & 1) ? m11 : m00));
                fence_async_smem();
                #pragma unroll
                for (int i = 0; i < 128; i++) a[i] = sub_bf16x2(a[i], (i & 1) ? m11 : m00);
                {
                    rs0 = (sq[0] + sq[2]) + (sq[4] + sq[6]); rs1 = (sq[1] + sq[3]) + (sq[5] + sq[7]);
                    rs0 += __shfl_xor_sync(0xffffffffu, rs0, 1); rs1 += __shfl_xor_sync(0xffffffffu, rs1, 1);
                    rs0 += __shfl_xor_sync(0xffffffffu, rs0, 2); rs1 += __shfl_xor_sync(0xffffffffu, rs1, 2);
                    const float d0 = mean0 - bf_lo(s00), d1 = mean1 - bf_lo(s11);
                    rs0 = rsqrtf(fmaxf(fmaf(rs0, 1.0f / 576.0f, -d0 * d0), 0.f) + 1e-5f);
                    rs1 = rsqrtf(fmaxf(fmaf(rs1, 1.0f / 576.0f, -d1 * d1), 0.f) + 1e-5f);
                }
                named_bar(1, 256);
            }
            prof(3);
            auto cm_off = [&]() { uint32_t t_ = c.tid(); return (t_ >> 5) * 256 + (t_ & 31) * 4; };
            {
                float qc[36];
                #pragma unroll
                for (int i = 0; i < 36; i++) { qc[i] = 0.f; pv[i] = 0.f; }
                #pragma unroll 1
                for (int s = 0; s < 3; s++) {
                    c.pf = (s == 0);
                    run_step<K_QKV>(c, qc, a, [&](auto ST) {
                        constexpr int st = decltype(ST)::v;
                        if (s > 0) {
                            const uint32_t cm = cm_off();
                            sfor<0, 9>([&](auto B) {
                                constexpr int b = decltype(B)::v;
                                if constexpr ((b * 6) / 9 == st) {
                                    const float v0 = pv[4 * b] * rs0, v1 = pv[4 * b + 1] * rs0, v2 = pv[4 * b + 2] * rs1, v3 = pv[4 * b + 3] * rs1;
                                    if (s == 1) {
                                        sts32(PKT + b * 2048 + cm, pack_bf16(phi(v0), phi(v1)));
                                        sts32(PKT + b * 2048 + cm + 128, pack_bf16(phi(v2), phi(v3)));
                                    } else {
                                        const uint32_t w0 = pack_bf16(v0, v1), w1 = pack_bf16(v2, v3);
                                        if constexpr (b <= 4) { sts32(VT + b * 2048 + cm, w0); sts32(VT + b * 2048 + cm + 128, w1); }
                                        if constexpr (b >= 4) { sts32(VT + (b + 2) * 2048 + cm, w0); sts32(VT + (b + 2) * 2048 + cm + 128, w1); }
                                        if constexpr (b == 0) {
                                            const uint32_t one = (cm & 12) ? 0u : 0x00003F80u;
                                            sts32(VT + 5 * 2048 + cm, one); sts32(VT + 5 * 2048 + cm + 128, one);
                                        }
                                        if constexpr (b == 8) {
                                            const uint32_t z = KVB + c.tid() * 16;
                                            sts128(z, 0, 0, 0, 0); sts128(z + 4096, 0, 0, 0, 0); sts128(z + 8192, 0, 0, 0, 0);
                                            if (z < KVB + 512) sts128(z + 12288, 0, 0, 0, 0);
                                            fence_async_smem();
                                        }
                                    }
                                }
                            });
                        }
                    }, [](auto) {});
                    reg_copy<36>(pv, qc);
                    prof(4 + s);
                }
            }
            {
                #pragma unroll
                for (int i = 0; i < 32; i++) hc[i] = 0.f;
                named_bar(1, 256);
                const uint32_t wgo = ((c.tid() >> 7) * 512);
                wg_fence();
                sfor<0, 8>([&](auto KS) {
                    constexpr int ks = decltype(KS)::v;
                    wg_tt64<(ks ? 1 : 0)>(hc, mkdesc(PKT + ks * 256, 128, 2048, 0) + wgo,
                                          mkdesc(VT + ks * 256, 128, 2048, 0) + wgo + (wgo >> 2));
                });
                wg_commit();
                const uint32_t pq = PQT + cm_off() + ((c.tid() >> 7) * 512) * 16;
                sfor<0, 9>([&](auto B) {
                    constexpr int b = decltype(B)::v;
                    sts32(pq + b * 1024, pack_bf16(phi(pv[4 * b] * rs0), phi(pv[4 * b + 1] * rs0)));
                    sts32(pq + b * 1024 + 128, pack_bf16(phi(pv[4 * b + 2] * rs1), phi(pv[4 * b + 3] * rs1)));
                });
                fence_async_smem();
                wg_wait<0>();
                reg_fence<32>(hc);
                reg_copy<24>(pv, hc);
            }
            prof(7);
            rs0 *= 0.5f; rs1 *= 0.5f;
            mbar_wait(bar(B_INIT), 0);
            auto gelun = [&](auto B0, auto B1, uint32_t bofs, uint32_t* w) {
                constexpr int b0 = decltype(B0)::v, nb = decltype(B1)::v - b0;
                float2 bv[nb];
                #pragma unroll
                for (int i = 0; i < nb; i++) bv[i] = lds64f(bofs + (b0 + i) * 32);
                #pragma unroll
                for (int i = 0; i < nb; i++) {
                    const int b = b0 + i;
                    w[2 * i]     = pack_bf16(gelu_h(fmaf(pv[4 * b], rs0, bv[i].x)), gelu_h(fmaf(pv[4 * b + 1], rs0, bv[i].y)));
                    w[2 * i + 1] = pack_bf16(gelu_h(fmaf(pv[4 * b + 2], rs1, bv[i].x)), gelu_h(fmaf(pv[4 * b + 3], rs1, bv[i].y)));
                }
            };
            auto spill_off = [&]() { uint32_t t_ = c.tid(); return HA + (t_ >> 7) * 8192 + (t_ & 127) * 8; };
            auto reload = [&](auto S0, auto S1) {
                const uint32_t spill = spill_off();
                sfor<decltype(S0)::v * 8, decltype(S1)::v * 8>([&](auto Q) {
                    constexpr int q = decltype(Q)::v;
                    lds64(spill + (q / 8) * 16384 + (q % 8) * 1024, a + q * 2);
                });
            };
            #pragma unroll 1
            for (int idx = 0; idx < 18; idx++) {
                run_step<K_H>(c, hc, a, [&](auto ST) {
                    constexpr int st = decltype(ST)::v;
                    if (idx >= 10) {
                        if constexpr (st < 2) {
                            const uint32_t b_ = v_bid();
                            const uint32_t chunk = (idx == 10) ? 8 : ((b_ + idx - 10) & 7);
                            unsigned char* yp = g_yacc + ((v_epoch() & 1) * 144 + (b_ >> 3) * 9 + chunk) * YT_BYTES + c.tid() * 16;
                            sfor<2 * st, 2 * st + 2>([&](auto Q) {
                                constexpr int q = decltype(Q)::v;
                                asm volatile("red.global.add.noftz.v4.bf16x2 [%0], {%1,%2,%3,%4};" :: "l"(yp + q * 4096),
                                             "r"(pack_bf16(pv[8 * q], pv[8 * q + 1])), "r"(pack_bf16(pv[8 * q + 2], pv[8 * q + 3])),
                                             "r"(pack_bf16(pv[8 * q + 4], pv[8 * q + 5])), "r"(pack_bf16(pv[8 * q + 6], pv[8 * q + 7])) : "memory");
                            });
                            if constexpr (st == 1) event(idx - 7);
                        }
                    } else if (idx >= 1) {
                        const uint32_t bofs = B1S + (idx - 1) * 256 + (c.tid() & 3) * 8;
                        if (idx < 9) {
                            if constexpr (st == 0) {
                                if (idx == OSTEP_AT + 1) {
                                    if ((c.tid() & 31) == 0) asm volatile("cp.async.bulk.wait_group 0;" ::: "memory");
                                    event(2);
                                }
                            }
                            const uint32_t spill = spill_off() + (idx - 1) * 16384;
                            constexpr int b0 = st * 3, b1 = (st == 2 ? 8 : st * 3 + 3);
                            uint32_t w[6];
                            gelun(IC<b0>{}, IC<b1>{}, bofs, w);
                            #pragma unroll
                            for (int b = b0; b < b1; b++) sts64(spill + b * 1024, w[2 * (b - b0)], w[2 * (b - b0) + 1]);
                        } else {
                            if constexpr (st < 2) {
                                const uint32_t tb = tail_off();
                                uint32_t w[8];
                                gelun(IC<st * 4>{}, IC<st * 4 + 4>{}, bofs, w);
                                #pragma unroll
                                for (int i = 0; i < 4; i++) { sts32(tb ^ ((st * 4 + i) << 4), w[2 * i]); sts32((tb ^ ((st * 4 + i) << 4)) + 1024, w[2 * i + 1]); }
                            }
                            if constexpr (st == 1) { fence_async_smem(); named_bar(2 + (c.tid() >> 7), 128); }
                        }
                    } else {
                        if constexpr (st < 2) {
                            constexpr int hf = st;
                            const int t_ = c.tid(), wg = t_ >> 7, t = t_ & 3;
                            float* dst = g_kv + ((v_epoch() & 1) * 8 + (v_bid() & 7)) * 1440;
                            const int d = wg * 32 + ((t_ >> 5) & 3) * 16 + ((t_ >> 2) & 7) + hf * 8;
                            const bool dv = wg ? (d >= 36 && d < 72) : (d < 36);
                            const int e00 = wg * 24 + 2 * t - (d / 18) * 18;
                            float* dp = dst + d * 20 + e00;
                            #pragma unroll
                            for (int i = 0; i < 6; i++) {
                                const int e = e00 + i * 8;
                                const bool blk = wg ? (i >= 1) : (i <= 4);
                                if (dv && blk && e >= 0 && e < 18)
                                    asm volatile("red.global.add.v2.f32 [%0], {%1,%2};" :: "l"(dp + i * 8), "f"(pv[4 * i + 2 * hf]), "f"(pv[4 * i + 2 * hf + 1]) : "memory");
                            }
                            if (dv && t == 0) atomicAdd(dst + d * 20 + 18, wg ? pv[2 * hf] : pv[20 + 2 * hf]);
                            if constexpr (st == 1) event(1);
                        }
                    }
                }, [&](auto ST) {
                    constexpr int st = decltype(ST)::v;
                    if (idx == 8) {
                        reload(IC<3 * st>{}, IC<(st == 2 ? 8 : 3 * st + 3)>{});
                        if constexpr (st == 2) warp_arrive(bar(B_OFREE));
                    }
                });
                reg_copy<32>(pv, hc);
                prof(8 + idx);
                if (idx == OSTEP_AT) {
                    mbar_wait(bar(B_KVB), 0);
                    prof(34);
                    const uint32_t pqo = (c.tid() >> 7) * 576;
                    const int t_ = c.tid(), b_ = v_bid(), t = t_ & 3, l4 = t_ & 28;
                    const uint32_t op = OST + ((t_ >> 5) * 16 + ((t_ >> 2) & 7)) * 144 + t * 4;
                    float r3[2];
                    sfor<0, 2>([&](auto PS) {
                        constexpr int ps = decltype(PS)::v;
                        wg_fence();
                        sfor<0, 5>([&](auto KS) {
                            constexpr int ks = decltype(KS)::v;
                            wg_ss64<(ks ? 1 : 0)>(hc, mkdesc(PQT + ks * 2048, ks == 4 ? 0 : 1024, 128, 0) + pqo, mkdesc(KVB + ps * 8 * 1280 + ks * 256, 128, 1280, 0));
                        });
                        wg_commit();
                        wg_wait<0>();
                        reg_fence<32>(hc);
                        #pragma unroll
                        for (int hf = 0; hf < 2; hf++) {
                            if constexpr (ps == 0) {
                                float r[4];
                                r[0] = rcp(__shfl_sync(0xffffffffu, hc[2 * hf], l4) + 1e-6f);
                                r[1] = rcp(__shfl_sync(0xffffffffu, hc[1 + 2 * hf], l4) + 1e-6f);
                                r[2] = rcp(__shfl_sync(0xffffffffu, hc[2 * hf], l4 + 1) + 1e-6f);
                                r[3] = rcp(__shfl_sync(0xffffffffu, hc[1 + 2 * hf], l4 + 1) + 1e-6f);
                                r3[hf] = r[3];
                                #pragma unroll
                                for (int i = 0; i < 7; i++) {
                                    float rr = (i < 2) ? r[0] : (i == 2) ? (t < 1 ? r[0] : r[1]) : (i == 3) ? r[1] : (i == 4) ? (t < 2 ? r[1] : r[2])
                                             : (i == 5) ? r[2] : (t < 3 ? r[2] : r[3]);
                                    sts32(op + hf * 8 * 144 + i * 16, pack_bf16(hc[4 * i + 4 + 2 * hf] * rr, hc[4 * i + 5 + 2 * hf] * rr));
                                }
                            } else {
                                #pragma unroll
                                for (int i = 0; i < 2; i++)
                                    sts32(op + hf * 8 * 144 + 112 + i * 16, pack_bf16(hc[4 * i + 2 * hf] * r3[hf], hc[4 * i + 1 + 2 * hf] * r3[hf]));
                            }
                        }
                    });
                    fence_async_smem();
                    __syncwarp();
                    if ((t_ & 31) == 0) {
                        asm volatile("cp.async.bulk.tensor.2d.global.shared::cta.bulk_group [%0, {%2, %3}], [%1];"
                                     :: "l"(&tm_ost), "r"(OST + (t_ >> 5) * 2304), "r"((b_ & 7) * 72), "r"((b_ >> 3) * 128 + (t_ >> 5) * 16) : "memory");
                        asm volatile("cp.async.bulk.commit_group;" ::: "memory");
                    }
                }
            }
        }
        if (is_main) warp_arrive(bar(B_O8FREE));
        else {
            mbar_wait(bar(B_INIT), 0);
            #pragma unroll
            for (int i = 0; i < 32; i++) { asm volatile("mov.b32 %0, 0;" : "=f"(hc[i])); asm volatile("mov.b32 %0, 0;" : "=f"(pv[i])); }
        }
        auto add_b2 = [&]() {
            #pragma unroll
            for (int b = 0; b < 8; b++) {
                float2 bv = lds64f(B2S + b * 32 + (c.tid() & 3) * 8);
                pv[4 * b] += bv.x; pv[4 * b + 1] += bv.y; pv[4 * b + 2] += bv.x; pv[4 * b + 3] += bv.y;
            }
        };
        auto load_xy = [&](int ftile, int nrdy, uint32_t* xr, uint32_t* yv) {
            const int mt = ftile / 9, ch = ftile - mt * 9;
            const uint32_t t_ = c.tid();
            const __nv_bfloat16* xp = p.x + (size_t)(mt * 128 + (t_ >> 5) * 16 + ((t_ >> 2) & 7)) * DM + ch * 64 + 2 * (t_ & 3);
            #pragma unroll
            for (int i = 0; i < 8; i++) {
                asm volatile("ld.global.nc.u32 %0, [%1];" : "=r"(xr[2 * i]) : "l"(xp + i * 8));
                asm volatile("ld.global.nc.u32 %0, [%1];" : "=r"(xr[2 * i + 1]) : "l"(xp + 8 * DM + i * 8));
            }
            prof(26);
            smem_wait_gt(EPO + 4, nrdy);
            prof(27);
            const unsigned char* yp = g_yacc + ((v_epoch() & 1) * 144 + ftile) * YT_BYTES + t_ * 16;
            #pragma unroll
            for (int q = 0; q < YT_BYTES / 4096; q++)
                asm volatile("ld.global.cg.v4.u32 {%0,%1,%2,%3}, [%4];" : "=r"(yv[4 * q]), "=r"(yv[4 * q + 1]), "=r"(yv[4 * q + 2]), "=r"(yv[4 * q + 3]) : "l"(yp + q * 4096) : "memory");
        };
        auto gate = [&](const uint32_t* yv) {
            #pragma unroll
            for (int i = 0; i < 16; i++) { pv[2 * i] += bf_lo(yv[i]); pv[2 * i + 1] += bf_hi(yv[i]); }
            #pragma unroll
            for (int i = 0; i < 32; i++) { const float h = 0.5f * pv[i]; pv[i] = fmaf(h, tanh_ap(h), h); }
        };
        auto store_out = [&](int ftile, const uint32_t* xr) {
            const int mt = ftile / 9, ch = ftile - mt * 9;
            const uint32_t t_ = c.tid();
            __nv_bfloat16* op = p.out + (size_t)(mt * 128 + (t_ >> 5) * 16 + ((t_ >> 2) & 7)) * DM + ch * 64 + 2 * (t_ & 3);
            #pragma unroll
            for (int b = 0; b < 8; b++) {
                *reinterpret_cast<uint32_t*>(op + b * 8) =
                    pack_bf16(fmaf(hc[4 * b], pv[4 * b], bf_lo(xr[2 * b])), fmaf(hc[4 * b + 1], pv[4 * b + 1], bf_hi(xr[2 * b])));
                *reinterpret_cast<uint32_t*>(op + 8 * DM + b * 8) =
                    pack_bf16(fmaf(hc[4 * b + 2], pv[4 * b + 2], bf_lo(xr[2 * b + 1])), fmaf(hc[4 * b + 3], pv[4 * b + 3], bf_hi(xr[2 * b + 1])));
            }
        };
        const int njob = is_main ? 1 : 4;
        #pragma unroll 1
        for (int job = 0; job < njob; job++) {
            const uint32_t jpar = job & 1;
            const uint32_t b_ = v_bid();
            const bool mainf = b_ < NMAIN;
            const int ftile = (b_ >> 3) * 9 + (b_ & 7);
            uint32_t oa[128];
            {
                mbar_wait(bar(B_OFULL), jpar);
                const uint32_t lrow = lrow_off();
                sfor<0, 32>([&](auto KS) {
                    constexpr int ks = decltype(KS)::v;
                    ldsm4((lrow ^ ((ks % 4) << 5)) + (ks / 4) * 16384, oa + ks * 4);
                });
                warp_arrive(bar(B_OFREE));
                if (job) c.tph ^= 1;
            }
            c.pf = false;
            run_step<K_H>(c, hc, oa, [&](auto ST) {
                constexpr int st = decltype(ST)::v;
                if (mainf) {
                    if constexpr (st == 0) add_b2();
                    else if constexpr (st == 1) load_xy(ftile, 0, oa, oa + 16);
                    else { prof(28); gate(oa + 16); prof(29); }
                }
                if constexpr (st == 1) mbar_wait(bar(B_O8FULL), jpar);
            }, [](auto) {}, job == njob - 1);
            prof(30);
            if (mainf) {
                store_out(ftile, oa);
            } else {
                warp_arrive(bar(B_O8FREE));
                uint4* sp = reinterpret_cast<uint4*>(g_s8) + ((b_ - NMAIN) * 4 + job) * 1024 + c.tid();
                #pragma unroll
                for (int q = 0; q < 4; q++)
                    sp[q * 256] = make_uint4(pack_bf16(hc[8 * q], hc[8 * q + 1]), pack_bf16(hc[8 * q + 2], hc[8 * q + 3]),
                                             pack_bf16(hc[8 * q + 4], hc[8 * q + 5]), pack_bf16(hc[8 * q + 6], hc[8 * q + 7]));
                prof(8 + job);
            }
        }
        if (!is_main) {
            #pragma unroll 1
            for (int job = 0; job < 4; job++) {
                const int tile = (v_bid() - NMAIN) * 4 + job;
                uint32_t xr[16], yv[YT_BYTES / 1024];
                const uint4* sp = reinterpret_cast<const uint4*>(g_s8) + tile * 1024 + c.tid();
                #pragma unroll
                for (int q = 0; q < 4; q++) {
                    const uint4 u = __ldcg(sp + q * 256);
                    hc[8 * q] = bf_lo(u.x); hc[8 * q + 1] = bf_hi(u.x); hc[8 * q + 2] = bf_lo(u.y); hc[8 * q + 3] = bf_hi(u.y);
                    hc[8 * q + 4] = bf_lo(u.z); hc[8 * q + 5] = bf_hi(u.z); hc[8 * q + 6] = bf_lo(u.w); hc[8 * q + 7] = bf_hi(u.w);
                }
                #pragma unroll
                for (int i = 0; i < 32; i++) pv[i] = 0.f;
                add_b2();
                load_xy(tile * 9 + 8, job, xr, yv);
                gate(yv);
                store_out(tile * 9 + 8, xr);
                prof(12 + job);
            }
        }
        prof(40);
        if (c.tid() == 0) g_epoch[v_bid()] = v_epoch() + 1;
    }
}

typedef CUresult (*EncodeFn)(CUtensorMap*, CUtensorMapDataType, cuuint32_t, void*, const cuuint64_t*, const cuuint64_t*,
                             const cuuint32_t*, const cuuint32_t*, CUtensorMapInterleave, CUtensorMapSwizzle,
                             CUtensorMapL2promotion, CUtensorMapFloatOOBfill);

void make_map(EncodeFn enc, CUtensorMap* tm, const void* base, int rows, int cols, int box_rows, int box_cols = 64, bool swz = true) {
    cuuint64_t gdim[2] = {(cuuint64_t)cols, (cuuint64_t)rows};
    cuuint64_t gstr[1] = {(cuuint64_t)cols * 2};
    cuuint32_t box[2] = {(cuuint32_t)box_cols, (cuuint32_t)box_rows};
    cuuint32_t estr[2] = {1, 1};
    enc(tm, CU_TENSOR_MAP_DATA_TYPE_BFLOAT16, 2, const_cast<void*>(base), gdim, gstr, box, estr, CU_TENSOR_MAP_INTERLEAVE_NONE,
        swz ? CU_TENSOR_MAP_SWIZZLE_128B : CU_TENSOR_MAP_SWIZZLE_NONE, CU_TENSOR_MAP_L2_PROMOTION_L2_128B, CU_TENSOR_MAP_FLOAT_OOB_FILL_NONE);
}

}

extern "C" void kernel_launch(void* const* d_in, const int* in_sizes, int n_in, void* d_out, int out_size) {
    static EncodeFn enc = nullptr;
    static void* o_ptr = nullptr;
    if (!enc) {
        void* fn = nullptr;
        cudaDriverEntryPointQueryResult qr;
        cudaGetDriverEntryPoint("cuTensorMapEncodeTiled", &fn, cudaEnableDefault, &qr);
        enc = (EncodeFn)fn;
        cudaGetSymbolAddress(&o_ptr, g_o);
        cudaFuncSetAttribute(fused_kernel, cudaFuncAttributeMaxDynamicSharedMemorySize, SMEM_BYTES);
    }
    Params p;
    p.x = (const __nv_bfloat16*)d_in[0];
    p.wqkv = (const __nv_bfloat16*)d_in[1];
    p.wo = (const __nv_bfloat16*)d_in[2];
    p.w1 = (const __nv_bfloat16*)d_in[4];
    p.b1 = (const __nv_bfloat16*)d_in[5];
    p.w2 = (const __nv_bfloat16*)d_in[6];
    p.b2 = (const __nv_bfloat16*)d_in[7];
    p.out = (__nv_bfloat16*)d_out;
    CUtensorMap tm_x, tm_w1, tm_w2, tm_wo, tm_o, tm_qkv, tm_qkve, tm_ost;
    make_map(enc, &tm_ost, o_ptr, SEQ, DM, 16, 72, false);
    make_map(enc, &tm_qkv, p.wqkv, DM, 3 * DM, 96);
    make_map(enc, &tm_qkve, p.wqkv, DM, 3 * DM, 96, 8);
    make_map(enc, &tm_x, p.x, SEQ, DM, 128);
    make_map(enc, &tm_w1, p.w1, DM, FF, 192);
    make_map(enc, &tm_w2, p.w2, FF, DM, 192);
    make_map(enc, &tm_wo, p.wo, DM, DM, 192);
    make_map(enc, &tm_o, o_ptr, SEQ, DM, 128);
    fused_kernel<<<NMAIN + NAUX, 384, SMEM_BYTES>>>(tm_x, tm_w1, tm_w2, tm_wo, tm_o, tm_qkv, tm_qkve, tm_ost, p);
}
```

```cpp
#include <cuda_runtime.h>
#include <cuda.h>
#include <cuda_bf16.h>
#include <stdint.h>

#define OSTEP_AT 4
#define PF1_NS 1500
#define PF2_NS 2000
#define PFIDX 3
#define PF3_NS 800
#define PF0_NS 1200
#define SIG_NS 64
#define POLL_NS 100
#define YF32 0

namespace {
constexpr int WAIT_ITERS = 3000000;

constexpr int SEQ = 2048, DM = 576, FF = 4608;
constexpr int NMAIN = 128, NAUX = 4;

constexpr uint32_t SB    = 0x400;
constexpr uint32_t HA    = SB;
constexpr uint32_t XB    = SB + 131072;
constexpr uint32_t RING  = SB + 147456;
constexpr uint32_t SLOT  = 24576;
constexpr uint32_t MISC  = SB + 221184;
constexpr uint32_t BARS  = MISC;
constexpr uint32_t B1S   = MISC + 512;
constexpr uint32_t B2S   = MISC + 2816;
constexpr uint32_t EPO   = MISC + 3072;
constexpr uint32_t EVC   = MISC + 3104;
constexpr uint32_t SMEM_BYTES = 221184 + 3200 + 512;
constexpr uint32_t PKT   = HA + 32768;
constexpr uint32_t VT    = HA + 51200;
constexpr uint32_t OST   = HA + 79872;
constexpr uint32_t PQT   = HA + 98304;
constexpr uint32_t KVB   = HA + 116736;

enum { B_FULL = 0, B_EMPTY = 3, B_XFULL = 6, B_OFULL = 9, B_O8FULL = 10, B_OFREE = 11, B_O8FREE = 12, B_KVB = 13, B_INIT = 14, B_COUNT = 15 };
__device__ __forceinline__ constexpr uint32_t bar(int i) { return BARS + 8u * i; }

constexpr int YT_BYTES = YF32 ? 32768 : 16384;
__device__ __align__(1024) __nv_bfloat16 g_o[SEQ * DM];
__device__ __align__(1024) unsigned char g_yacc[2 * 16 * 9 * YT_BYTES];
__device__ __align__(128) float g_kv[2 * 8 * 72 * 20];
__device__ __align__(128) unsigned int g_s8[16 * 4096];
__device__ __align__(128) unsigned int g_cnt[(8 + 16 + 16 * 9) * 8];
__device__ unsigned int g_epoch[NMAIN + NAUX];
__device__ __forceinline__ unsigned int* cnt_kv(int j) { return g_cnt + j * 8; }
__device__ __forceinline__ unsigned int* cnt_o(int m) { return g_cnt + (8 + m) * 8; }
__device__ __forceinline__ unsigned int* cnt_y(int m, int c) { return g_cnt + (24 + m * 9 + c) * 8; }

__device__ __forceinline__ void mbar_init(uint32_t b, uint32_t cnt) { asm volatile("mbarrier.init.shared::cta.b64 [%0], %1;" :: "r"(b), "r"(cnt)); }
__device__ __forceinline__ void mbar_expect_tx(uint32_t b, uint32_t bytes) { asm volatile("mbarrier.arrive.expect_tx.shared::cta.b64 _, [%0], %1;" :: "r"(b), "r"(bytes) : "memory"); }
__device__ __forceinline__ void mbar_arrive(uint32_t b) { asm volatile("mbarrier.arrive.shared::cta.b64 _, [%0];" :: "r"(b) : "memory"); }
__device__ __forceinline__ void prof(int) {}
__device__ __forceinline__ void mbar_wait(uint32_t b, uint32_t parity) {
    asm volatile("{\n.reg .pred p;\n.reg .u32 c;\nmov.u32 c, 0;\n"
                 "WAIT_LOOP:\nmbarrier.try_wait.parity.shared::cta.b64 p, [%0], %1;\n@p bra WAIT_DONE;\n"
                 "add.u32 c, c, 1;\nsetp.lt.u32 p, c, 20000000;\n@p bra WAIT_LOOP;\ntrap;\nWAIT_DONE:\n}"
                 :: "r"(b), "r"(parity) : "memory");
}
__device__ __forceinline__ void smem_wait_gt(uint32_t addr, uint32_t val) {
    asm volatile("{\n.reg .pred p;\n.reg .u32 c, v;\nmov.u32 c, 0;\n"
                 "SW_LOOP:\nld.acquire.cta.shared.u32 v, [%0];\nsetp.gt.u32 p, v, %1;\n@p bra SW_DONE;\n"
                 "nanosleep.u32 64;\nadd.u32 c, c, 1;\nsetp.lt.u32 p, c, 20000000;\n@p bra SW_LOOP;\ntrap;\nSW_DONE:\n}"
                 :: "r"(addr), "r"(val) : "memory");
}
__device__ __forceinline__ void tma_2d(uint32_t dst, const CUtensorMap* tm, uint32_t b, int c0, int c1) {
    asm volatile("cp.async.bulk.tensor.2d.shared::cluster.global.mbarrier::complete_tx::bytes [%0], [%1, {%3, %4}], [%2];"
                 :: "r"(dst), "l"(tm), "r"(b), "r"(c0), "r"(c1) : "memory");
}
__device__ __forceinline__ void fence_async_smem() { asm volatile("fence.proxy.async.shared::cta;" ::: "memory"); }
__device__ __forceinline__ void fence_async_all() { asm volatile("fence.proxy.async;" ::: "memory"); }
__device__ __forceinline__ void named_bar(int id, int n) { asm volatile("bar.sync %0, %1;" :: "r"(id), "r"(n) : "memory"); }
__device__ __forceinline__ void wg_fence() { asm volatile("wgmma.fence.sync.aligned;" ::: "memory"); }
__device__ __forceinline__ void wg_commit() { asm volatile("wgmma.commit_group.sync.aligned;" ::: "memory"); }
template<int N> __device__ __forceinline__ void wg_wait() { asm volatile("wgmma.wait_group.sync.aligned %0;" :: "n"(N) : "memory"); }
template<int N> __device__ __forceinline__ void reg_fence(float* d) {
    #pragma unroll
    for (int i = 0; i < N; i++) asm volatile("" : "+f"(d[i]) :: "memory");
}
template<int N> __device__ __forceinline__ void reg_copy(float* d, const float* s) {
    #pragma unroll
    for (int i = 0; i < N; i++) asm volatile("mov.b32 %0, %1;" : "=f"(d[i]) : "f"(s[i]));
}
__device__ __forceinline__ uint32_t pack_bf16(float lo, float hi) { uint32_t r; asm("cvt.rn.bf16x2.f32 %0, %1, %2;" : "=r"(r) : "f"(hi), "f"(lo)); return r; }
__device__ __forceinline__ float bf_lo(uint32_t v) { return __uint_as_float(v << 16); }
__device__ __forceinline__ float bf_hi(uint32_t v) { return __uint_as_float(v & 0xffff0000u); }
__device__ __forceinline__ uint32_t sub_bf16x2(uint32_t a, uint32_t b) { uint32_t r; asm("sub.rn.bf16x2 %0, %1, %2;" : "=r"(r) : "r"(a), "r"(b)); return r; }
__device__ __forceinline__ float ex2(float x) { float r; asm("ex2.approx.ftz.f32 %0, %1;" : "=f"(r) : "f"(x)); return r; }
__device__ __forceinline__ float rcp(float x) { float r; asm("rcp.approx.ftz.f32 %0, %1;" : "=f"(r) : "f"(x)); return r; }
__device__ __forceinline__ float tanh_ap(float x) { float r; asm("tanh.approx.f32 %0, %1;" : "=f"(r) : "f"(x)); return r; }
__device__ __forceinline__ void sts32(uint32_t a, uint32_t v) { asm volatile("st.shared.b32 [%0], %1;" :: "r"(a), "r"(v)); }
__device__ __forceinline__ void sts128(uint32_t a, uint32_t x, uint32_t y, uint32_t z, uint32_t w) { asm volatile("st.shared.v4.b32 [%0], {%1,%2,%3,%4};" :: "r"(a), "r"(x), "r"(y), "r"(z), "r"(w)); }
__device__ __forceinline__ void sts64(uint32_t a, uint32_t x, uint32_t y) { asm volatile("st.shared.v2.b32 [%0], {%1,%2};" :: "r"(a), "r"(x), "r"(y)); }
__device__ __forceinline__ void lds64(uint32_t a, uint32_t* v) { asm volatile("ld.shared.v2.b32 {%0,%1}, [%2];" : "=r"(v[0]), "=r"(v[1]) : "r"(a)); }
__device__ __forceinline__ float2 lds64f(uint32_t a) { float2 v; asm("ld.shared.v2.f32 {%0,%1}, [%2];" : "=f"(v.x), "=f"(v.y) : "r"(a)); return v; }
__device__ __forceinline__ void ldsm4(uint32_t a, uint32_t* v) {
    asm volatile("ldmatrix.sync.aligned.m8n8.x4.shared.b16 {%0,%1,%2,%3}, [%4];" : "=r"(v[0]), "=r"(v[1]), "=r"(v[2]), "=r"(v[3]) : "r"(a));
}
__device__ __forceinline__ void mma_ones(float* c, const uint32_t* a) {
    const uint32_t one2 = 0x3F803F80u;
    asm volatile("mma.sync.aligned.m16n8k16.row.col.f32.bf16.bf16.f32 {%0,%1,%2,%3}, {%4,%5,%6,%7}, {%8,%8}, {%0,%1,%2,%3};"
                 : "+f"(c[0]), "+f"(c[1]), "+f"(c[2]), "+f"(c[3]) : "r"(a[0]), "r"(a[1]), "r"(a[2]), "r"(a[3]), "r"(one2));
}
__device__ __forceinline__ unsigned int ld_acquire(const unsigned int* p) { unsigned int v; asm volatile("ld.acquire.gpu.global.u32 %0, [%1];" : "=r"(v) : "l"(p) : "memory"); return v; }
__device__ __forceinline__ void wait_cnt(const unsigned int* p, unsigned int target) {
    for (int i = 0; i < WAIT_ITERS; i++) {
        if ((int)(ld_acquire(p) - target) >= 0) return;
        __nanosleep(POLL_NS);
    }
    __trap();
}
__device__ __forceinline__ uint32_t v_tid() { uint32_t r; asm volatile("mov.u32 %0, %%tid.x;" : "=r"(r)); return r; }
__device__ __forceinline__ uint32_t v_bid() { uint32_t r; asm volatile("mov.u32 %0, %%ctaid.x;" : "=r"(r)); return r; }
__device__ __forceinline__ uint32_t v_epoch() { uint32_t r; asm volatile("ld.shared.u32 %0, [%1];" : "=r"(r) : "r"(EPO)); return r; }
__device__ __forceinline__ void prefetch_l2(const void* p) { asm volatile("prefetch.global.L2 [%0];" :: "l"(p)); }

__host__ __device__ constexpr uint64_t mkdesc(uint32_t addr, uint32_t lbo, uint32_t sbo, uint32_t swz) {
    return (uint64_t)((addr & 0x3FFFF) >> 4) | ((uint64_t)((lbo >> 4) & 0x3FFF) << 16) | ((uint64_t)((sbo >> 4) & 0x3FFF) << 32) | ((uint64_t)swz << 62);
}

template<int SD> __device__ __forceinline__ void wg_rs64(float* d, const uint32_t* a, uint64_t bd) {
  if constexpr (SD) {
    asm volatile("{\n.reg .pred p;\nsetp.eq.b32 p, 0, 0;\n"
    "wgmma.mma_async.sync.aligned.m64n64k16.f32.bf16.bf16 {%0,%1,%2,%3,%4,%5,%6,%7,%8,%9,%10,%11,%12,%13,%14,%15,%16,%17,%18,%19,%20,%21,%22,%23,%24,%25,%26,%27,%28,%29,%30,%31}, {%32,%33,%34,%35}, %36, p, 1, 1, 1;\n}"
    : "+f"(d[0]),"+f"(d[1]),"+f"(d[2]),"+f"(d[3]),"+f"(d[4]),"+f"(d[5]),"+f"(d[6]),"+f"(d[7]),"+f"(d[8]),"+f"(d[9]),"+f"(d[10]),"+f"(d[11]),"+f"(d[12]),"+f"(d[13]),"+f"(d[14]),"+f"(d[15]),"+f"(d[16]),"+f"(d[17]),"+f"(d[18]),"+f"(d[19]),"+f"(d[20]),"+f"(d[21]),"+f"(d[22]),"+f"(d[23]),"+f"(d[24]),"+f"(d[25]),"+f"(d[26]),"+f"(d[27]),"+f"(d[28]),"+f"(d[29]),"+f"(d[30]),"+f"(d[31])
    : "r"(a[0]),"r"(a[1]),"r"(a[2]),"r"(a[3]), "l"(bd));
  } else {
    asm volatile("{\n.reg .pred p;\nsetp.ne.b32 p, 0, 0;\n"
    "wgmma.mma_async.sync.aligned.m64n64k16.f32.bf16.bf16 {%0,%1,%2,%3,%4,%5,%6,%7,%8,%9,%10,%11,%12,%13,%14,%15,%16,%17,%18,%19,%20,%21,%22,%23,%24,%25,%26,%27,%28,%29,%30,%31}, {%32,%33,%34,%35}, %36, p, 1, 1, 1;\n}"
    : "+f"(d[0]),"+f"(d[1]),"+f"(d[2]),"+f"(d[3]),"+f"(d[4]),"+f"(d[5]),"+f"(d[6]),"+f"(d[7]),"+f"(d[8]),"+f"(d[9]),"+f"(d[10]),"+f"(d[11]),"+f"(d[12]),"+f"(d[13]),"+f"(d[14]),"+f"(d[15]),"+f"(d[16]),"+f"(d[17]),"+f"(d[18]),"+f"(d[19]),"+f"(d[20]),"+f"(d[21]),"+f"(d[22]),"+f"(d[23]),"+f"(d[24]),"+f"(d[25]),"+f"(d[26]),"+f"(d[27]),"+f"(d[28]),"+f"(d[29]),"+f"(d[30]),"+f"(d[31])
    : "r"(a[0]),"r"(a[1]),"r"(a[2]),"r"(a[3]), "l"(bd));
  }
}
template<int SD> __device__ __forceinline__ void wg_ss64(float* d, uint64_t ad, uint64_t bd) {
  if constexpr (SD) {
    asm volatile("{\n.reg .pred p;\nsetp.eq.b32 p, 0, 0;\n"
    "wgmma.mma_async.sync.aligned.m64n64k16.f32.bf16.bf16 {%0,%1,%2,%3,%4,%5,%6,%7,%8,%9,%10,%11,%12,%13,%14,%15,%16,%17,%18,%19,%20,%21,%22,%23,%24,%25,%26,%27,%28,%29,%30,%31}, %32, %33, p, 1, 1, 0, 1;\n}"
    : "+f"(d[0]),"+f"(d[1]),"+f"(d[2]),"+f"(d[3]),"+f"(d[4]),"+f"(d[5]),"+f"(d[6]),"+f"(d[7]),"+f"(d[8]),"+f"(d[9]),"+f"(d[10]),"+f"(d[11]),"+f"(d[12]),"+f"(d[13]),"+f"(d[14]),"+f"(d[15]),"+f"(d[16]),"+f"(d[17]),"+f"(d[18]),"+f"(d[19]),"+f"(d[20]),"+f"(d[21]),"+f"(d[22]),"+f"(d[23]),"+f"(d[24]),"+f"(d[25]),"+f"(d[26]),"+f"(d[27]),"+f"(d[28]),"+f"(d[29]),"+f"(d[30]),"+f"(d[31])
    : "l"(ad), "l"(bd));
  } else {
    asm volatile("{\n.reg .pred p;\nsetp.ne.b32 p, 0, 0;\n"
    "wgmma.mma_async.sync.aligned.m64n64k16.f32.bf16.bf16 {%0,%1,%2,%3,%4,%5,%6,%7,%8,%9,%10,%11,%12,%13,%14,%15,%16,%17,%18,%19,%20,%21,%22,%23,%24,%25,%26,%27,%28,%29,%30,%31}, %32, %33, p, 1, 1, 0, 1;\n}"
    : "+f"(d[0]),"+f"(d[1]),"+f"(d[2]),"+f"(d[3]),"+f"(d[4]),"+f"(d[5]),"+f"(d[6]),"+f"(d[7]),"+f"(d[8]),"+f"(d[9]),"+f"(d[10]),"+f"(d[11]),"+f"(d[12]),"+f"(d[13]),"+f"(d[14]),"+f"(d[15]),"+f"(d[16]),"+f"(d[17]),"+f"(d[18]),"+f"(d[19]),"+f"(d[20]),"+f"(d[21]),"+f"(d[22]),"+f"(d[23]),"+f"(d[24]),"+f"(d[25]),"+f"(d[26]),"+f"(d[27]),"+f"(d[28]),"+f"(d[29]),"+f"(d[30]),"+f"(d[31])
    : "l"(ad), "l"(bd));
  }
}
template<int SD> __device__ __forceinline__ void wg_rs72(float* d, const uint32_t* a, uint64_t bd) {
  if constexpr (SD) {
    asm volatile("{\n.reg .pred p;\nsetp.eq.b32 p, 0, 0;\n"
    "wgmma.mma_async.sync.aligned.m64n72k16.f32.bf16.bf16 {%0,%1,%2,%3,%4,%5,%6,%7,%8,%9,%10,%11,%12,%13,%14,%15,%16,%17,%18,%19,%20,%21,%22,%23,%24,%25,%26,%27,%28,%29,%30,%31,%32,%33,%34,%35}, {%36,%37,%38,%39}, %40, p, 1, 1, 1;\n}"
    : "+f"(d[0]),"+f"(d[1]),"+f"(d[2]),"+f"(d[3]),"+f"(d[4]),"+f"(d[5]),"+f"(d[6]),"+f"(d[7]),"+f"(d[8]),"+f"(d[9]),"+f"(d[10]),"+f"(d[11]),"+f"(d[12]),"+f"(d[13]),"+f"(d[14]),"+f"(d[15]),"+f"(d[16]),"+f"(d[17]),"+f"(d[18]),"+f"(d[19]),"+f"(d[20]),"+f"(d[21]),"+f"(d[22]),"+f"(d[23]),"+f"(d[24]),"+f"(d[25]),"+f"(d[26]),"+f"(d[27]),"+f"(d[28]),"+f"(d[29]),"+f"(d[30]),"+f"(d[31]),"+f"(d[32]),"+f"(d[33]),"+f"(d[34]),"+f"(d[35])
    : "r"(a[0]),"r"(a[1]),"r"(a[2]),"r"(a[3]), "l"(bd));
  } else {
    asm volatile("{\n.reg .pred p;\nsetp.ne.b32 p, 0, 0;\n"
    "wgmma.mma_async.sync.aligned.m64n72k16.f32.bf16.bf16 {%0,%1,%2,%3,%4,%5,%6,%7,%8,%9,%10,%11,%12,%13,%14,%15,%16,%17,%18,%19,%20,%21,%22,%23,%24,%25,%26,%27,%28,%29,%30,%31,%32,%33,%34,%35}, {%36,%37,%38,%39}, %40, p, 1, 1, 1;\n}"
    : "+f"(d[0]),"+f"(d[1]),"+f"(d[2]),"+f"(d[3]),"+f"(d[4]),"+f"(d[5]),"+f"(d[6]),"+f"(d[7]),"+f"(d[8]),"+f"(d[9]),"+f"(d[10]),"+f"(d[11]),"+f"(d[12]),"+f"(d[13]),"+f"(d[14]),"+f"(d[15]),"+f"(d[16]),"+f"(d[17]),"+f"(d[18]),"+f"(d[19]),"+f"(d[20]),"+f"(d[21]),"+f"(d[22]),"+f"(d[23]),"+f"(d[24]),"+f"(d[25]),"+f"(d[26]),"+f"(d[27]),"+f"(d[28]),"+f"(d[29]),"+f"(d[30]),"+f"(d[31]),"+f"(d[32]),"+f"(d[33]),"+f"(d[34]),"+f"(d[35])
    : "r"(a[0]),"r"(a[1]),"r"(a[2]),"r"(a[3]), "l"(bd));
  }
}
template<int SD> __device__ __forceinline__ void wg_ss72(float* d, uint64_t ad, uint64_t bd) {
  if constexpr (SD) {
    asm volatile("{\n.reg .pred p;\nsetp.eq.b32 p, 0, 0;\n"
    "wgmma.mma_async.sync.aligned.m64n72k16.f32.bf16.bf16 {%0,%1,%2,%3,%4,%5,%6,%7,%8,%9,%10,%11,%12,%13,%14,%15,%16,%17,%18,%19,%20,%21,%22,%23,%24,%25,%26,%27,%28,%29,%30,%31,%32,%33,%34,%35}, %36, %37, p, 1, 1, 0, 1;\n}"
    : "+f"(d[0]),"+f"(d[1]),"+f"(d[2]),"+f"(d[3]),"+f"(d[4]),"+f"(d[5]),"+f"(d[6]),"+f"(d[7]),"+f"(d[8]),"+f"(d[9]),"+f"(d[10]),"+f"(d[11]),"+f"(d[12]),"+f"(d[13]),"+f"(d[14]),"+f"(d[15]),"+f"(d[16]),"+f"(d[17]),"+f"(d[18]),"+f"(d[19]),"+f"(d[20]),"+f"(d[21]),"+f"(d[22]),"+f"(d[23]),"+f"(d[24]),"+f"(d[25]),"+f"(d[26]),"+f"(d[27]),"+f"(d[28]),"+f"(d[29]),"+f"(d[30]),"+f"(d[31]),"+f"(d[32]),"+f"(d[33]),"+f"(d[34]),"+f"(d[35])
    : "l"(ad), "l"(bd));
  } else {
    asm volatile("{\n.reg .pred p;\nsetp.ne.b32 p, 0, 0;\n"
    "wgmma.mma_async.sync.aligned.m64n72k16.f32.bf16.bf16 {%0,%1,%2,%3,%4,%5,%6,%7,%8,%9,%10,%11,%12,%13,%14,%15,%16,%17,%18,%19,%20,%21,%22,%23,%24,%25,%26,%27,%28,%29,%30,%31,%32,%33,%34,%35}, %36, %37, p, 1, 1, 0, 1;\n}"
    : "+f"(d[0]),"+f"(d[1]),"+f"(d[2]),"+f"(d[3]),"+f"(d[4]),"+f"(d[5]),"+f"(d[6]),"+f"(d[7]),"+f"(d[8]),"+f"(d[9]),"+f"(d[10]),"+f"(d[11]),"+f"(d[12]),"+f"(d[13]),"+f"(d[14]),"+f"(d[15]),"+f"(d[16]),"+f"(d[17]),"+f"(d[18]),"+f"(d[19]),"+f"(d[20]),"+f"(d[21]),"+f"(d[22]),"+f"(d[23]),"+f"(d[24]),"+f"(d[25]),"+f"(d[26]),"+f"(d[27]),"+f"(d[28]),"+f"(d[29]),"+f"(d[30]),"+f"(d[31]),"+f"(d[32]),"+f"(d[33]),"+f"(d[34]),"+f"(d[35])
    : "l"(ad), "l"(bd));
  }
}
template<int SD> __device__ __forceinline__ void wg_tt64(float* d, uint64_t ad, uint64_t bd) {
  if constexpr (SD) {
    asm volatile("{\n.reg .pred p;\nsetp.eq.b32 p, 0, 0;\n"
    "wgmma.mma_async.sync.aligned.m64n64k16.f32.bf16.bf16 {%0,%1,%2,%3,%4,%5,%6,%7,%8,%9,%10,%11,%12,%13,%14,%15,%16,%17,%18,%19,%20,%21,%22,%23,%24,%25,%26,%27,%28,%29,%30,%31}, %32, %33, p, 1, 1, 1, 1;\n}"
    : "+f"(d[0]),"+f"(d[1]),"+f"(d[2]),"+f"(d[3]),"+f"(d[4]),"+f"(d[5]),"+f"(d[6]),"+f"(d[7]),"+f"(d[8]),"+f"(d[9]),"+f"(d[10]),"+f"(d[11]),"+f"(d[12]),"+f"(d[13]),"+f"(d[14]),"+f"(d[15]),"+f"(d[16]),"+f"(d[17]),"+f"(d[18]),"+f"(d[19]),"+f"(d[20]),"+f"(d[21]),"+f"(d[22]),"+f"(d[23]),"+f"(d[24]),"+f"(d[25]),"+f"(d[26]),"+f"(d[27]),"+f"(d[28]),"+f"(d[29]),"+f"(d[30]),"+f"(d[31])
    : "l"(ad), "l"(bd));
  } else {
    asm volatile("{\n.reg .pred p;\nsetp.ne.b32 p, 0, 0;\n"
    "wgmma.mma_async.sync.aligned.m64n64k16.f32.bf16.bf16 {%0,%1,%2,%3,%4,%5,%6,%7,%8,%9,%10,%11,%12,%13,%14,%15,%16,%17,%18,%19,%20,%21,%22,%23,%24,%25,%26,%27,%28,%29,%30,%31}, %32, %33, p, 1, 1, 1, 1;\n}"
    : "+f"(d[0]),"+f"(d[1]),"+f"(d[2]),"+f"(d[3]),"+f"(d[4]),"+f"(d[5]),"+f"(d[6]),"+f"(d[7]),"+f"(d[8]),"+f"(d[9]),"+f"(d[10]),"+f"(d[11]),"+f"(d[12]),"+f"(d[13]),"+f"(d[14]),"+f"(d[15]),"+f"(d[16]),"+f"(d[17]),"+f"(d[18]),"+f"(d[19]),"+f"(d[20]),"+f"(d[21]),"+f"(d[22]),"+f"(d[23]),"+f"(d[24]),"+f"(d[25]),"+f"(d[26]),"+f"(d[27]),"+f"(d[28]),"+f"(d[29]),"+f"(d[30]),"+f"(d[31])
    : "l"(ad), "l"(bd));
  }
}

template<int V> struct IC { static constexpr int v = V; };
template<int I, int N, class F> __device__ __forceinline__ void sfor(F&& f) {
    if constexpr (I < N) { f(IC<I>{}); sfor<I + 1, N>(f); }
}

enum { K_QKV = 0, K_H = 1 };

struct Ctx {
    uint32_t tph;
    uint32_t tid_;
    bool pf = false;
    __device__ __forceinline__ uint32_t tid() const { uint32_t r; asm volatile("mov.u32 %0, %1;" : "=r"(r) : "r"(tid_)); return r; }
};
__device__ __forceinline__ void release_slot(const Ctx& c, int slot) { if ((c.tid() & 31) == 0) mbar_arrive(bar(B_EMPTY + slot)); }

__device__ __forceinline__ void turn_wait(const Ctx& c) { asm volatile("bar.sync %0, 256;" :: "r"(4 + (c.tid() >> 7)) : "memory"); }
__device__ __forceinline__ void turn_pass(const Ctx& c) { asm volatile("bar.arrive %0, 256;" :: "r"(5 - (c.tid() >> 7)) : "memory"); }

template<int KIND, class PART, class POST>
__device__ __forceinline__ void run_step(Ctx& c, float* acc, const uint32_t* a, PART&& part, POST&& post, bool last = false) {
    constexpr int NST = (KIND == K_QKV) ? 6 : 3;
    constexpr int KPS = 36 / NST;
    sfor<0, NST>([&](auto ST) {
        constexpr int st = decltype(ST)::v;
        constexpr int slot = st % 3;
        mbar_wait(bar(B_FULL + slot), c.tph);
        uint32_t wgo = 0;
        if constexpr (st == NST - 1) wgo = (c.tid() >> 7) * 512;
        if (KIND == K_H && c.pf) prof(44 + st * 5);
        turn_wait(c);
        if (KIND == K_H && c.pf) prof(45 + st * 5);
        wg_fence();
        sfor<0, KPS>([&](auto KK) {
            constexpr int kk = decltype(KK)::v;
            constexpr int ks = st * KPS + kk;
            constexpr int SD = ks ? 1 : 0;
            if constexpr (KIND == K_QKV) {
                constexpr uint64_t bd = mkdesc(RING + slot * SLOT + kk * 2048, 12288, 1024, 1);
                if constexpr (ks < 32) wg_rs72<SD>(acc, a + ks * 4, bd);
                else wg_ss72<SD>(acc, mkdesc(XB + (ks - 32) * 32, 16, 1024, 1) + wgo, bd);
            } else {
                constexpr uint64_t bd = mkdesc(RING + slot * SLOT + kk * 2048, 16, 1024, 1);
                if constexpr (ks < 32) wg_rs64<SD>(acc, a + ks * 4, bd);
                else wg_ss64<SD>(acc, mkdesc(XB + (ks - 32) * 32, 16, 1024, 1) + wgo, bd);
            }
        });
        wg_commit();
        if (st < NST - 1 || !last || c.tid() < 128) turn_pass(c);
        if (KIND == K_H && c.pf) prof(46 + st * 5);
        part(ST);
        if (KIND == K_H && c.pf) prof(47 + st * 5);
        wg_wait<0>();
        if (KIND == K_H && c.pf) prof(48 + st * 5);
        release_slot(c, slot);
        if constexpr (slot == 2) c.tph ^= 1;
        post(ST);
    });
    if constexpr (KIND == K_QKV) reg_fence<36>(acc); else reg_fence<32>(acc);
}

__device__ __forceinline__ float phi(float t) {
    float e = ex2(t * 1.4426950408889634f);
    return (t > 0.f ? t + 1.0f : e) + 1e-6f;
}
__device__ __forceinline__ float gelu_h(float hx) {
    float u = hx * fmaf(hx * hx, 0.2854192650f, 1.5957691216f);
    return fmaf(hx, tanh_ap(u), hx);
}

struct Params {
    const __nv_bfloat16* x;
    const __nv_bfloat16* wqkv;
    const __nv_bfloat16* wo;
    const __nv_bfloat16* w1;
    const __nv_bfloat16* b1;
    const __nv_bfloat16* w2;
    const __nv_bfloat16* b2;
    __nv_bfloat16* out;
};

__global__ void __launch_bounds__(384, 1)
fused_kernel(const __grid_constant__ CUtensorMap tm_x, const __grid_constant__ CUtensorMap tm_w1,
             const __grid_constant__ CUtensorMap tm_w2, const __grid_constant__ CUtensorMap tm_wo,
             const __grid_constant__ CUtensorMap tm_o, const __grid_constant__ CUtensorMap tm_qkv,
             const __grid_constant__ CUtensorMap tm_qkve, const __grid_constant__ CUtensorMap tm_ost, const Params p) {
    extern __shared__ __align__(1024) unsigned char smem_raw[];
    const int tid = threadIdx.x;
    const int bid = blockIdx.x;
    const bool is_main = bid < NMAIN;
    const int j = bid & 7;
    const int m = bid >> 3;

    if (tid == 0) {
        if ((uint32_t)__cvta_generic_to_shared(smem_raw) != SB) __trap();
        for (int i = 0; i < 3; i++) {
            mbar_init(bar(B_FULL + i), 1); mbar_init(bar(B_EMPTY + i), 8);
            mbar_init(bar(B_XFULL + i), 1);
        }
        mbar_init(bar(B_KVB), 2); mbar_init(bar(B_INIT), 1);
        mbar_init(bar(B_OFULL), 1); mbar_init(bar(B_O8FULL), 1); mbar_init(bar(B_OFREE), 8); mbar_init(bar(B_O8FREE), 8);
        asm volatile("fence.mbarrier_init.release.cluster;" ::: "memory");
    }
    if (tid == 256) { asm volatile("prefetch.tensormap [%0];" :: "l"(&tm_x) : "memory"); asm volatile("prefetch.tensormap [%0];" :: "l"(&tm_qkv) : "memory"); asm volatile("prefetch.tensormap [%0];" :: "l"(&tm_qkve) : "memory"); }
    if (tid >= 40 && tid < 48) sts32(EVC + (tid - 40) * 4, 0);
    if (tid == 48) sts32(EPO + 4, 0);
    __syncthreads();

    if (tid >= 256) {
        asm volatile("setmaxnreg.dec.sync.aligned.u32 24;");
        const int hw = (tid >> 5) - 8, lane = tid & 31;
        uint32_t epoch = 0;
        if (hw > 0) {
            epoch = g_epoch[bid];
            if (hw == 3) {
                if (lane == 0) sts32(EPO, epoch);
                if (is_main) {
                    #pragma unroll 1
                    for (int i = lane; i < 288; i += 32) {
                        uint32_t v = *reinterpret_cast<const uint32_t*>(p.b1 + j * 576 + 2 * i);
                        sts32(B1S + 8 * i, __float_as_uint(0.5f * bf_lo(v))); sts32(B1S + 8 * i + 4, __float_as_uint(0.5f * bf_hi(v)));
                    }
                }
                uint32_t v = *reinterpret_cast<const uint32_t*>(p.b2 + (is_main ? j : 8) * 64 + 2 * lane);
                sts32(B2S + 8 * lane, v << 16); sts32(B2S + 8 * lane + 4, v & 0xffff0000u);
                __syncwarp();
                if (lane == 0) mbar_arrive(bar(B_INIT));
            }
        }
        const uint32_t par = epoch & 1;
        if (hw == 0) {
            if (lane == 0) {
                uint32_t n = 0;
                if (is_main) {
                    #pragma unroll 1
                    for (int kb = 0; kb < 9; kb++) {
                        if (kb % 3 == 0) mbar_expect_tx(bar(B_XFULL + kb / 3), 49152);
                        tma_2d(HA + kb * 16384, &tm_x, bar(B_XFULL + kb / 3), kb * 64, m * 128);
                    }
                    #pragma unroll 1
                    for (int u = 0; u < 18; u++) {
                        const int st = u % 3, step = u / 6;
                        const int col = ((step == 2) ? 0 : (step + 1) * 576) + j * 72, row = (u % 6) * 96;
                        mbar_wait(bar(B_EMPTY + st), (n & 1) ^ 1);
                        mbar_expect_tx(bar(B_FULL + st), 96 * 144);
                        tma_2d(RING + st * SLOT, &tm_qkv, bar(B_FULL + st), col, row);
                        tma_2d(RING + st * SLOT + 12288, &tm_qkve, bar(B_FULL + st), col + 64, row);
                        if (st == 2) n++;
                    }
                }
                const int nsteps = is_main ? 19 : 1;
                #pragma unroll 1
                for (int s = 0; s < nsteps; s++, n++) {
                    const CUtensorMap* tm; int col, row;
                    if (!is_main) { tm = &tm_wo; col = 512; row = 0; }
                    else if (s < 9) { tm = &tm_w1; col = j * 576 + s * 64; row = 0; }
                    else if (s < 18) { tm = &tm_w2; col = (s == 9) ? 512 : (((j + s - 9) & 7) * 64); row = j * 576; }
                    else { tm = &tm_wo; col = j * 64; row = 0; }
                    #pragma unroll 1
                    for (int st = 0; st < 3; st++) {
                        mbar_wait(bar(B_EMPTY + st), (n & 1) ^ 1);
                        mbar_expect_tx(bar(B_FULL + st), SLOT);
                        tma_2d(RING + st * SLOT, tm, bar(B_FULL + st), col, row + st * 192);
                    }
                }
            }
        } else {
            if (is_main) {
                const int t = tid - 288;
                __nanosleep(PF0_NS);
                #pragma unroll 1
                for (int i = t; i < 36 * 6; i += 96) {
                    int r = i / 6, q = i - r * 6;
                    prefetch_l2(reinterpret_cast<const char*>(p.wqkv) + (36 * m + r) * 3456 + (q >> 1) * 1152 + j * 144 + (q & 1) * 128);
                }
                __nanosleep(PF1_NS);
                #pragma unroll 1
                for (int i = t; i < 36 * 9; i += 96) {
                    int r = i / 9, q = i - r * 9;
                    prefetch_l2(reinterpret_cast<const char*>(p.w1) + (36 * m + r) * 9216 + j * 1152 + q * 128);
                    __nanosleep(PF3_NS);
                }
                __nanosleep(PF2_NS);
                #pragma unroll 1
                for (int i = t; i < 36 * 9; i += 96)
                    prefetch_l2(reinterpret_cast<const char*>(p.w2) + (576 * j + 36 * m) * 1152 + i * 128);
                if (t < 41 && (bid * 41 + t) < 5184) prefetch_l2(reinterpret_cast<const char*>(p.wo) + (bid * 41 + t) * 128);
                if (hw != 2) {
                    if (lane == 0) wait_cnt(cnt_kv(j), (epoch + 1) * 16);
                    __syncwarp();
                    const float4* kv = reinterpret_cast<const float4*>(g_kv + (par * 8 + j) * 1440);
                    #pragma unroll 2
                    for (int i = lane + (hw == 1 ? 0 : 32); i < 360; i += 64) {
                        const float4 v = __ldcg(kv + i);
                        const int d = i / 5, e = (i - d * 5) * 4, h = d / 18;
                        const uint32_t base = KVB + (d >> 3) * 128 + (d & 7) * 16;
                        const int n0 = 8 + h * 18 + e;
                        sts32(base + (n0 >> 3) * 1280 + (n0 & 7) * 2, pack_bf16(v.x, v.y));
                        if (e < 16) sts32(base + ((n0 + 2) >> 3) * 1280 + ((n0 + 2) & 7) * 2, pack_bf16(v.z, v.w));
                        else asm volatile("st.shared.u16 [%0], %1;" :: "r"(base + h * 2), "h"((unsigned short)pack_bf16(v.z, 0.f)) : "memory");
                    }
                    fence_async_smem();
                    __syncwarp();
                    if (lane == 0) mbar_arrive(bar(B_KVB));
                }
            }
            if (hw == 1) {
                if (lane == 0) {
                    const int nit = is_main ? 1 : 4;
                    for (int it = 0; it < nit; it++) {
                        const int mt = is_main ? m : ((bid - NMAIN) * 4 + it);
                        const bool wf = is_main || it > 0;
                        const uint32_t fp = is_main ? 0 : ((it - 1) & 1);
                        wait_cnt(cnt_o(mt), (epoch + 1) * 8);
                        fence_async_all();
                        if (wf) mbar_wait(bar(B_OFREE), fp);
                        mbar_expect_tx(bar(B_OFULL), 131072);
                        #pragma unroll 1
                        for (int kb = 0; kb < 8; kb++) tma_2d(HA + kb * 16384, &tm_o, bar(B_OFULL), kb * 64, mt * 128);
                        if (wf) mbar_wait(bar(B_O8FREE), fp);
                        mbar_expect_tx(bar(B_O8FULL), 16384);
                        tma_2d(XB, &tm_o, bar(B_O8FULL), 512, mt * 128);
                    }
                    if (is_main) { wait_cnt(cnt_y(m, j), (epoch + 1) * 7); asm volatile("st.release.cta.shared.u32 [%0], %1;" :: "r"(EPO + 4), "r"(1) : "memory"); }
                }
            } else if (hw == 2) {
                if (!is_main) {
                    if (lane == 0) {
                        #pragma unroll 1
                        for (int it = 0; it < 4; it++) {
                            wait_cnt(cnt_y((bid - NMAIN) * 4 + it, 8), (epoch + 1) * 8);
                            asm volatile("st.release.cta.shared.u32 [%0], %1;" :: "r"(EPO + 4), "r"(it + 1) : "memory");
                        }
                    }
                } else {
                    #pragma unroll 1
                    for (int e = 0; e < 10; e++) {
                        int spin = 0;
                        while (true) {
                            uint32_t v;
                            asm volatile("ld.acquire.cta.shared.u32 %0, [%1];" : "=r"(v) : "r"(EVC + (lane & 7) * 4) : "memory");
                            if (__all_sync(0xffffffffu, v > (uint32_t)e)) break;
                            if (++spin > 20000000) __trap();
                            __nanosleep(SIG_NS);
                        }
                        if (lane == 0) {
                            unsigned int* cp = (e == 0) ? cnt_kv(j) : (e == 1) ? cnt_o(m) : cnt_y(m, e == 2 ? 8 : ((j + e - 2) & 7));
                            if (e == 1) fence_async_all();
                            __threadfence();
                            asm volatile("red.relaxed.gpu.global.add.u32 [%0], 1;" :: "l"(cp) : "memory");
                        }
                        __syncwarp();
                    }
                }
            } else {
                {
                    const int t0 = is_main ? (m * 9 + j) : ((bid - NMAIN) * 4 * 9 + 8);
                    const int nt = is_main ? 1 : 4;
                    for (int t = 0; t < nt; t++) {
                        uint4* z = reinterpret_cast<uint4*>(g_yacc + (size_t)((par ^ 1) * 144 + t0 + t * 9) * YT_BYTES);
                        for (int i = lane; i < YT_BYTES / 16; i += 32) z[i] = make_uint4(0, 0, 0, 0);
                    }
                    if (is_main && m == 0) {
                        float* z = g_kv + ((par ^ 1) * 8 + j) * 1440;
                        for (int i = lane; i < 1440; i += 32) z[i] = 0.f;
                    }
                }
            }
        }
    } else {
        asm volatile("setmaxnreg.inc.sync.aligned.u32 240;");
        prof(0);
        Ctx c; c.tph = 0; c.tid_ = v_tid();
        float hc[32], pv[36];
        if (tid >> 7) turn_pass(c);
        auto event = [&](uint32_t ev) {
            __syncwarp();
            if (((c.tid() & 31) == 0)) asm volatile("st.release.cta.shared.u32 [%0], %1;" :: "r"(EVC + (c.tid() >> 3)), "r"(ev) : "memory");
        };
        auto warp_arrive = [&](uint32_t b) { __syncwarp(); if (((c.tid() & 31) == 0)) mbar_arrive(b); };

        auto lrow_off = [&]() { uint32_t t_ = c.tid(); return HA + ((t_ >> 5) * 16 + (t_ & 15)) * 128 + ((((t_ >> 4) & 1) ^ (t_ & 7)) << 4); };
        auto tail_off = [&]() { uint32_t t_ = c.tid(), g = (t_ >> 2) & 7; return XB + ((t_ >> 5) * 16 + g) * 128 + (g << 4) + (t_ & 3) * 4; };
        if (is_main) {
            uint32_t a[128];
            float rs0, rs1;
            {
                uint32_t tl[16];
                const uint32_t lrow = lrow_off();
                float cs[4][4], sq[8];
                #pragma unroll
                for (int i = 0; i < 4; i++) {
                    #pragma unroll
                    for (int k = 0; k < 4; k++) { cs[i][k] = 0.f; sq[k] = 0.f; sq[k + 4] = 0.f; }
                }
                uint32_t s00 = 0, s11 = 0;
                auto frag = [&](auto KS) -> uint32_t* { constexpr int ks = decltype(KS)::v; return (ks < 32) ? (a + (ks & 31) * 4) : (tl + (ks & 3) * 4); };
                auto sqacc = [&](auto KS) {
                    const uint32_t* f = frag(KS);
                    #pragma unroll
                    for (int r = 0; r < 4; r++) {
                        const uint32_t w = sub_bf16x2(f[r], (r & 1) ? s11 : s00);
                        const float lo = bf_lo(w), hi = bf_hi(w);
                        sq[r] = fmaf(lo, lo, sq[r]); sq[r + 4] = fmaf(hi, hi, sq[r + 4]);
                    }
                };
                sfor<0, 3>([&](auto G) {
                    constexpr int g = decltype(G)::v;
                    mbar_wait(bar(B_XFULL + g), 0);
                    prof(37 + g);
                    sfor<12 * g, 12 * g + 12>([&](auto KS) {
                        constexpr int ks = decltype(KS)::v;
                        ldsm4((lrow ^ ((ks % 4) << 5)) + (ks / 4) * 16384, frag(KS));
                    });
                    sfor<12 * g, 12 * g + 12>([&](auto KS) { mma_ones(cs[decltype(KS)::v & 3], frag(KS)); });
                    if constexpr (g == 0) {
                        const float t0 = (cs[0][0] + cs[1][0] + cs[2][0] + cs[3][0]) * (1.0f / 192.0f), t1 = (cs[0][2] + cs[1][2] + cs[2][2] + cs[3][2]) * (1.0f / 192.0f);
                        s00 = pack_bf16(t0, t0); s11 = pack_bf16(t1, t1);
                    }
                    sfor<12 * g, 12 * g + 12>(sqacc);
                });
                prof(2);
                const float mean0 = (cs[0][0] + cs[1][0] + cs[2][0] + cs[3][0]) * (1.0f / 576.0f), mean1 = (cs[0][2] + cs[1][2] + cs[2][2] + cs[3][2]) * (1.0f / 576.0f);
                const uint32_t m00 = pack_bf16(mean0, mean0), m11 = pack_bf16(mean1, mean1);
                const uint32_t tb = tail_off();
                #pragma unroll
                for (int i = 0; i < 16; i++) sts32((tb ^ ((i >> 1) << 4)) + (i & 1) * 1024, sub_bf16x2(tl[i], (i & 1) ? m11 : m00));
                fence_async_smem();
                #pragma unroll
                for (int i = 0; i < 128; i++) a[i] = sub_bf16x2(a[i], (i & 1) ? m11 : m00);
                {
                    rs0 = (sq[0] + sq[2]) + (sq[4] + sq[6]); rs1 = (sq[1] + sq[3]) + (sq[5] + sq[7]);
                    rs0 += __shfl_xor_sync(0xffffffffu, rs0, 1); rs1 += __shfl_xor_sync(0xffffffffu, rs1, 1);
                    rs0 += __shfl_xor_sync(0xffffffffu, rs0, 2); rs1 += __shfl_xor_sync(0xffffffffu, rs1, 2);
                    const float d0 = mean0 - bf_lo(s00), d1 = mean1 - bf_lo(s11);
                    rs0 = rsqrtf(fmaxf(fmaf(rs0, 1.0f / 576.0f, -d0 * d0), 0.f) + 1e-5f);
                    rs1 = rsqrtf(fmaxf(fmaf(rs1, 1.0f / 576.0f, -d1 * d1), 0.f) + 1e-5f);
                }
                named_bar(1, 256);
            }
            prof(3);
            auto cm_off = [&]() { uint32_t t_ = c.tid(); return (t_ >> 5) * 256 + (t_ & 31) * 4; };
            {
                float qc[36];
                #pragma unroll
                for (int i = 0; i < 36; i++) { qc[i] = 0.f; pv[i] = 0.f; }
                #pragma unroll 1
                for (int s = 0; s < 3; s++) {
                    c.pf = (s == 0);
                    run_step<K_QKV>(c, qc, a, [&](auto ST) {
                        constexpr int st = decltype(ST)::v;
                        if (s > 0) {
                            const uint32_t cm = cm_off();
                            sfor<0, 9>([&](auto B) {
                                constexpr int b = decltype(B)::v;
                                if constexpr ((b * 6) / 9 == st) {
                                    const float v0 = pv[4 * b] * rs0, v1 = pv[4 * b + 1] * rs0, v2 = pv[4 * b + 2] * rs1, v3 = pv[4 * b + 3] * rs1;
                                    if (s == 1) {
                                        sts32(PKT + b * 2048 + cm, pack_bf16(phi(v0), phi(v1)));
                                        sts32(PKT + b * 2048 + cm + 128, pack_bf16(phi(v2), phi(v3)));
                                    } else {
                                        const uint32_t w0 = pack_bf16(v0, v1), w1 = pack_bf16(v2, v3);
                                        if constexpr (b <= 4) { sts32(VT + b * 2048 + cm, w0); sts32(VT + b * 2048 + cm + 128, w1); }
                                        if constexpr (b >= 4) { sts32(VT + (b + 2) * 2048 + cm, w0); sts32(VT + (b + 2) * 2048 + cm + 128, w1); }
                                        if constexpr (b == 0) {
                                            const uint32_t one = (cm & 12) ? 0u : 0x00003F80u;
                                            sts32(VT + 5 * 2048 + cm, one); sts32(VT + 5 * 2048 + cm + 128, one);
                                        }
                                        if constexpr (b == 8) {
                                            const uint32_t z = KVB + c.tid() * 16;
                                            sts128(z, 0, 0, 0, 0); sts128(z + 4096, 0, 0, 0, 0); sts128(z + 8192, 0, 0, 0, 0);
                                            if (z < KVB + 512) sts128(z + 12288, 0, 0, 0, 0);
                                            fence_async_smem();
                                        }
                                    }
                                }
                            });
                        }
                    }, [](auto) {});
                    reg_copy<36>(pv, qc);
                    prof(4 + s);
                }
            }
            {
                #pragma unroll
                for (int i = 0; i < 32; i++) hc[i] = 0.f;
                named_bar(1, 256);
                const uint32_t wgo = ((c.tid() >> 7) * 512);
                wg_fence();
                sfor<0, 8>([&](auto KS) {
                    constexpr int ks = decltype(KS)::v;
                    wg_tt64<(ks ? 1 : 0)>(hc, mkdesc(PKT + ks * 256, 128, 2048, 0) + wgo,
                                          mkdesc(VT + ks * 256, 128, 2048, 0) + wgo + (wgo >> 2));
                });
                wg_commit();
                const uint32_t pq = PQT + cm_off() + ((c.tid() >> 7) * 512) * 16;
                sfor<0, 9>([&](auto B) {
                    constexpr int b = decltype(B)::v;
                    sts32(pq + b * 1024, pack_bf16(phi(pv[4 * b] * rs0), phi(pv[4 * b + 1] * rs0)));
                    sts32(pq + b * 1024 + 128, pack_bf16(phi(pv[4 * b + 2] * rs1), phi(pv[4 * b + 3] * rs1)));
                });
                fence_async_smem();
                wg_wait<0>();
                reg_fence<32>(hc);
                reg_copy<24>(pv, hc);
            }
            prof(7);
            rs0 *= 0.5f; rs1 *= 0.5f;
            mbar_wait(bar(B_INIT), 0);
            auto gelun = [&](auto B0, auto B1, uint32_t bofs, uint32_t* w) {
                constexpr int b0 = decltype(B0)::v, nb = decltype(B1)::v - b0;
                float2 bv[nb];
                #pragma unroll
                for (int i = 0; i < nb; i++) bv[i] = lds64f(bofs + (b0 + i) * 32);
                #pragma unroll
                for (int i = 0; i < nb; i++) {
                    const int b = b0 + i;
                    w[2 * i]     = pack_bf16(gelu_h(fmaf(pv[4 * b], rs0, bv[i].x)), gelu_h(fmaf(pv[4 * b + 1], rs0, bv[i].y)));
                    w[2 * i + 1] = pack_bf16(gelu_h(fmaf(pv[4 * b + 2], rs1, bv[i].x)), gelu_h(fmaf(pv[4 * b + 3], rs1, bv[i].y)));
                }
            };
            auto spill_off = [&]() { uint32_t t_ = c.tid(); return HA + (t_ >> 7) * 8192 + (t_ & 127) * 8; };
            auto reload = [&](auto S0, auto S1) {
                const uint32_t spill = spill_off();
                sfor<decltype(S0)::v * 8, decltype(S1)::v * 8>([&](auto Q) {
                    constexpr int q = decltype(Q)::v;
                    lds64(spill + (q / 8) * 16384 + (q % 8) * 1024, a + q * 2);
                });
            };
            #pragma unroll 1
            for (int idx = 0; idx < 18; idx++) {
                run_step<K_H>(c, hc, a, [&](auto ST) {
                    constexpr int st = decltype(ST)::v;
                    if (idx >= 10) {
                        if constexpr (st < 2) {
                            const uint32_t b_ = v_bid();
                            const uint32_t chunk = (idx == 10) ? 8 : ((b_ + idx - 10) & 7);
                            unsigned char* yp = g_yacc + ((v_epoch() & 1) * 144 + (b_ >> 3) * 9 + chunk) * YT_BYTES + c.tid() * 16;
                            sfor<2 * st, 2 * st + 2>([&](auto Q) {
                                constexpr int q = decltype(Q)::v;
                                asm volatile("red.global.add.noftz.v4.bf16x2 [%0], {%1,%2,%3,%4};" :: "l"(yp + q * 4096),
                                             "r"(pack_bf16(pv[8 * q], pv[8 * q + 1])), "r"(pack_bf16(pv[8 * q + 2], pv[8 * q + 3])),
                                             "r"(pack_bf16(pv[8 * q + 4], pv[8 * q + 5])), "r"(pack_bf16(pv[8 * q + 6], pv[8 * q + 7])) : "memory");
                            });
                            if constexpr (st == 1) event(idx - 7);
                        }
                    } else if (idx >= 1) {
                        const uint32_t bofs = B1S + (idx - 1) * 256 + (c.tid() & 3) * 8;
                        if (idx < 9) {
                            if constexpr (st == 0) {
                                if (idx == OSTEP_AT + 1) {
                                    if ((c.tid() & 31) == 0) asm volatile("cp.async.bulk.wait_group 0;" ::: "memory");
                                    event(2);
                                }
                            }
                            const uint32_t spill = spill_off() + (idx - 1) * 16384;
                            constexpr int b0 = st * 3, b1 = (st == 2 ? 8 : st * 3 + 3);
                            uint32_t w[6];
                            gelun(IC<b0>{}, IC<b1>{}, bofs, w);
                            #pragma unroll
                            for (int b = b0; b < b1; b++) sts64(spill + b * 1024, w[2 * (b - b0)], w[2 * (b - b0) + 1]);
                        } else {
                            if constexpr (st < 2) {
                                const uint32_t tb = tail_off();
                                uint32_t w[8];
                                gelun(IC<st * 4>{}, IC<st * 4 + 4>{}, bofs, w);
                                #pragma unroll
                                for (int i = 0; i < 4; i++) { sts32(tb ^ ((st * 4 + i) << 4), w[2 * i]); sts32((tb ^ ((st * 4 + i) << 4)) + 1024, w[2 * i + 1]); }
                            }
                            if constexpr (st == 1) { fence_async_smem(); named_bar(2 + (c.tid() >> 7), 128); }
                        }
                    } else {
                        if constexpr (st < 2) {
                            constexpr int hf = st;
                            const int t_ = c.tid(), wg = t_ >> 7, t = t_ & 3;
                            float* dst = g_kv + ((v_epoch() & 1) * 8 + (v_bid() & 7)) * 1440;
                            const int d = wg * 32 + ((t_ >> 5) & 3) * 16 + ((t_ >> 2) & 7) + hf * 8;
                            const bool dv = wg ? (d >= 36 && d < 72) : (d < 36);
                            const int e00 = wg * 24 + 2 * t - (d / 18) * 18;
                            float* dp = dst + d * 20 + e00;
                            #pragma unroll
                            for (int i = 0; i < 6; i++) {
                                const int e = e00 + i * 8;
                                const bool blk = wg ? (i >= 1) : (i <= 4);
                                if (dv && blk && e >= 0 && e < 18)
                                    asm volatile("red.global.add.v2.f32 [%0], {%1,%2};" :: "l"(dp + i * 8), "f"(pv[4 * i + 2 * hf]), "f"(pv[4 * i + 2 * hf + 1]) : "memory");
                            }
                            if (dv && t == 0) atomicAdd(dst + d * 20 + 18, wg ? pv[2 * hf] : pv[20 + 2 * hf]);
                            if constexpr (st == 1) event(1);
                        }
                    }
                }, [&](auto ST) {
                    constexpr int st = decltype(ST)::v;
                    if (idx == 8) {
                        reload(IC<3 * st>{}, IC<(st == 2 ? 8 : 3 * st + 3)>{});
                        if constexpr (st == 2) warp_arrive(bar(B_OFREE));
                    }
                });
                reg_copy<32>(pv, hc);
                prof(8 + idx);
                if (idx == OSTEP_AT) {
                    mbar_wait(bar(B_KVB), 0);
                    prof(34);
                    const uint32_t pqo = (c.tid() >> 7) * 576;
                    const int t_ = c.tid(), b_ = v_bid(), t = t_ & 3, l4 = t_ & 28;
                    const uint32_t op = OST + ((t_ >> 5) * 16 + ((t_ >> 2) & 7)) * 144 + t * 4;
                    float r3[2];
                    sfor<0, 2>([&](auto PS) {
                        constexpr int ps = decltype(PS)::v;
                        wg_fence();
                        sfor<0, 5>([&](auto KS) {
                            constexpr int ks = decltype(KS)::v;
                            wg_ss64<(ks ? 1 : 0)>(hc, mkdesc(PQT + ks * 2048, ks == 4 ? 0 : 1024, 128, 0) + pqo, mkdesc(KVB + ps * 8 * 1280 + ks * 256, 128, 1280, 0));
                        });
                        wg_commit();
                        wg_wait<0>();
                        reg_fence<32>(hc);
                        #pragma unroll
                        for (int hf = 0; hf < 2; hf++) {
                            if constexpr (ps == 0) {
                                float r[4];
                                r[0] = rcp(__shfl_sync(0xffffffffu, hc[2 * hf], l4) + 1e-6f);
                                r[1] = rcp(__shfl_sync(0xffffffffu, hc[1 + 2 * hf], l4) + 1e-6f);
                                r[2] = rcp(__shfl_sync(0xffffffffu, hc[2 * hf], l4 + 1) + 1e-6f);
                                r[3] = rcp(__shfl_sync(0xffffffffu, hc[1 + 2 * hf], l4 + 1) + 1e-6f);
                                r3[hf] = r[3];
                                #pragma unroll
                                for (int i = 0; i < 7; i++) {
                                    float rr = (i < 2) ? r[0] : (i == 2) ? (t < 1 ? r[0] : r[1]) : (i == 3) ? r[1] : (i == 4) ? (t < 2 ? r[1] : r[2])
                                             : (i == 5) ? r[2] : (t < 3 ? r[2] : r[3]);
                                    sts32(op + hf * 8 * 144 + i * 16, pack_bf16(hc[4 * i + 4 + 2 * hf] * rr, hc[4 * i + 5 + 2 * hf] * rr));
                                }
                            } else {
                                #pragma unroll
                                for (int i = 0; i < 2; i++)
                                    sts32(op + hf * 8 * 144 + 112 + i * 16, pack_bf16(hc[4 * i + 2 * hf] * r3[hf], hc[4 * i + 1 + 2 * hf] * r3[hf]));
                            }
                        }
                    });
                    fence_async_smem();
                    __syncwarp();
                    if ((t_ & 31) == 0) {
                        asm volatile("cp.async.bulk.tensor.2d.global.shared::cta.bulk_group [%0, {%2, %3}], [%1];"
                                     :: "l"(&tm_ost), "r"(OST + (t_ >> 5) * 2304), "r"((b_ & 7) * 72), "r"((b_ >> 3) * 128 + (t_ >> 5) * 16) : "memory");
                        asm volatile("cp.async.bulk.commit_group;" ::: "memory");
                    }
                }
            }
        }
        if (is_main) warp_arrive(bar(B_O8FREE));
        else {
            mbar_wait(bar(B_INIT), 0);
            #pragma unroll
            for (int i = 0; i < 32; i++) { asm volatile("mov.b32 %0, 0;" : "=f"(hc[i])); asm volatile("mov.b32 %0, 0;" : "=f"(pv[i])); }
        }
        auto add_b2 = [&]() {
            #pragma unroll
            for (int b = 0; b < 8; b++) {
                float2 bv = lds64f(B2S + b * 32 + (c.tid() & 3) * 8);
                pv[4 * b] += bv.x; pv[4 * b + 1] += bv.y; pv[4 * b + 2] += bv.x; pv[4 * b + 3] += bv.y;
            }
        };
        auto load_xy = [&](int ftile, int nrdy, uint32_t* xr, uint32_t* yv) {
            const int mt = ftile / 9, ch = ftile - mt * 9;
            const uint32_t t_ = c.tid();
            const __nv_bfloat16* xp = p.x + (size_t)(mt * 128 + (t_ >> 5) * 16 + ((t_ >> 2) & 7)) * DM + ch * 64 + 2 * (t_ & 3);
            #pragma unroll
            for (int i = 0; i < 8; i++) {
                asm volatile("ld.global.nc.u32 %0, [%1];" : "=r"(xr[2 * i]) : "l"(xp + i * 8));
                asm volatile("ld.global.nc.u32 %0, [%1];" : "=r"(xr[2 * i + 1]) : "l"(xp + 8 * DM + i * 8));
            }
            prof(26);
            smem_wait_gt(EPO + 4, nrdy);
            prof(27);
            const unsigned char* yp = g_yacc + ((v_epoch() & 1) * 144 + ftile) * YT_BYTES + t_ * 16;
            #pragma unroll
            for (int q = 0; q < YT_BYTES / 4096; q++)
                asm volatile("ld.global.cg.v4.u32 {%0,%1,%2,%3}, [%4];" : "=r"(yv[4 * q]), "=r"(yv[4 * q + 1]), "=r"(yv[4 * q + 2]), "=r"(yv[4 * q + 3]) : "l"(yp + q * 4096) : "memory");
        };
        auto gate = [&](const uint32_t* yv) {
            #pragma unroll
            for (int i = 0; i < 16; i++) { pv[2 * i] += bf_lo(yv[i]); pv[2 * i + 1] += bf_hi(yv[i]); }
            #pragma unroll
            for (int i = 0; i < 32; i++) { const float h = 0.5f * pv[i]; pv[i] = fmaf(h, tanh_ap(h), h); }
        };
        auto store_out = [&](int ftile, const uint32_t* xr) {
            const int mt = ftile / 9, ch = ftile - mt * 9;
            const uint32_t t_ = c.tid();
            const bool odd = t_ & 1;
            __nv_bfloat16* op = p.out + (size_t)(mt * 128 + (t_ >> 5) * 16 + ((t_ >> 2) & 7)) * DM + ch * 64 + (t_ & 2) * 2 + (t_ & 1) * 8;
            #pragma unroll
            for (int b = 0; b < 8; b += 2) {
                #pragma unroll
                for (int hf = 0; hf < 2; hf++) {
                    const int i0 = 4 * b + 2 * hf, i1 = i0 + 4;
                    const uint32_t w0 = pack_bf16(fmaf(hc[i0], pv[i0], bf_lo(xr[2 * b + hf])), fmaf(hc[i0 + 1], pv[i0 + 1], bf_hi(xr[2 * b + hf])));
                    const uint32_t w1 = pack_bf16(fmaf(hc[i1], pv[i1], bf_lo(xr[2 * b + 2 + hf])), fmaf(hc[i1 + 1], pv[i1 + 1], bf_hi(xr[2 * b + 2 + hf])));
                    const uint32_t r = __shfl_xor_sync(0xffffffffu, odd ? w0 : w1, 1);
                    *reinterpret_cast<uint2*>(op + hf * 8 * DM + b * 8) = odd ? make_uint2(r, w1) : make_uint2(w0, r);
                }
            }
        };
        const int njob = is_main ? 1 : 4;
        #pragma unroll 1
        for (int job = 0; job < njob; job++) {
            const uint32_t jpar = job & 1;
            const uint32_t b_ = v_bid();
            const bool mainf = b_ < NMAIN;
            const int ftile = (b_ >> 3) * 9 + (b_ & 7);
            uint32_t oa[128];
            {
                mbar_wait(bar(B_OFULL), jpar);
                const uint32_t lrow = lrow_off();
                sfor<0, 32>([&](auto KS) {
                    constexpr int ks = decltype(KS)::v;
                    ldsm4((lrow ^ ((ks % 4) << 5)) + (ks / 4) * 16384, oa + ks * 4);
                });
                warp_arrive(bar(B_OFREE));
                if (job) c.tph ^= 1;
            }
            c.pf = false;
            run_step<K_H>(c, hc, oa, [&](auto ST) {
                constexpr int st = decltype(ST)::v;
                if (mainf) {
                    if constexpr (st == 0) add_b2();
                    else if constexpr (st == 1) load_xy(ftile, 0, oa, oa + 16);
                    else { prof(28); gate(oa + 16); prof(29); }
                }
                if constexpr (st == 1) mbar_wait(bar(B_O8FULL), jpar);
            }, [](auto) {}, job == njob - 1);
            prof(30);
            if (mainf) {
                store_out(ftile, oa);
            } else {
                warp_arrive(bar(B_O8FREE));
                uint4* sp = reinterpret_cast<uint4*>(g_s8) + ((b_ - NMAIN) * 4 + job) * 1024 + c.tid();
                #pragma unroll
                for (int q = 0; q < 4; q++)
                    sp[q * 256] = make_uint4(pack_bf16(hc[8 * q], hc[8 * q + 1]), pack_bf16(hc[8 * q + 2], hc[8 * q + 3]),
                                             pack_bf16(hc[8 * q + 4], hc[8 * q + 5]), pack_bf16(hc[8 * q + 6], hc[8 * q + 7]));
                prof(8 + job);
            }
        }
        if (!is_main) {
            #pragma unroll 1
            for (int job = 0; job < 4; job++) {
                const int tile = (v_bid() - NMAIN) * 4 + job;
                uint32_t xr[16], yv[YT_BYTES / 1024];
                const uint4* sp = reinterpret_cast<const uint4*>(g_s8) + tile * 1024 + c.tid();
                #pragma unroll
                for (int q = 0; q < 4; q++) {
                    const uint4 u = __ldcg(sp + q * 256);
                    hc[8 * q] = bf_lo(u.x); hc[8 * q + 1] = bf_hi(u.x); hc[8 * q + 2] = bf_lo(u.y); hc[8 * q + 3] = bf_hi(u.y);
                    hc[8 * q + 4] = bf_lo(u.z); hc[8 * q + 5] = bf_hi(u.z); hc[8 * q + 6] = bf_lo(u.w); hc[8 * q + 7] = bf_hi(u.w);
                }
                #pragma unroll
                for (int i = 0; i < 32; i++) pv[i] = 0.f;
                add_b2();
                load_xy(tile * 9 + 8, job, xr, yv);
                gate(yv);
                store_out(tile * 9 + 8, xr);
                prof(12 + job);
            }
        }
        prof(40);
        if (c.tid() == 0) g_epoch[v_bid()] = v_epoch() + 1;
    }
}

typedef CUresult (*EncodeFn)(CUtensorMap*, CUtensorMapDataType, cuuint32_t, void*, const cuuint64_t*, const cuuint64_t*,
                             const cuuint32_t*, const cuuint32_t*, CUtensorMapInterleave, CUtensorMapSwizzle,
                             CUtensorMapL2promotion, CUtensorMapFloatOOBfill);

void make_map(EncodeFn enc, CUtensorMap* tm, const void* base, int rows, int cols, int box_rows, int box_cols = 64, bool swz = true) {
    cuuint64_t gdim[2] = {(cuuint64_t)cols, (cuuint64_t)rows};
    cuuint64_t gstr[1] = {(cuuint64_t)cols * 2};
    cuuint32_t box[2] = {(cuuint32_t)box_cols, (cuuint32_t)box_rows};
    cuuint32_t estr[2] = {1, 1};
    enc(tm, CU_TENSOR_MAP_DATA_TYPE_BFLOAT16, 2, const_cast<void*>(base), gdim, gstr, box, estr, CU_TENSOR_MAP_INTERLEAVE_NONE,
        swz ? CU_TENSOR_MAP_SWIZZLE_128B : CU_TENSOR_MAP_SWIZZLE_NONE, CU_TENSOR_MAP_L2_PROMOTION_L2_128B, CU_TENSOR_MAP_FLOAT_OOB_FILL_NONE);
}

}

extern "C" void kernel_launch(void* const* d_in, const int* in_sizes, int n_in, void* d_out, int out_size) {
    static EncodeFn enc = nullptr;
    static void* o_ptr = nullptr;
    if (!enc) {
        void* fn = nullptr;
        cudaDriverEntryPointQueryResult qr;
        cudaGetDriverEntryPoint("cuTensorMapEncodeTiled", &fn, cudaEnableDefault, &qr);
        enc = (EncodeFn)fn;
        cudaGetSymbolAddress(&o_ptr, g_o);
        cudaFuncSetAttribute(fused_kernel, cudaFuncAttributeMaxDynamicSharedMemorySize, SMEM_BYTES);
    }
    Params p;
    p.x = (const __nv_bfloat16*)d_in[0];
    p.wqkv = (const __nv_bfloat16*)d_in[1];
    p.wo = (const __nv_bfloat16*)d_in[2];
    p.w1 = (const __nv_bfloat16*)d_in[4];
    p.b1 = (const __nv_bfloat16*)d_in[5];
    p.w2 = (const __nv_bfloat16*)d_in[6];
    p.b2 = (const __nv_bfloat16*)d_in[7];
    p.out = (__nv_bfloat16*)d_out;
    CUtensorMap tm_x, tm_w1, tm_w2, tm_wo, tm_o, tm_qkv, tm_qkve, tm_ost;
    make_map(enc, &tm_ost, o_ptr, SEQ, DM, 16, 72, false);
    make_map(enc, &tm_qkv, p.wqkv, DM, 3 * DM, 96);
    make_map(enc, &tm_qkve, p.wqkv, DM, 3 * DM, 96, 8);
    make_map(enc, &tm_x, p.x, SEQ, DM, 128);
    make_map(enc, &tm_w1, p.w1, DM, FF, 192);
    make_map(enc, &tm_w2, p.w2, FF, DM, 192);
    make_map(enc, &tm_wo, p.wo, DM, DM, 192);
    make_map(enc, &tm_o, o_ptr, SEQ, DM, 128);
    fused_kernel<<<NMAIN + NAUX, 384, SMEM_BYTES>>>(tm_x, tm_w1, tm_w2, tm_wo, tm_o, tm_qkv, tm_qkve, tm_ost, p);
}
```

```cpp
#include <cuda_runtime.h>
#include <cuda.h>
#include <cuda_bf16.h>
#include <stdint.h>

#define OSTEP_AT 4
#define PF1_NS 1500
#define PF2_NS 2000
#define PFIDX 3
#define PF3_NS 800
#define PF0_NS 1200
#define SIG_NS 64
#define POLL_NS 100
#define YF32 0

namespace {
constexpr int WAIT_ITERS = 3000000;

constexpr int SEQ = 2048, DM = 576, FF = 4608;
constexpr int NMAIN = 128, NAUX = 4;

constexpr uint32_t SB    = 0x400;
constexpr uint32_t HA    = SB;
constexpr uint32_t XB    = SB + 131072;
constexpr uint32_t RING  = SB + 147456;
constexpr uint32_t SLOT  = 24576;
constexpr uint32_t MISC  = SB + 221184;
constexpr uint32_t BARS  = MISC;
constexpr uint32_t B1S   = MISC + 512;
constexpr uint32_t B2S   = MISC + 2816;
constexpr uint32_t EPO   = MISC + 3072;
constexpr uint32_t EVC   = MISC + 3104;
constexpr uint32_t SMEM_BYTES = 221184 + 3200 + 512;
constexpr uint32_t PKT   = HA + 32768;
constexpr uint32_t VT    = HA + 51200;
constexpr uint32_t OST   = HA + 79872;
constexpr uint32_t PQT   = HA + 98304;
constexpr uint32_t KVB   = HA + 116736;

enum { B_FULL = 0  , B_EMPTY = 6  , B_XFULL = 12, B_OFULL = 15, B_O8FULL = 16, B_OFREE = 17, B_O8FREE = 18, B_KVB = 19, B_INIT = 20, B_COUNT = 21 };
__host__ __device__ constexpr uint32_t qslot(int i) { return i < 3 ? RING + i * SLOT : i == 3 ? HA : i == 4 ? HA + 73728 : HA + 98304; }
__device__ __forceinline__ constexpr uint32_t bar(int i) { return BARS + 8u * i; }

constexpr int YT_BYTES = YF32 ? 32768 : 16384;
__device__ __align__(1024) __nv_bfloat16 g_o[SEQ * DM];
__device__ __align__(1024) unsigned char g_yacc[2 * 16 * 9 * YT_BYTES];
__device__ __align__(128) float g_kv[2 * 8 * 72 * 20];
__device__ __align__(128) unsigned int g_s8[16 * 4096];
__device__ __align__(128) unsigned int g_cnt[(8 + 16 + 16 * 9) * 8];
__device__ unsigned int g_epoch[NMAIN + NAUX];
__device__ __forceinline__ unsigned int* cnt_kv(int j) { return g_cnt + j * 8; }
__device__ __forceinline__ unsigned int* cnt_o(int m) { return g_cnt + (8 + m) * 8; }
__device__ __forceinline__ unsigned int* cnt_y(int m, int c) { return g_cnt + (24 + m * 9 + c) * 8; }

__device__ __forceinline__ void mbar_init(uint32_t b, uint32_t cnt) { asm volatile("mbarrier.init.shared::cta.b64 [%0], %1;" :: "r"(b), "r"(cnt)); }
__device__ __forceinline__ void mbar_expect_tx(uint32_t b, uint32_t bytes) { asm volatile("mbarrier.arrive.expect_tx.shared::cta.b64 _, [%0], %1;" :: "r"(b), "r"(bytes) : "memory"); }
__device__ __forceinline__ void mbar_arrive(uint32_t b) { asm volatile("mbarrier.arrive.shared::cta.b64 _, [%0];" :: "r"(b) : "memory"); }
__device__ __forceinline__ void prof(int) {}
__device__ __forceinline__ void mbar_wait(uint32_t b, uint32_t parity) {
    asm volatile("{\n.reg .pred p;\n.reg .u32 c;\nmov.u32 c, 0;\n"
                 "WAIT_LOOP:\nmbarrier.try_wait.parity.shared::cta.b64 p, [%0], %1;\n@p bra WAIT_DONE;\n"
                 "add.u32 c, c, 1;\nsetp.lt.u32 p, c, 20000000;\n@p bra WAIT_LOOP;\ntrap;\nWAIT_DONE:\n}"
                 :: "r"(b), "r"(parity) : "memory");
}
__device__ __forceinline__ void smem_wait_gt(uint32_t addr, uint32_t val) {
    asm volatile("{\n.reg .pred p;\n.reg .u32 c, v;\nmov.u32 c, 0;\n"
                 "SW_LOOP:\nld.acquire.cta.shared.u32 v, [%0];\nsetp.gt.u32 p, v, %1;\n@p bra SW_DONE;\n"
                 "nanosleep.u32 64;\nadd.u32 c, c, 1;\nsetp.lt.u32 p, c, 20000000;\n@p bra SW_LOOP;\ntrap;\nSW_DONE:\n}"
                 :: "r"(addr), "r"(val) : "memory");
}
__device__ __forceinline__ void tma_2d(uint32_t dst, const CUtensorMap* tm, uint32_t b, int c0, int c1) {
    asm volatile("cp.async.bulk.tensor.2d.shared::cluster.global.mbarrier::complete_tx::bytes [%0], [%1, {%3, %4}], [%2];"
                 :: "r"(dst), "l"(tm), "r"(b), "r"(c0), "r"(c1) : "memory");
}
__device__ __forceinline__ void fence_async_smem() { asm volatile("fence.proxy.async.shared::cta;" ::: "memory"); }
__device__ __forceinline__ void fence_async_all() { asm volatile("fence.proxy.async;" ::: "memory"); }
__device__ __forceinline__ void named_bar(int id, int n) { asm volatile("bar.sync %0, %1;" :: "r"(id), "r"(n) : "memory"); }
__device__ __forceinline__ void wg_fence() { asm volatile("wgmma.fence.sync.aligned;" ::: "memory"); }
__device__ __forceinline__ void wg_commit() { asm volatile("wgmma.commit_group.sync.aligned;" ::: "memory"); }
template<int N> __device__ __forceinline__ void wg_wait() { asm volatile("wgmma.wait_group.sync.aligned %0;" :: "n"(N) : "memory"); }
template<int N> __device__ __forceinline__ void reg_fence(float* d) {
    #pragma unroll
    for (int i = 0; i < N; i++) asm volatile("" : "+f"(d[i]) :: "memory");
}
template<int N> __device__ __forceinline__ void reg_copy(float* d, const float* s) {
    #pragma unroll
    for (int i = 0; i < N; i++) asm volatile("mov.b32 %0, %1;" : "=f"(d[i]) : "f"(s[i]));
}
__device__ __forceinline__ uint32_t pack_bf16(float lo, float hi) { uint32_t r; asm("cvt.rn.bf16x2.f32 %0, %1, %2;" : "=r"(r) : "f"(hi), "f"(lo)); return r; }
__device__ __forceinline__ float bf_lo(uint32_t v) { return __uint_as_float(v << 16); }
__device__ __forceinline__ float bf_hi(uint32_t v) { return __uint_as_float(v & 0xffff0000u); }
__device__ __forceinline__ uint32_t sub_bf16x2(uint32_t a, uint32_t b) { uint32_t r; asm("sub.rn.bf16x2 %0, %1, %2;" : "=r"(r) : "r"(a), "r"(b)); return r; }
__device__ __forceinline__ float ex2(float x) { float r; asm("ex2.approx.ftz.f32 %0, %1;" : "=f"(r) : "f"(x)); return r; }
__device__ __forceinline__ float rcp(float x) { float r; asm("rcp.approx.ftz.f32 %0, %1;" : "=f"(r) : "f"(x)); return r; }
__device__ __forceinline__ float tanh_ap(float x) { float r; asm("tanh.approx.f32 %0, %1;" : "=f"(r) : "f"(x)); return r; }
__device__ __forceinline__ void sts32(uint32_t a, uint32_t v) { asm volatile("st.shared.b32 [%0], %1;" :: "r"(a), "r"(v)); }
__device__ __forceinline__ void sts128(uint32_t a, uint32_t x, uint32_t y, uint32_t z, uint32_t w) { asm volatile("st.shared.v4.b32 [%0], {%1,%2,%3,%4};" :: "r"(a), "r"(x), "r"(y), "r"(z), "r"(w)); }
__device__ __forceinline__ void sts64(uint32_t a, uint32_t x, uint32_t y) { asm volatile("st.shared.v2.b32 [%0], {%1,%2};" :: "r"(a), "r"(x), "r"(y)); }
__device__ __forceinline__ void lds64(uint32_t a, uint32_t* v) { asm volatile("ld.shared.v2.b32 {%0,%1}, [%2];" : "=r"(v[0]), "=r"(v[1]) : "r"(a)); }
__device__ __forceinline__ float2 lds64f(uint32_t a) { float2 v; asm("ld.shared.v2.f32 {%0,%1}, [%2];" : "=f"(v.x), "=f"(v.y) : "r"(a)); return v; }
__device__ __forceinline__ void ldsm4(uint32_t a, uint32_t* v) {
    asm volatile("ldmatrix.sync.aligned.m8n8.x4.shared.b16 {%0,%1,%2,%3}, [%4];" : "=r"(v[0]), "=r"(v[1]), "=r"(v[2]), "=r"(v[3]) : "r"(a));
}
__device__ __forceinline__ void mma_ones(float* c, const uint32_t* a) {
    const uint32_t one2 = 0x3F803F80u;
    asm volatile("mma.sync.aligned.m16n8k16.row.col.f32.bf16.bf16.f32 {%0,%1,%2,%3}, {%4,%5,%6,%7}, {%8,%8}, {%0,%1,%2,%3};"
                 : "+f"(c[0]), "+f"(c[1]), "+f"(c[2]), "+f"(c[3]) : "r"(a[0]), "r"(a[1]), "r"(a[2]), "r"(a[3]), "r"(one2));
}
__device__ __forceinline__ unsigned int ld_acquire(const unsigned int* p) { unsigned int v; asm volatile("ld.acquire.gpu.global.u32 %0, [%1];" : "=r"(v) : "l"(p) : "memory"); return v; }
__device__ __forceinline__ void wait_cnt(const unsigned int* p, unsigned int target) {
    for (int i = 0; i < WAIT_ITERS; i++) {
        if ((int)(ld_acquire(p) - target) >= 0) return;
        __nanosleep(POLL_NS);
    }
    __trap();
}
__device__ __forceinline__ uint32_t v_tid() { uint32_t r; asm volatile("mov.u32 %0, %%tid.x;" : "=r"(r)); return r; }
__device__ __forceinline__ uint32_t v_bid() { uint32_t r; asm volatile("mov.u32 %0, %%ctaid.x;" : "=r"(r)); return r; }
__device__ __forceinline__ uint32_t v_epoch() { uint32_t r; asm volatile("ld.shared.u32 %0, [%1];" : "=r"(r) : "r"(EPO)); return r; }
__device__ __forceinline__ void prefetch_l2(const void* p) { asm volatile("prefetch.global.L2 [%0];" :: "l"(p)); }

__host__ __device__ constexpr uint64_t mkdesc(uint32_t addr, uint32_t lbo, uint32_t sbo, uint32_t swz) {
    return (uint64_t)((addr & 0x3FFFF) >> 4) | ((uint64_t)((lbo >> 4) & 0x3FFF) << 16) | ((uint64_t)((sbo >> 4) & 0x3FFF) << 32) | ((uint64_t)swz << 62);
}

template<int SD> __device__ __forceinline__ void wg_rs64(float* d, const uint32_t* a, uint64_t bd) {
  if constexpr (SD) {
    asm volatile("{\n.reg .pred p;\nsetp.eq.b32 p, 0, 0;\n"
    "wgmma.mma_async.sync.aligned.m64n64k16.f32.bf16.bf16 {%0,%1,%2,%3,%4,%5,%6,%7,%8,%9,%10,%11,%12,%13,%14,%15,%16,%17,%18,%19,%20,%21,%22,%23,%24,%25,%26,%27,%28,%29,%30,%31}, {%32,%33,%34,%35}, %36, p, 1, 1, 1;\n}"
    : "+f"(d[0]),"+f"(d[1]),"+f"(d[2]),"+f"(d[3]),"+f"(d[4]),"+f"(d[5]),"+f"(d[6]),"+f"(d[7]),"+f"(d[8]),"+f"(d[9]),"+f"(d[10]),"+f"(d[11]),"+f"(d[12]),"+f"(d[13]),"+f"(d[14]),"+f"(d[15]),"+f"(d[16]),"+f"(d[17]),"+f"(d[18]),"+f"(d[19]),"+f"(d[20]),"+f"(d[21]),"+f"(d[22]),"+f"(d[23]),"+f"(d[24]),"+f"(d[25]),"+f"(d[26]),"+f"(d[27]),"+f"(d[28]),"+f"(d[29]),"+f"(d[30]),"+f"(d[31])
    : "r"(a[0]),"r"(a[1]),"r"(a[2]),"r"(a[3]), "l"(bd));
  } else {
    asm volatile("{\n.reg .pred p;\nsetp.ne.b32 p, 0, 0;\n"
    "wgmma.mma_async.sync.aligned.m64n64k16.f32.bf16.bf16 {%0,%1,%2,%3,%4,%5,%6,%7,%8,%9,%10,%11,%12,%13,%14,%15,%16,%17,%18,%19,%20,%21,%22,%23,%24,%25,%26,%27,%28,%29,%30,%31}, {%32,%33,%34,%35}, %36, p, 1, 1, 1;\n}"
    : "+f"(d[0]),"+f"(d[1]),"+f"(d[2]),"+f"(d[3]),"+f"(d[4]),"+f"(d[5]),"+f"(d[6]),"+f"(d[7]),"+f"(d[8]),"+f"(d[9]),"+f"(d[10]),"+f"(d[11]),"+f"(d[12]),"+f"(d[13]),"+f"(d[14]),"+f"(d[15]),"+f"(d[16]),"+f"(d[17]),"+f"(d[18]),"+f"(d[19]),"+f"(d[20]),"+f"(d[21]),"+f"(d[22]),"+f"(d[23]),"+f"(d[24]),"+f"(d[25]),"+f"(d[26]),"+f"(d[27]),"+f"(d[28]),"+f"(d[29]),"+f"(d[30]),"+f"(d[31])
    : "r"(a[0]),"r"(a[1]),"r"(a[2]),"r"(a[3]), "l"(bd));
  }
}
template<int SD> __device__ __forceinline__ void wg_ss64(float* d, uint64_t ad, uint64_t bd) {
  if constexpr (SD) {
    asm volatile("{\n.reg .pred p;\nsetp.eq.b32 p, 0, 0;\n"
    "wgmma.mma_async.sync.aligned.m64n64k16.f32.bf16.bf16 {%0,%1,%2,%3,%4,%5,%6,%7,%8,%9,%10,%11,%12,%13,%14,%15,%16,%17,%18,%19,%20,%21,%22,%23,%24,%25,%26,%27,%28,%29,%30,%31}, %32, %33, p, 1, 1, 0, 1;\n}"
    : "+f"(d[0]),"+f"(d[1]),"+f"(d[2]),"+f"(d[3]),"+f"(d[4]),"+f"(d[5]),"+f"(d[6]),"+f"(d[7]),"+f"(d[8]),"+f"(d[9]),"+f"(d[10]),"+f"(d[11]),"+f"(d[12]),"+f"(d[13]),"+f"(d[14]),"+f"(d[15]),"+f"(d[16]),"+f"(d[17]),"+f"(d[18]),"+f"(d[19]),"+f"(d[20]),"+f"(d[21]),"+f"(d[22]),"+f"(d[23]),"+f"(d[24]),"+f"(d[25]),"+f"(d[26]),"+f"(d[27]),"+f"(d[28]),"+f"(d[29]),"+f"(d[30]),"+f"(d[31])
    : "l"(ad), "l"(bd));
  } else {
    asm volatile("{\n.reg .pred p;\nsetp.ne.b32 p, 0, 0;\n"
    "wgmma.mma_async.sync.aligned.m64n64k16.f32.bf16.bf16 {%0,%1,%2,%3,%4,%5,%6,%7,%8,%9,%10,%11,%12,%13,%14,%15,%16,%17,%18,%19,%20,%21,%22,%23,%24,%25,%26,%27,%28,%29,%30,%31}, %32, %33, p, 1, 1, 0, 1;\n}"
    : "+f"(d[0]),"+f"(d[1]),"+f"(d[2]),"+f"(d[3]),"+f"(d[4]),"+f"(d[5]),"+f"(d[6]),"+f"(d[7]),"+f"(d[8]),"+f"(d[9]),"+f"(d[10]),"+f"(d[11]),"+f"(d[12]),"+f"(d[13]),"+f"(d[14]),"+f"(d[15]),"+f"(d[16]),"+f"(d[17]),"+f"(d[18]),"+f"(d[19]),"+f"(d[20]),"+f"(d[21]),"+f"(d[22]),"+f"(d[23]),"+f"(d[24]),"+f"(d[25]),"+f"(d[26]),"+f"(d[27]),"+f"(d[28]),"+f"(d[29]),"+f"(d[30]),"+f"(d[31])
    : "l"(ad), "l"(bd));
  }
}
template<int SD> __device__ __forceinline__ void wg_rs72(float* d, const uint32_t* a, uint64_t bd) {
  if constexpr (SD) {
    asm volatile("{\n.reg .pred p;\nsetp.eq.b32 p, 0, 0;\n"
    "wgmma.mma_async.sync.aligned.m64n72k16.f32.bf16.bf16 {%0,%1,%2,%3,%4,%5,%6,%7,%8,%9,%10,%11,%12,%13,%14,%15,%16,%17,%18,%19,%20,%21,%22,%23,%24,%25,%26,%27,%28,%29,%30,%31,%32,%33,%34,%35}, {%36,%37,%38,%39}, %40, p, 1, 1, 1;\n}"
    : "+f"(d[0]),"+f"(d[1]),"+f"(d[2]),"+f"(d[3]),"+f"(d[4]),"+f"(d[5]),"+f"(d[6]),"+f"(d[7]),"+f"(d[8]),"+f"(d[9]),"+f"(d[10]),"+f"(d[11]),"+f"(d[12]),"+f"(d[13]),"+f"(d[14]),"+f"(d[15]),"+f"(d[16]),"+f"(d[17]),"+f"(d[18]),"+f"(d[19]),"+f"(d[20]),"+f"(d[21]),"+f"(d[22]),"+f"(d[23]),"+f"(d[24]),"+f"(d[25]),"+f"(d[26]),"+f"(d[27]),"+f"(d[28]),"+f"(d[29]),"+f"(d[30]),"+f"(d[31]),"+f"(d[32]),"+f"(d[33]),"+f"(d[34]),"+f"(d[35])
    : "r"(a[0]),"r"(a[1]),"r"(a[2]),"r"(a[3]), "l"(bd));
  } else {
    asm volatile("{\n.reg .pred p;\nsetp.ne.b32 p, 0, 0;\n"
    "wgmma.mma_async.sync.aligned.m64n72k16.f32.bf16.bf16 {%0,%1,%2,%3,%4,%5,%6,%7,%8,%9,%10,%11,%12,%13,%14,%15,%16,%17,%18,%19,%20,%21,%22,%23,%24,%25,%26,%27,%28,%29,%30,%31,%32,%33,%34,%35}, {%36,%37,%38,%39}, %40, p, 1, 1, 1;\n}"
    : "+f"(d[0]),"+f"(d[1]),"+f"(d[2]),"+f"(d[3]),"+f"(d[4]),"+f"(d[5]),"+f"(d[6]),"+f"(d[7]),"+f"(d[8]),"+f"(d[9]),"+f"(d[10]),"+f"(d[11]),"+f"(d[12]),"+f"(d[13]),"+f"(d[14]),"+f"(d[15]),"+f"(d[16]),"+f"(d[17]),"+f"(d[18]),"+f"(d[19]),"+f"(d[20]),"+f"(d[21]),"+f"(d[22]),"+f"(d[23]),"+f"(d[24]),"+f"(d[25]),"+f"(d[26]),"+f"(d[27]),"+f"(d[28]),"+f"(d[29]),"+f"(d[30]),"+f"(d[31]),"+f"(d[32]),"+f"(d[33]),"+f"(d[34]),"+f"(d[35])
    : "r"(a[0]),"r"(a[1]),"r"(a[2]),"r"(a[3]), "l"(bd));
  }
}
template<int SD> __device__ __forceinline__ void wg_ss72(float* d, uint64_t ad, uint64_t bd) {
  if constexpr (SD) {
    asm volatile("{\n.reg .pred p;\nsetp.eq.b32 p, 0, 0;\n"
    "wgmma.mma_async.sync.aligned.m64n72k16.f32.bf16.bf16 {%0,%1,%2,%3,%4,%5,%6,%7,%8,%9,%10,%11,%12,%13,%14,%15,%16,%17,%18,%19,%20,%21,%22,%23,%24,%25,%26,%27,%28,%29,%30,%31,%32,%33,%34,%35}, %36, %37, p, 1, 1, 0, 1;\n}"
    : "+f"(d[0]),"+f"(d[1]),"+f"(d[2]),"+f"(d[3]),"+f"(d[4]),"+f"(d[5]),"+f"(d[6]),"+f"(d[7]),"+f"(d[8]),"+f"(d[9]),"+f"(d[10]),"+f"(d[11]),"+f"(d[12]),"+f"(d[13]),"+f"(d[14]),"+f"(d[15]),"+f"(d[16]),"+f"(d[17]),"+f"(d[18]),"+f"(d[19]),"+f"(d[20]),"+f"(d[21]),"+f"(d[22]),"+f"(d[23]),"+f"(d[24]),"+f"(d[25]),"+f"(d[26]),"+f"(d[27]),"+f"(d[28]),"+f"(d[29]),"+f"(d[30]),"+f"(d[31]),"+f"(d[32]),"+f"(d[33]),"+f"(d[34]),"+f"(d[35])
    : "l"(ad), "l"(bd));
  } else {
    asm volatile("{\n.reg .pred p;\nsetp.ne.b32 p, 0, 0;\n"
    "wgmma.mma_async.sync.aligned.m64n72k16.f32.bf16.bf16 {%0,%1,%2,%3,%4,%5,%6,%7,%8,%9,%10,%11,%12,%13,%14,%15,%16,%17,%18,%19,%20,%21,%22,%23,%24,%25,%26,%27,%28,%29,%30,%31,%32,%33,%34,%35}, %36, %37, p, 1, 1, 0, 1;\n}"
    : "+f"(d[0]),"+f"(d[1]),"+f"(d[2]),"+f"(d[3]),"+f"(d[4]),"+f"(d[5]),"+f"(d[6]),"+f"(d[7]),"+f"(d[8]),"+f"(d[9]),"+f"(d[10]),"+f"(d[11]),"+f"(d[12]),"+f"(d[13]),"+f"(d[14]),"+f"(d[15]),"+f"(d[16]),"+f"(d[17]),"+f"(d[18]),"+f"(d[19]),"+f"(d[20]),"+f"(d[21]),"+f"(d[22]),"+f"(d[23]),"+f"(d[24]),"+f"(d[25]),"+f"(d[26]),"+f"(d[27]),"+f"(d[28]),"+f"(d[29]),"+f"(d[30]),"+f"(d[31]),"+f"(d[32]),"+f"(d[33]),"+f"(d[34]),"+f"(d[35])
    : "l"(ad), "l"(bd));
  }
}
template<int SD> __device__ __forceinline__ void wg_tt64(float* d, uint64_t ad, uint64_t bd) {
  if constexpr (SD) {
    asm volatile("{\n.reg .pred p;\nsetp.eq.b32 p, 0, 0;\n"
    "wgmma.mma_async.sync.aligned.m64n64k16.f32.bf16.bf16 {%0,%1,%2,%3,%4,%5,%6,%7,%8,%9,%10,%11,%12,%13,%14,%15,%16,%17,%18,%19,%20,%21,%22,%23,%24,%25,%26,%27,%28,%29,%30,%31}, %32, %33, p, 1, 1, 1, 1;\n}"
    : "+f"(d[0]),"+f"(d[1]),"+f"(d[2]),"+f"(d[3]),"+f"(d[4]),"+f"(d[5]),"+f"(d[6]),"+f"(d[7]),"+f"(d[8]),"+f"(d[9]),"+f"(d[10]),"+f"(d[11]),"+f"(d[12]),"+f"(d[13]),"+f"(d[14]),"+f"(d[15]),"+f"(d[16]),"+f"(d[17]),"+f"(d[18]),"+f"(d[19]),"+f"(d[20]),"+f"(d[21]),"+f"(d[22]),"+f"(d[23]),"+f"(d[24]),"+f"(d[25]),"+f"(d[26]),"+f"(d[27]),"+f"(d[28]),"+f"(d[29]),"+f"(d[30]),"+f"(d[31])
    : "l"(ad), "l"(bd));
  } else {
    asm volatile("{\n.reg .pred p;\nsetp.ne.b32 p, 0, 0;\n"
    "wgmma.mma_async.sync.aligned.m64n64k16.f32.bf16.bf16 {%0,%1,%2,%3,%4,%5,%6,%7,%8,%9,%10,%11,%12,%13,%14,%15,%16,%17,%18,%19,%20,%21,%22,%23,%24,%25,%26,%27,%28,%29,%30,%31}, %32, %33, p, 1, 1, 1, 1;\n}"
    : "+f"(d[0]),"+f"(d[1]),"+f"(d[2]),"+f"(d[3]),"+f"(d[4]),"+f"(d[5]),"+f"(d[6]),"+f"(d[7]),"+f"(d[8]),"+f"(d[9]),"+f"(d[10]),"+f"(d[11]),"+f"(d[12]),"+f"(d[13]),"+f"(d[14]),"+f"(d[15]),"+f"(d[16]),"+f"(d[17]),"+f"(d[18]),"+f"(d[19]),"+f"(d[20]),"+f"(d[21]),"+f"(d[22]),"+f"(d[23]),"+f"(d[24]),"+f"(d[25]),"+f"(d[26]),"+f"(d[27]),"+f"(d[28]),"+f"(d[29]),"+f"(d[30]),"+f"(d[31])
    : "l"(ad), "l"(bd));
  }
}

template<int V> struct IC { static constexpr int v = V; };
template<int I, int N, class F> __device__ __forceinline__ void sfor(F&& f) {
    if constexpr (I < N) { f(IC<I>{}); sfor<I + 1, N>(f); }
}

enum { K_QKV = 0, K_H = 1 };

struct Ctx {
    uint32_t tph;
    uint32_t tid_;
    bool pf = false;
    __device__ __forceinline__ uint32_t tid() const { uint32_t r; asm volatile("mov.u32 %0, %1;" : "=r"(r) : "r"(tid_)); return r; }
};
__device__ __forceinline__ void release_slot(const Ctx& c, int slot) { if ((c.tid() & 31) == 0) mbar_arrive(bar(B_EMPTY + slot)); }

__device__ __forceinline__ void turn_wait(const Ctx& c) { asm volatile("bar.sync %0, 256;" :: "r"(4 + (c.tid() >> 7)) : "memory"); }
__device__ __forceinline__ void turn_pass(const Ctx& c) { asm volatile("bar.arrive %0, 256;" :: "r"(5 - (c.tid() >> 7)) : "memory"); }

template<int KIND, class PART, class POST>
__device__ __forceinline__ void run_step(Ctx& c, float* acc, const uint32_t* a, PART&& part, POST&& post, bool last = false) {
    constexpr int NST = (KIND == K_QKV) ? 6 : 3;
    constexpr int KPS = 36 / NST;
    sfor<0, NST>([&](auto ST) {
        constexpr int st = decltype(ST)::v;
        constexpr int slot = st;
        mbar_wait(bar(B_FULL + slot), c.tph);
        uint32_t wgo = 0;
        if constexpr (st == NST - 1) wgo = (c.tid() >> 7) * 512;
        if (KIND == K_H && c.pf) prof(44 + st * 5);
        turn_wait(c);
        if (KIND == K_H && c.pf) prof(45 + st * 5);
        wg_fence();
        sfor<0, KPS>([&](auto KK) {
            constexpr int kk = decltype(KK)::v;
            constexpr int ks = st * KPS + kk;
            constexpr int SD = ks ? 1 : 0;
            if constexpr (KIND == K_QKV) {
                constexpr uint64_t bd = mkdesc(qslot(slot) + kk * 2048, 12288, 1024, 1);
                if constexpr (ks < 32) wg_rs72<SD>(acc, a + ks * 4, bd);
                else wg_ss72<SD>(acc, mkdesc(XB + (ks - 32) * 32, 16, 1024, 1) + wgo, bd);
            } else {
                constexpr uint64_t bd = mkdesc(RING + slot * SLOT + kk * 2048, 16, 1024, 1);
                if constexpr (ks < 32) wg_rs64<SD>(acc, a + ks * 4, bd);
                else wg_ss64<SD>(acc, mkdesc(XB + (ks - 32) * 32, 16, 1024, 1) + wgo, bd);
            }
        });
        wg_commit();
        if (st < NST - 1 || !last || c.tid() < 128) turn_pass(c);
        if (KIND == K_H && c.pf) prof(46 + st * 5);
        part(ST);
        if (KIND == K_H && c.pf) prof(47 + st * 5);
        wg_wait<0>();
        if (KIND == K_H && c.pf) prof(48 + st * 5);
        release_slot(c, slot);
        if constexpr (st == NST - 1) c.tph ^= 1;
        post(ST);
    });
    if constexpr (KIND == K_QKV) reg_fence<36>(acc); else reg_fence<32>(acc);
}

__device__ __forceinline__ float phi(float t) {
    float e = ex2(t * 1.4426950408889634f);
    return (t > 0.f ? t + 1.0f : e) + 1e-6f;
}
__device__ __forceinline__ float gelu_h(float hx) {
    float u = hx * fmaf(hx * hx, 0.2854192650f, 1.5957691216f);
    return fmaf(hx, tanh_ap(u), hx);
}

struct Params {
    const __nv_bfloat16* x;
    const __nv_bfloat16* wqkv;
    const __nv_bfloat16* wo;
    const __nv_bfloat16* w1;
    const __nv_bfloat16* b1;
    const __nv_bfloat16* w2;
    const __nv_bfloat16* b2;
    __nv_bfloat16* out;
};

__global__ void __launch_bounds__(384, 1)
fused_kernel(const __grid_constant__ CUtensorMap tm_x, const __grid_constant__ CUtensorMap tm_w1,
             const __grid_constant__ CUtensorMap tm_w2, const __grid_constant__ CUtensorMap tm_wo,
             const __grid_constant__ CUtensorMap tm_o, const __grid_constant__ CUtensorMap tm_qkv,
             const __grid_constant__ CUtensorMap tm_qkve, const __grid_constant__ CUtensorMap tm_ost, const Params p) {
    extern __shared__ __align__(1024) unsigned char smem_raw[];
    const int tid = threadIdx.x;
    const int bid = blockIdx.x;
    const bool is_main = bid < NMAIN;
    const int j = bid & 7;
    const int m = bid >> 3;

    if (tid == 0) {
        if ((uint32_t)__cvta_generic_to_shared(smem_raw) != SB) __trap();
        for (int i = 0; i < 3; i++) {
            mbar_init(bar(B_FULL + i), 1); mbar_init(bar(B_EMPTY + i), 8);
            mbar_init(bar(B_FULL + 3 + i), 1); mbar_init(bar(B_EMPTY + 3 + i), 8);
        }
        mbar_init(bar(B_KVB), 2); mbar_init(bar(B_INIT), 1);
        mbar_init(bar(B_OFULL), 1); mbar_init(bar(B_O8FULL), 1); mbar_init(bar(B_OFREE), 8); mbar_init(bar(B_O8FREE), 8);
        asm volatile("fence.mbarrier_init.release.cluster;" ::: "memory");
    }
    if (tid == 256 && is_main) {
        for (int i = 0; i < 3; i++) mbar_init(bar(B_XFULL + i), 1);
        asm volatile("fence.mbarrier_init.release.cluster;" ::: "memory");
        fence_async_smem();
        #pragma unroll 1
        for (int kb = 0; kb < 9; kb++) {
            if (kb % 3 == 0) mbar_expect_tx(bar(B_XFULL + kb / 3), 49152);
            tma_2d(HA + kb * 16384, &tm_x, bar(B_XFULL + kb / 3), kb * 64, m * 128);
        }
    }
    if (tid == 288) { asm volatile("prefetch.tensormap [%0];" :: "l"(&tm_qkv) : "memory"); asm volatile("prefetch.tensormap [%0];" :: "l"(&tm_qkve) : "memory"); }
    if (tid >= 40 && tid < 48) sts32(EVC + (tid - 40) * 4, 0);
    if (tid == 48) sts32(EPO + 4, 0);
    __syncthreads();

    if (tid >= 256) {
        asm volatile("setmaxnreg.dec.sync.aligned.u32 24;");
        const int hw = (tid >> 5) - 8, lane = tid & 31;
        uint32_t epoch = 0;
        if (hw > 0) {
            epoch = g_epoch[bid];
            if (hw == 3) {
                if (lane == 0) sts32(EPO, epoch);
                if (is_main) {
                    #pragma unroll 1
                    for (int i = lane; i < 288; i += 32) {
                        uint32_t v = *reinterpret_cast<const uint32_t*>(p.b1 + j * 576 + 2 * i);
                        sts32(B1S + 8 * i, __float_as_uint(0.5f * bf_lo(v))); sts32(B1S + 8 * i + 4, __float_as_uint(0.5f * bf_hi(v)));
                    }
                }
                uint32_t v = *reinterpret_cast<const uint32_t*>(p.b2 + (is_main ? j : 8) * 64 + 2 * lane);
                sts32(B2S + 8 * lane, v << 16); sts32(B2S + 8 * lane + 4, v & 0xffff0000u);
                __syncwarp();
                if (lane == 0) mbar_arrive(bar(B_INIT));
            }
        }
        const uint32_t par = epoch & 1;
        if (hw == 0) {
            if (lane == 0) {
                uint32_t n = 0;
                if (is_main) {
                    #pragma unroll 1
                    for (int u = 0; u < 18; u++) {
                        const int st = u % 6, step = u / 6;
                        const int col = ((step == 2) ? 0 : (step + 1) * 576) + j * 72, row = st * 96;
                        mbar_wait(bar(B_EMPTY + st), (step & 1) ^ (st < 3));
                        mbar_expect_tx(bar(B_FULL + st), 96 * 144);
                        tma_2d(qslot(st), &tm_qkv, bar(B_FULL + st), col, row);
                        tma_2d(qslot(st) + 12288, &tm_qkve, bar(B_FULL + st), col + 64, row);
                    }
                    n = 3;
                }
                const int nsteps = is_main ? 19 : 1;
                #pragma unroll 1
                for (int s = 0; s < nsteps; s++, n++) {
                    const CUtensorMap* tm; int col, row;
                    if (!is_main) { tm = &tm_wo; col = 512; row = 0; }
                    else if (s < 9) { tm = &tm_w1; col = j * 576 + s * 64; row = 0; }
                    else if (s < 18) { tm = &tm_w2; col = (s == 9) ? 512 : (((j + s - 9) & 7) * 64); row = j * 576; }
                    else { tm = &tm_wo; col = j * 64; row = 0; }
                    #pragma unroll 1
                    for (int st = 0; st < 3; st++) {
                        mbar_wait(bar(B_EMPTY + st), (n & 1) ^ 1);
                        mbar_expect_tx(bar(B_FULL + st), SLOT);
                        tma_2d(RING + st * SLOT, tm, bar(B_FULL + st), col, row + st * 192);
                    }
                }
            }
        } else {
            if (is_main) {
                const int t = tid - 288;
                __nanosleep(PF0_NS);
                #pragma unroll 1
                for (int i = t; i < 36 * 6; i += 96) {
                    int r = i / 6, q = i - r * 6;
                    prefetch_l2(reinterpret_cast<const char*>(p.wqkv) + (36 * m + r) * 3456 + (q >> 1) * 1152 + j * 144 + (q & 1) * 128);
                }
                __nanosleep(PF1_NS);
                #pragma unroll 1
                for (int i = t; i < 36 * 9; i += 96) {
                    int r = i / 9, q = i - r * 9;
                    prefetch_l2(reinterpret_cast<const char*>(p.w1) + (36 * m + r) * 9216 + j * 1152 + q * 128);
                    __nanosleep(PF3_NS);
                }
                __nanosleep(PF2_NS);
                #pragma unroll 1
                for (int i = t; i < 36 * 9; i += 96)
                    prefetch_l2(reinterpret_cast<const char*>(p.w2) + (576 * j + 36 * m) * 1152 + i * 128);
                if (t < 41 && (bid * 41 + t) < 5184) prefetch_l2(reinterpret_cast<const char*>(p.wo) + (bid * 41 + t) * 128);
                if (hw != 2) {
                    if (lane == 0) wait_cnt(cnt_kv(j), (epoch + 1) * 16);
                    __syncwarp();
                    const float4* kv = reinterpret_cast<const float4*>(g_kv + (par * 8 + j) * 1440);
                    #pragma unroll 2
                    for (int i = lane + (hw == 1 ? 0 : 32); i < 360; i += 64) {
                        const float4 v = __ldcg(kv + i);
                        const int d = i / 5, e = (i - d * 5) * 4, h = d / 18;
                        const uint32_t base = KVB + (d >> 3) * 128 + (d & 7) * 16;
                        const int n0 = 8 + h * 18 + e;
                        sts32(base + (n0 >> 3) * 1280 + (n0 & 7) * 2, pack_bf16(v.x, v.y));
                        if (e < 16) sts32(base + ((n0 + 2) >> 3) * 1280 + ((n0 + 2) & 7) * 2, pack_bf16(v.z, v.w));
                        else asm volatile("st.shared.u16 [%0], %1;" :: "r"(base + h * 2), "h"((unsigned short)pack_bf16(v.z, 0.f)) : "memory");
                    }
                    fence_async_smem();
                    __syncwarp();
                    if (lane == 0) mbar_arrive(bar(B_KVB));
                }
            }
            if (hw == 1) {
                if (lane == 0) {
                    const int nit = is_main ? 1 : 4;
                    for (int it = 0; it < nit; it++) {
                        const int mt = is_main ? m : ((bid - NMAIN) * 4 + it);
                        const bool wf = is_main || it > 0;
                        const uint32_t fp = is_main ? 0 : ((it - 1) & 1);
                        wait_cnt(cnt_o(mt), (epoch + 1) * 8);
                        fence_async_all();
                        if (wf) mbar_wait(bar(B_OFREE), fp);
                        mbar_expect_tx(bar(B_OFULL), 131072);
                        #pragma unroll 1
                        for (int kb = 0; kb < 8; kb++) tma_2d(HA + kb * 16384, &tm_o, bar(B_OFULL), kb * 64, mt * 128);
                        if (wf) mbar_wait(bar(B_O8FREE), fp);
                        mbar_expect_tx(bar(B_O8FULL), 16384);
                        tma_2d(XB, &tm_o, bar(B_O8FULL), 512, mt * 128);
                    }
                    if (is_main) { wait_cnt(cnt_y(m, j), (epoch + 1) * 7); asm volatile("st.release.cta.shared.u32 [%0], %1;" :: "r"(EPO + 4), "r"(1) : "memory"); }
                }
            } else if (hw == 2) {
                if (!is_main) {
                    if (lane == 0) {
                        #pragma unroll 1
                        for (int it = 0; it < 4; it++) {
                            wait_cnt(cnt_y((bid - NMAIN) * 4 + it, 8), (epoch + 1) * 8);
                            asm volatile("st.release.cta.shared.u32 [%0], %1;" :: "r"(EPO + 4), "r"(it + 1) : "memory");
                        }
                    }
                } else {
                    #pragma unroll 1
                    for (int e = 0; e < 10; e++) {
                        int spin = 0;
                        while (true) {
                            uint32_t v;
                            asm volatile("ld.acquire.cta.shared.u32 %0, [%1];" : "=r"(v) : "r"(EVC + (lane & 7) * 4) : "memory");
                            if (__all_sync(0xffffffffu, v > (uint32_t)e)) break;
                            if (++spin > 20000000) __trap();
                            __nanosleep(SIG_NS);
                        }
                        if (lane == 0) {
                            unsigned int* cp = (e == 0) ? cnt_kv(j) : (e == 1) ? cnt_o(m) : cnt_y(m, e == 2 ? 8 : ((j + e - 2) & 7));
                            if (e == 1) fence_async_all();
                            __threadfence();
                            asm volatile("red.relaxed.gpu.global.add.u32 [%0], 1;" :: "l"(cp) : "memory");
                        }
                        __syncwarp();
                    }
                }
            } else {
                {
                    const int t0 = is_main ? (m * 9 + j) : ((bid - NMAIN) * 4 * 9 + 8);
                    const int nt = is_main ? 1 : 4;
                    for (int t = 0; t < nt; t++) {
                        uint4* z = reinterpret_cast<uint4*>(g_yacc + (size_t)((par ^ 1) * 144 + t0 + t * 9) * YT_BYTES);
                        for (int i = lane; i < YT_BYTES / 16; i += 32) z[i] = make_uint4(0, 0, 0, 0);
                    }
                    if (is_main && m == 0) {
                        float* z = g_kv + ((par ^ 1) * 8 + j) * 1440;
                        for (int i = lane; i < 1440; i += 32) z[i] = 0.f;
                    }
                }
            }
        }
    } else {
        asm volatile("setmaxnreg.inc.sync.aligned.u32 240;");
        prof(0);
        Ctx c; c.tph = 0; c.tid_ = v_tid();
        float hc[32], pv[36];
        if (tid >> 7) turn_pass(c);
        auto event = [&](uint32_t ev) {
            __syncwarp();
            if (((c.tid() & 31) == 0)) asm volatile("st.release.cta.shared.u32 [%0], %1;" :: "r"(EVC + (c.tid() >> 3)), "r"(ev) : "memory");
        };
        auto warp_arrive = [&](uint32_t b) { __syncwarp(); if (((c.tid() & 31) == 0)) mbar_arrive(b); };

        auto lrow_off = [&]() { uint32_t t_ = c.tid(); return HA + ((t_ >> 5) * 16 + (t_ & 15)) * 128 + ((((t_ >> 4) & 1) ^ (t_ & 7)) << 4); };
        auto tail_off = [&]() { uint32_t t_ = c.tid(), g = (t_ >> 2) & 7; return XB + ((t_ >> 5) * 16 + g) * 128 + (g << 4) + (t_ & 3) * 4; };
        if (is_main) {
            uint32_t a[128];
            float rs0, rs1;
            {
                uint32_t tl[16];
                const uint32_t lrow = lrow_off();
                float cs[4][4], sq[8];
                #pragma unroll
                for (int i = 0; i < 4; i++) {
                    #pragma unroll
                    for (int k = 0; k < 4; k++) { cs[i][k] = 0.f; sq[k] = 0.f; sq[k + 4] = 0.f; }
                }
                uint32_t s00 = 0, s11 = 0;
                auto frag = [&](auto KS) -> uint32_t* { constexpr int ks = decltype(KS)::v; return (ks < 32) ? (a + (ks & 31) * 4) : (tl + (ks & 3) * 4); };
                auto sqacc = [&](auto KS) {
                    const uint32_t* f = frag(KS);
                    #pragma unroll
                    for (int r = 0; r < 4; r++) {
                        const uint32_t w = sub_bf16x2(f[r], (r & 1) ? s11 : s00);
                        const float lo = bf_lo(w), hi = bf_hi(w);
                        sq[r] = fmaf(lo, lo, sq[r]); sq[r + 4] = fmaf(hi, hi, sq[r + 4]);
                    }
                };
                sfor<0, 3>([&](auto G) {
                    constexpr int g = decltype(G)::v;
                    mbar_wait(bar(B_XFULL + g), 0);
                    prof(37 + g);
                    sfor<12 * g, 12 * g + 12>([&](auto KS) {
                        constexpr int ks = decltype(KS)::v;
                        ldsm4((lrow ^ ((ks % 4) << 5)) + (ks / 4) * 16384, frag(KS));
                    });
                    warp_arrive(bar(B_EMPTY + 3 + g));
                    sfor<12 * g, 12 * g + 12>([&](auto KS) { mma_ones(cs[decltype(KS)::v & 3], frag(KS)); });
                    if constexpr (g == 0) {
                        const float t0 = (cs[0][0] + cs[1][0] + cs[2][0] + cs[3][0]) * (1.0f / 192.0f), t1 = (cs[0][2] + cs[1][2] + cs[2][2] + cs[3][2]) * (1.0f / 192.0f);
                        s00 = pack_bf16(t0, t0); s11 = pack_bf16(t1, t1);
                    }
                    sfor<12 * g, 12 * g + 12>(sqacc);
                });
                prof(2);
                const float mean0 = (cs[0][0] + cs[1][0] + cs[2][0] + cs[3][0]) * (1.0f / 576.0f), mean1 = (cs[0][2] + cs[1][2] + cs[2][2] + cs[3][2]) * (1.0f / 576.0f);
                const uint32_t m00 = pack_bf16(mean0, mean0), m11 = pack_bf16(mean1, mean1);
                const uint32_t tb = tail_off();
                #pragma unroll
                for (int i = 0; i < 16; i++) sts32((tb ^ ((i >> 1) << 4)) + (i & 1) * 1024, sub_bf16x2(tl[i], (i & 1) ? m11 : m00));
                fence_async_smem();
                #pragma unroll
                for (int i = 0; i < 128; i++) a[i] = sub_bf16x2(a[i], (i & 1) ? m11 : m00);
                {
                    rs0 = (sq[0] + sq[2]) + (sq[4] + sq[6]); rs1 = (sq[1] + sq[3]) + (sq[5] + sq[7]);
                    rs0 += __shfl_xor_sync(0xffffffffu, rs0, 1); rs1 += __shfl_xor_sync(0xffffffffu, rs1, 1);
                    rs0 += __shfl_xor_sync(0xffffffffu, rs0, 2); rs1 += __shfl_xor_sync(0xffffffffu, rs1, 2);
                    const float d0 = mean0 - bf_lo(s00), d1 = mean1 - bf_lo(s11);
                    rs0 = rsqrtf(fmaxf(fmaf(rs0, 1.0f / 576.0f, -d0 * d0), 0.f) + 1e-5f);
                    rs1 = rsqrtf(fmaxf(fmaf(rs1, 1.0f / 576.0f, -d1 * d1), 0.f) + 1e-5f);
                }
                named_bar(1, 256);
            }
            prof(3);
            auto cm_off = [&]() { uint32_t t_ = c.tid(); return (t_ >> 5) * 256 + (t_ & 31) * 4; };
            {
                float qc[36];
                #pragma unroll
                for (int i = 0; i < 36; i++) { qc[i] = 0.f; pv[i] = 0.f; }
                #pragma unroll 1
                for (int s = 0; s < 3; s++) {
                    c.pf = (s == 0);
                    run_step<K_QKV>(c, qc, a, [&](auto ST) {
                        constexpr int st = decltype(ST)::v;
                        if (s > 0) {
                            const uint32_t cm = cm_off();
                            sfor<0, 9>([&](auto B) {
                                constexpr int b = decltype(B)::v;
                                if constexpr ((b * 6) / 9 == st) {
                                    const float v0 = pv[4 * b] * rs0, v1 = pv[4 * b + 1] * rs0, v2 = pv[4 * b + 2] * rs1, v3 = pv[4 * b + 3] * rs1;
                                    if (s == 1) {
                                        sts32(PKT + b * 2048 + cm, pack_bf16(phi(v0), phi(v1)));
                                        sts32(PKT + b * 2048 + cm + 128, pack_bf16(phi(v2), phi(v3)));
                                    } else {
                                        const uint32_t w0 = pack_bf16(v0, v1), w1 = pack_bf16(v2, v3);
                                        if constexpr (b <= 4) { sts32(VT + b * 2048 + cm, w0); sts32(VT + b * 2048 + cm + 128, w1); }
                                        if constexpr (b >= 4) { sts32(VT + (b + 2) * 2048 + cm, w0); sts32(VT + (b + 2) * 2048 + cm + 128, w1); }
                                        if constexpr (b == 0) {
                                            const uint32_t one = (cm & 12) ? 0u : 0x00003F80u;
                                            sts32(VT + 5 * 2048 + cm, one); sts32(VT + 5 * 2048 + cm + 128, one);
                                        }
                                        if constexpr (b == 8) fence_async_smem();
                                    }
                                }
                            });
                        }
                    }, [](auto) {});
                    reg_copy<36>(pv, qc);
                    prof(4 + s);
                }
            }
            {
                #pragma unroll
                for (int i = 0; i < 32; i++) hc[i] = 0.f;
                named_bar(1, 256);
                const uint32_t wgo = ((c.tid() >> 7) * 512);
                wg_fence();
                sfor<0, 8>([&](auto KS) {
                    constexpr int ks = decltype(KS)::v;
                    wg_tt64<(ks ? 1 : 0)>(hc, mkdesc(PKT + ks * 256, 128, 2048, 0) + wgo,
                                          mkdesc(VT + ks * 256, 128, 2048, 0) + wgo + (wgo >> 2));
                });
                wg_commit();
                {
                    const uint32_t z = KVB + c.tid() * 16;
                    sts128(z, 0, 0, 0, 0); sts128(z + 4096, 0, 0, 0, 0); sts128(z + 8192, 0, 0, 0, 0);
                    if (z < KVB + 512) sts128(z + 12288, 0, 0, 0, 0);
                }
                const uint32_t pq = PQT + cm_off() + ((c.tid() >> 7) * 512) * 16;
                sfor<0, 9>([&](auto B) {
                    constexpr int b = decltype(B)::v;
                    sts32(pq + b * 1024, pack_bf16(phi(pv[4 * b] * rs0), phi(pv[4 * b + 1] * rs0)));
                    sts32(pq + b * 1024 + 128, pack_bf16(phi(pv[4 * b + 2] * rs1), phi(pv[4 * b + 3] * rs1)));
                });
                fence_async_smem();
                wg_wait<0>();
                reg_fence<32>(hc);
                reg_copy<24>(pv, hc);
            }
            prof(7);
            rs0 *= 0.5f; rs1 *= 0.5f;
            mbar_wait(bar(B_INIT), 0);
            auto gelun = [&](auto B0, auto B1, uint32_t bofs, uint32_t* w) {
                constexpr int b0 = decltype(B0)::v, nb = decltype(B1)::v - b0;
                float2 bv[nb];
                #pragma unroll
                for (int i = 0; i < nb; i++) bv[i] = lds64f(bofs + (b0 + i) * 32);
                #pragma unroll
                for (int i = 0; i < nb; i++) {
                    const int b = b0 + i;
                    w[2 * i]     = pack_bf16(gelu_h(fmaf(pv[4 * b], rs0, bv[i].x)), gelu_h(fmaf(pv[4 * b + 1], rs0, bv[i].y)));
                    w[2 * i + 1] = pack_bf16(gelu_h(fmaf(pv[4 * b + 2], rs1, bv[i].x)), gelu_h(fmaf(pv[4 * b + 3], rs1, bv[i].y)));
                }
            };
            auto spill_off = [&]() { uint32_t t_ = c.tid(); return HA + (t_ >> 7) * 8192 + (t_ & 127) * 8; };
            auto reload = [&](auto S0, auto S1) {
                const uint32_t spill = spill_off();
                sfor<decltype(S0)::v * 8, decltype(S1)::v * 8>([&](auto Q) {
                    constexpr int q = decltype(Q)::v;
                    lds64(spill + (q / 8) * 16384 + (q % 8) * 1024, a + q * 2);
                });
            };
            #pragma unroll 1
            for (int idx = 0; idx < 18; idx++) {
                run_step<K_H>(c, hc, a, [&](auto ST) {
                    constexpr int st = decltype(ST)::v;
                    if (idx >= 10) {
                        if constexpr (st < 2) {
                            const uint32_t b_ = v_bid();
                            const uint32_t chunk = (idx == 10) ? 8 : ((b_ + idx - 10) & 7);
                            unsigned char* yp = g_yacc + ((v_epoch() & 1) * 144 + (b_ >> 3) * 9 + chunk) * YT_BYTES + c.tid() * 16;
                            sfor<2 * st, 2 * st + 2>([&](auto Q) {
                                constexpr int q = decltype(Q)::v;
                                asm volatile("red.global.add.noftz.v4.bf16x2 [%0], {%1,%2,%3,%4};" :: "l"(yp + q * 4096),
                                             "r"(pack_bf16(pv[8 * q], pv[8 * q + 1])), "r"(pack_bf16(pv[8 * q + 2], pv[8 * q + 3])),
                                             "r"(pack_bf16(pv[8 * q + 4], pv[8 * q + 5])), "r"(pack_bf16(pv[8 * q + 6], pv[8 * q + 7])) : "memory");
                            });
                            if constexpr (st == 1) event(idx - 7);
                        }
                    } else if (idx >= 1) {
                        const uint32_t bofs = B1S + (idx - 1) * 256 + (c.tid() & 3) * 8;
                        if (idx < 9) {
                            if constexpr (st == 0) {
                                if (idx == OSTEP_AT + 1) {
                                    if ((c.tid() & 31) == 0) asm volatile("cp.async.bulk.wait_group 0;" ::: "memory");
                                    event(2);
                                }
                            }
                            const uint32_t spill = spill_off() + (idx - 1) * 16384;
                            constexpr int b0 = st * 3, b1 = (st == 2 ? 8 : st * 3 + 3);
                            uint32_t w[6];
                            gelun(IC<b0>{}, IC<b1>{}, bofs, w);
                            #pragma unroll
                            for (int b = b0; b < b1; b++) sts64(spill + b * 1024, w[2 * (b - b0)], w[2 * (b - b0) + 1]);
                        } else {
                            if constexpr (st < 2) {
                                const uint32_t tb = tail_off();
                                uint32_t w[8];
                                gelun(IC<st * 4>{}, IC<st * 4 + 4>{}, bofs, w);
                                #pragma unroll
                                for (int i = 0; i < 4; i++) { sts32(tb ^ ((st * 4 + i) << 4), w[2 * i]); sts32((tb ^ ((st * 4 + i) << 4)) + 1024, w[2 * i + 1]); }
                            }
                            if constexpr (st == 1) { fence_async_smem(); named_bar(2 + (c.tid() >> 7), 128); }
                        }
                    } else {
                        if constexpr (st < 2) {
                            constexpr int hf = st;
                            const int t_ = c.tid(), wg = t_ >> 7, t = t_ & 3;
                            float* dst = g_kv + ((v_epoch() & 1) * 8 + (v_bid() & 7)) * 1440;
                            const int d = wg * 32 + ((t_ >> 5) & 3) * 16 + ((t_ >> 2) & 7) + hf * 8;
                            const bool dv = wg ? (d >= 36 && d < 72) : (d < 36);
                            const int e00 = wg * 24 + 2 * t - (d / 18) * 18;
                            float* dp = dst + d * 20 + e00;
                            #pragma unroll
                            for (int i = 0; i < 6; i++) {
                                const int e = e00 + i * 8;
                                const bool blk = wg ? (i >= 1) : (i <= 4);
                                if (dv && blk && e >= 0 && e < 18)
                                    asm volatile("red.global.add.v2.f32 [%0], {%1,%2};" :: "l"(dp + i * 8), "f"(pv[4 * i + 2 * hf]), "f"(pv[4 * i + 2 * hf + 1]) : "memory");
                            }
                            if (dv && t == 0) atomicAdd(dst + d * 20 + 18, wg ? pv[2 * hf] : pv[20 + 2 * hf]);
                            if constexpr (st == 1) event(1);
                        }
                    }
                }, [&](auto ST) {
                    constexpr int st = decltype(ST)::v;
                    if (idx == 8) {
                        reload(IC<3 * st>{}, IC<(st == 2 ? 8 : 3 * st + 3)>{});
                        if constexpr (st == 2) warp_arrive(bar(B_OFREE));
                    }
                });
                reg_copy<32>(pv, hc);
                prof(8 + idx);
                if (idx == OSTEP_AT) {
                    mbar_wait(bar(B_KVB), 0);
                    prof(34);
                    const uint32_t pqo = (c.tid() >> 7) * 576;
                    const int t_ = c.tid(), b_ = v_bid(), t = t_ & 3, l4 = t_ & 28;
                    const uint32_t op = OST + ((t_ >> 5) * 16 + ((t_ >> 2) & 7)) * 144 + t * 4;
                    float r3[2];
                    sfor<0, 2>([&](auto PS) {
                        constexpr int ps = decltype(PS)::v;
                        wg_fence();
                        sfor<0, 5>([&](auto KS) {
                            constexpr int ks = decltype(KS)::v;
                            wg_ss64<(ks ? 1 : 0)>(hc, mkdesc(PQT + ks * 2048, ks == 4 ? 0 : 1024, 128, 0) + pqo, mkdesc(KVB + ps * 8 * 1280 + ks * 256, 128, 1280, 0));
                        });
                        wg_commit();
                        wg_wait<0>();
                        reg_fence<32>(hc);
                        #pragma unroll
                        for (int hf = 0; hf < 2; hf++) {
                            if constexpr (ps == 0) {
                                float r[4];
                                r[0] = rcp(__shfl_sync(0xffffffffu, hc[2 * hf], l4) + 1e-6f);
                                r[1] = rcp(__shfl_sync(0xffffffffu, hc[1 + 2 * hf], l4) + 1e-6f);
                                r[2] = rcp(__shfl_sync(0xffffffffu, hc[2 * hf], l4 + 1) + 1e-6f);
                                r[3] = rcp(__shfl_sync(0xffffffffu, hc[1 + 2 * hf], l4 + 1) + 1e-6f);
                                r3[hf] = r[3];
                                #pragma unroll
                                for (int i = 0; i < 7; i++) {
                                    float rr = (i < 2) ? r[0] : (i == 2) ? (t < 1 ? r[0] : r[1]) : (i == 3) ? r[1] : (i == 4) ? (t < 2 ? r[1] : r[2])
                                             : (i == 5) ? r[2] : (t < 3 ? r[2] : r[3]);
                                    sts32(op + hf * 8 * 144 + i * 16, pack_bf16(hc[4 * i + 4 + 2 * hf] * rr, hc[4 * i + 5 + 2 * hf] * rr));
                                }
                            } else {
                                #pragma unroll
                                for (int i = 0; i < 2; i++)
                                    sts32(op + hf * 8 * 144 + 112 + i * 16, pack_bf16(hc[4 * i + 2 * hf] * r3[hf], hc[4 * i + 1 + 2 * hf] * r3[hf]));
                            }
                        }
                    });
                    fence_async_smem();
                    __syncwarp();
                    if ((t_ & 31) == 0) {
                        asm volatile("cp.async.bulk.tensor.2d.global.shared::cta.bulk_group [%0, {%2, %3}], [%1];"
                                     :: "l"(&tm_ost), "r"(OST + (t_ >> 5) * 2304), "r"((b_ & 7) * 72), "r"((b_ >> 3) * 128 + (t_ >> 5) * 16) : "memory");
                        asm volatile("cp.async.bulk.commit_group;" ::: "memory");
                    }
                }
            }
        }
        if (is_main) warp_arrive(bar(B_O8FREE));
        else {
            mbar_wait(bar(B_INIT), 0);
            #pragma unroll
            for (int i = 0; i < 32; i++) { asm volatile("mov.b32 %0, 0;" : "=f"(hc[i])); asm volatile("mov.b32 %0, 0;" : "=f"(pv[i])); }
        }
        auto add_b2 = [&]() {
            #pragma unroll
            for (int b = 0; b < 8; b++) {
                float2 bv = lds64f(B2S + b * 32 + (c.tid() & 3) * 8);
                pv[4 * b] += bv.x; pv[4 * b + 1] += bv.y; pv[4 * b + 2] += bv.x; pv[4 * b + 3] += bv.y;
            }
        };
        auto load_xy = [&](int ftile, int nrdy, uint32_t* xr, uint32_t* yv) {
            const int mt = ftile / 9, ch = ftile - mt * 9;
            const uint32_t t_ = c.tid();
            const __nv_bfloat16* xp = p.x + (size_t)(mt * 128 + (t_ >> 5) * 16 + ((t_ >> 2) & 7)) * DM + ch * 64 + 2 * (t_ & 3);
            #pragma unroll
            for (int i = 0; i < 8; i++) {
                asm volatile("ld.global.nc.u32 %0, [%1];" : "=r"(xr[2 * i]) : "l"(xp + i * 8));
                asm volatile("ld.global.nc.u32 %0, [%1];" : "=r"(xr[2 * i + 1]) : "l"(xp + 8 * DM + i * 8));
            }
            prof(26);
            smem_wait_gt(EPO + 4, nrdy);
            prof(27);
            const unsigned char* yp = g_yacc + ((v_epoch() & 1) * 144 + ftile) * YT_BYTES + t_ * 16;
            #pragma unroll
            for (int q = 0; q < YT_BYTES / 4096; q++)
                asm volatile("ld.global.cg.v4.u32 {%0,%1,%2,%3}, [%4];" : "=r"(yv[4 * q]), "=r"(yv[4 * q + 1]), "=r"(yv[4 * q + 2]), "=r"(yv[4 * q + 3]) : "l"(yp + q * 4096) : "memory");
        };
        auto gate = [&](const uint32_t* yv) {
            #pragma unroll
            for (int i = 0; i < 16; i++) { pv[2 * i] += bf_lo(yv[i]); pv[2 * i + 1] += bf_hi(yv[i]); }
            #pragma unroll
            for (int i = 0; i < 32; i++) { const float h = 0.5f * pv[i]; pv[i] = fmaf(h, tanh_ap(h), h); }
        };
        auto store_out = [&](int ftile, const uint32_t* xr) {
            const int mt = ftile / 9, ch = ftile - mt * 9;
            const uint32_t t_ = c.tid();
            const bool odd = t_ & 1;
            __nv_bfloat16* op = p.out + (size_t)(mt * 128 + (t_ >> 5) * 16 + ((t_ >> 2) & 7)) * DM + ch * 64 + (t_ & 2) * 2 + (t_ & 1) * 8;
            #pragma unroll
            for (int b = 0; b < 8; b += 2) {
                #pragma unroll
                for (int hf = 0; hf < 2; hf++) {
                    const int i0 = 4 * b + 2 * hf, i1 = i0 + 4;
                    const uint32_t w0 = pack_bf16(fmaf(hc[i0], pv[i0], bf_lo(xr[2 * b + hf])), fmaf(hc[i0 + 1], pv[i0 + 1], bf_hi(xr[2 * b + hf])));
                    const uint32_t w1 = pack_bf16(fmaf(hc[i1], pv[i1], bf_lo(xr[2 * b + 2 + hf])), fmaf(hc[i1 + 1], pv[i1 + 1], bf_hi(xr[2 * b + 2 + hf])));
                    const uint32_t r = __shfl_xor_sync(0xffffffffu, odd ? w0 : w1, 1);
                    *reinterpret_cast<uint2*>(op + hf * 8 * DM + b * 8) = odd ? make_uint2(r, w1) : make_uint2(w0, r);
                }
            }
        };
        const int njob = is_main ? 1 : 4;
        #pragma unroll 1
        for (int job = 0; job < njob; job++) {
            const uint32_t jpar = job & 1;
            const uint32_t b_ = v_bid();
            const bool mainf = b_ < NMAIN;
            const int ftile = (b_ >> 3) * 9 + (b_ & 7);
            uint32_t oa[128];
            {
                mbar_wait(bar(B_OFULL), jpar);
                const uint32_t lrow = lrow_off();
                sfor<0, 32>([&](auto KS) {
                    constexpr int ks = decltype(KS)::v;
                    ldsm4((lrow ^ ((ks % 4) << 5)) + (ks / 4) * 16384, oa + ks * 4);
                });
                warp_arrive(bar(B_OFREE));
                if (job) c.tph ^= 1;
            }
            c.pf = false;
            run_step<K_H>(c, hc, oa, [&](auto ST) {
                constexpr int st = decltype(ST)::v;
                if (mainf) {
                    if constexpr (st == 0) add_b2();
                    else if constexpr (st == 1) load_xy(ftile, 0, oa, oa + 16);
                    else { prof(28); gate(oa + 16); prof(29); }
                }
                if constexpr (st == 1) mbar_wait(bar(B_O8FULL), jpar);
            }, [](auto) {}, job == njob - 1);
            prof(30);
            if (mainf) {
                store_out(ftile, oa);
            } else {
                warp_arrive(bar(B_O8FREE));
                uint4* sp = reinterpret_cast<uint4*>(g_s8) + ((b_ - NMAIN) * 4 + job) * 1024 + c.tid();
                #pragma unroll
                for (int q = 0; q < 4; q++)
                    sp[q * 256] = make_uint4(pack_bf16(hc[8 * q], hc[8 * q + 1]), pack_bf16(hc[8 * q + 2], hc[8 * q + 3]),
                                             pack_bf16(hc[8 * q + 4], hc[8 * q + 5]), pack_bf16(hc[8 * q + 6], hc[8 * q + 7]));
                prof(8 + job);
            }
        }
        if (!is_main) {
            #pragma unroll 1
            for (int job = 0; job < 4; job++) {
                const int tile = (v_bid() - NMAIN) * 4 + job;
                uint32_t xr[16], yv[YT_BYTES / 1024];
                const uint4* sp = reinterpret_cast<const uint4*>(g_s8) + tile * 1024 + c.tid();
                #pragma unroll
                for (int q = 0; q < 4; q++) {
                    const uint4 u = __ldcg(sp + q * 256);
                    hc[8 * q] = bf_lo(u.x); hc[8 * q + 1] = bf_hi(u.x); hc[8 * q + 2] = bf_lo(u.y); hc[8 * q + 3] = bf_hi(u.y);
                    hc[8 * q + 4] = bf_lo(u.z); hc[8 * q + 5] = bf_hi(u.z); hc[8 * q + 6] = bf_lo(u.w); hc[8 * q + 7] = bf_hi(u.w);
                }
                #pragma unroll
                for (int i = 0; i < 32; i++) pv[i] = 0.f;
                add_b2();
                load_xy(tile * 9 + 8, job, xr, yv);
                gate(yv);
                store_out(tile * 9 + 8, xr);
                prof(12 + job);
            }
        }
        prof(40);
        if (c.tid() == 0) g_epoch[v_bid()] = v_epoch() + 1;
    }
}

typedef CUresult (*EncodeFn)(CUtensorMap*, CUtensorMapDataType, cuuint32_t, void*, const cuuint64_t*, const cuuint64_t*,
                             const cuuint32_t*, const cuuint32_t*, CUtensorMapInterleave, CUtensorMapSwizzle,
                             CUtensorMapL2promotion, CUtensorMapFloatOOBfill);

void make_map(EncodeFn enc, CUtensorMap* tm, const void* base, int rows, int cols, int box_rows, int box_cols = 64, bool swz = true) {
    cuuint64_t gdim[2] = {(cuuint64_t)cols, (cuuint64_t)rows};
    cuuint64_t gstr[1] = {(cuuint64_t)cols * 2};
    cuuint32_t box[2] = {(cuuint32_t)box_cols, (cuuint32_t)box_rows};
    cuuint32_t estr[2] = {1, 1};
    enc(tm, CU_TENSOR_MAP_DATA_TYPE_BFLOAT16, 2, const_cast<void*>(base), gdim, gstr, box, estr, CU_TENSOR_MAP_INTERLEAVE_NONE,
        swz ? CU_TENSOR_MAP_SWIZZLE_128B : CU_TENSOR_MAP_SWIZZLE_NONE, CU_TENSOR_MAP_L2_PROMOTION_L2_128B, CU_TENSOR_MAP_FLOAT_OOB_FILL_NONE);
}

}

extern "C" void kernel_launch(void* const* d_in, const int* in_sizes, int n_in, void* d_out, int out_size) {
    static EncodeFn enc = nullptr;
    static void* o_ptr = nullptr;
    if (!enc) {
        void* fn = nullptr;
        cudaDriverEntryPointQueryResult qr;
        cudaGetDriverEntryPoint("cuTensorMapEncodeTiled", &fn, cudaEnableDefault, &qr);
        enc = (EncodeFn)fn;
        cudaGetSymbolAddress(&o_ptr, g_o);
        cudaFuncSetAttribute(fused_kernel, cudaFuncAttributeMaxDynamicSharedMemorySize, SMEM_BYTES);
    }
    Params p;
    p.x = (const __nv_bfloat16*)d_in[0];
    p.wqkv = (const __nv_bfloat16*)d_in[1];
    p.wo = (const __nv_bfloat16*)d_in[2];
    p.w1 = (const __nv_bfloat16*)d_in[4];
    p.b1 = (const __nv_bfloat16*)d_in[5];
    p.w2 = (const __nv_bfloat16*)d_in[6];
    p.b2 = (const __nv_bfloat16*)d_in[7];
    p.out = (__nv_bfloat16*)d_out;
    CUtensorMap tm_x, tm_w1, tm_w2, tm_wo, tm_o, tm_qkv, tm_qkve, tm_ost;
    make_map(enc, &tm_ost, o_ptr, SEQ, DM, 16, 72, false);
    make_map(enc, &tm_qkv, p.wqkv, DM, 3 * DM, 96);
    make_map(enc, &tm_qkve, p.wqkv, DM, 3 * DM, 96, 8);
    make_map(enc, &tm_x, p.x, SEQ, DM, 128);
    make_map(enc, &tm_w1, p.w1, DM, FF, 192);
    make_map(enc, &tm_w2, p.w2, FF, DM, 192);
    make_map(enc, &tm_wo, p.wo, DM, DM, 192);
    make_map(enc, &tm_o, o_ptr, SEQ, DM, 128);
    fused_kernel<<<NMAIN + NAUX, 384, SMEM_BYTES>>>(tm_x, tm_w1, tm_w2, tm_wo, tm_o, tm_qkv, tm_qkve, tm_ost, p);
}
```
